```python
import torch

def _softmax(x, axis=-1):
    return torch.softmax(x, dim=axis)
def _gelu(x):
    return torch.nn.functional.gelu(x, approximate="tanh")
def _silu(x):
    return torch.nn.functional.silu(x)
def _sigmoid(x):
    return torch.sigmoid(x)
def _layernorm(x, axis=-1, eps=1e-5):
    m = x.mean(dim=axis, keepdim=True)
    v = x.var(dim=axis, keepdim=True, unbiased=False)
    return (x - m) / torch.sqrt(v + eps)
def _scatter_add(tgt, idx, src, axis=0):
    return tgt.clone().index_add_(axis, idx, src)
def _segment_sum(src, seg, n):
    out = torch.zeros((n,) + src.shape[1:], dtype=src.dtype)
    return out.index_add_(0, seg, src)
def _pad(x, pw):
    flat = tuple(v for pair in reversed(pw) for v in pair)
    return torch.nn.functional.pad(x, flat)

kernel_name = 'standalone__window_attn_swin_v2__vision'

def setup_inputs():

    _w = (lambda a: (lambda t: t.to(torch.bfloat16) if t.is_floating_point() else t)(torch.as_tensor(a)))
    win = 8
    H = W = (384 // win) * win
    C = 96
    nh = 4
    shift = win // 2
    coords = torch.stack(torch.meshgrid(torch.arange(win), torch.arange(win), indexing="ij"), -1).reshape(-1, 2)
    rel = coords[:, None, :] - coords[None, :, :]
    rel_idx = ((rel[..., 0] + win - 1) * (2 * win - 1) + (rel[..., 1] + win - 1)).to(torch.int64)
    tab = torch.stack(torch.meshgrid(torch.arange(1 - win, win), torch.arange(1 - win, win), indexing="ij"), -1).reshape(-1, 2).to(float)
    tab = (lambda _x: torch.sign(torch.as_tensor(_x)))(tab) * (lambda _x: torch.log1p(torch.as_tensor(_x)))(torch.abs(tab))
    img = torch.zeros((H, W), dtype=torch.int64)
    cnt = 0
    for hs in (slice(0, H - win), slice(H - win, H - shift), slice(H - shift, H)):
        for ws in (slice(0, W - win), slice(W - win, W - shift), slice(W - shift, W)):
            img[hs, ws] = cnt; cnt += 1
    mw = img.reshape(H // win, win, W // win, win).permute(0, 2, 1, 3).reshape(-1, win * win)
    mask = (mw[:, :, None] != mw[:, None, :]).to(float) * (-100.0)
    return {
        "x": _w((lambda *s: torch.randn(*s, dtype=torch.bfloat16) * 0.05)(1, H, W, C)),
        "wqkv": _w((lambda *s: torch.randn(*s, dtype=torch.bfloat16) * 1.6)(C, 3 * C)),
        "wo": _w((lambda *s: torch.randn(*s, dtype=torch.bfloat16) * 0.05)(C, C)),
        "logit_scale": _w((lambda *s: torch.randn(*s, dtype=torch.bfloat16) * 1.6)(nh)),
        "cpb_w1": _w((lambda *s: torch.randn(*s, dtype=torch.bfloat16) * 0.8)(2, 4 * nh)),
        "cpb_w2": _w((lambda *s: torch.randn(*s, dtype=torch.bfloat16) * 0.8)(4 * nh, nh)),
        "rel_coords": _w(tab),
        "rel_idx": _w(rel_idx),
        "attn_mask": _w(mask),
    }

def reference(x, wqkv, wo, logit_scale, cpb_w1, cpb_w2, rel_coords, rel_idx, attn_mask):
    B, H, W, C = x.shape
    win = 8
    nh = 4
    hd = C // nh
    shift = win // 2
    ww = win * win
    nH, nW = H // win, W // win
    xs = torch.roll(x, (-shift, -shift), (1, 2))
    xw = (lambda x, *d: x.permute(*d))(xs.reshape(B, nH, win, nW, win, C), 0, 1, 3, 2, 4, 5).reshape(B * nH * nW, ww, C)
    qkv = (lambda x, *d: x.permute(*d))((xw @ wqkv).reshape(B * nH * nW, ww, 3, nh, hd), 2, 0, 3, 1, 4)
    q, k, v = qkv[0], qkv[1], qkv[2]
    qn = q * (torch.einsum("bhqd,bhqd->bhq", q, q)[..., None] + 1e-12) ** -0.5
    kn = k * (torch.einsum("bhkd,bhkd->bhk", k, k)[..., None] + 1e-12) ** -0.5
    logits = torch.einsum("bhqd,bhkd->bhqk", qn, kn)
    tau = torch.exp(torch.clip(logit_scale, -100.0, 4.6052))
    logits = logits * tau[None, :, None, None]
    hcpb = rel_coords @ cpb_w1
    hcpb = torch.where(hcpb > 0, hcpb, hcpb * 0)
    bias_tab = 16.0 * _sigmoid(hcpb @ cpb_w2)
    bias = (lambda x, *d: x.permute(*d))(bias_tab[rel_idx], 2, 0, 1)
    logits = logits.reshape(B, nH * nW, nh, ww, ww) + bias[None, None, :, :, :] + attn_mask[None, :, None, :, :]
    p = _softmax(logits.reshape(B * nH * nW, nh, ww, ww), axis=-1)
    o = (lambda x, *d: x.permute(*d))(torch.einsum("bhqk,bhkd->bhqd", p, v), 0, 2, 1, 3).reshape(B * nH * nW, ww, C) @ wo
    o = (lambda x, *d: x.permute(*d))(o.reshape(B, nH, nW, win, win, C), 0, 1, 3, 2, 4, 5).reshape(B, H, W, C)
    o = torch.roll(o, (shift, shift), (1, 2))
    return _layernorm(o, axis=-1)
```

```cpp
#include <cuda_runtime.h>
#include <cuda_bf16.h>
#include <stdint.h>

namespace {

constexpr int IMG   = 384;
constexpr int NWX   = 48;
constexpr int NWIN  = NWX * NWX;
constexpr int PIXB  = 192;
constexpr int ROWB  = IMG * PIXB;
constexpr float LOG2E = 1.4426950408889634f;

constexpr int SM_W    = 0;
constexpr int SM_WO   = SM_W + 36 * 1536;
constexpr int SM_EB   = SM_WO + 12 * 1536;
constexpr int SM_WG   = SM_EB + 32768;
constexpr int WG_X    = 0;
constexpr int WG_K    = 12288;
constexpr int WG_V    = WG_K + 14336;
constexpr int WG_SZ   = WG_V + 14336;
constexpr int SM_TAB  = SM_WG + WG_V + 4096;
constexpr int SM_MISC = SM_WG + 3 * WG_SZ;
constexpr int SM_TOTAL = SM_MISC + 32;

template <int SD> __device__ __forceinline__ void wgmma_ss_n96_t1(float (&d)[48], uint32_t da, uint32_t db) {
  if constexpr (SD) {
    asm volatile("{\n.reg .pred p;\n.reg .b64 da, db;\nsetp.ne.b32 p, 1, 0;\nmov.b64 da, {%48, 96};\nmov.b64 db, {%49, 96};\n"
      "wgmma.mma_async.sync.aligned.m64n96k16.f32.bf16.bf16 {%0, %1, %2, %3, %4, %5, %6, %7, %8, %9, %10, %11, %12, %13, %14, %15, %16, %17, %18, %19, %20, %21, %22, %23, %24, %25, %26, %27, %28, %29, %30, %31, %32, %33, %34, %35, %36, %37, %38, %39, %40, %41, %42, %43, %44, %45, %46, %47}, da, db, p, 1, 1, 0, 1;\n}\n"
      : "+f"(d[0]), "+f"(d[1]), "+f"(d[2]), "+f"(d[3]), "+f"(d[4]), "+f"(d[5]), "+f"(d[6]), "+f"(d[7]), "+f"(d[8]), "+f"(d[9]), "+f"(d[10]), "+f"(d[11]), "+f"(d[12]), "+f"(d[13]), "+f"(d[14]), "+f"(d[15]), "+f"(d[16]), "+f"(d[17]), "+f"(d[18]), "+f"(d[19]), "+f"(d[20]), "+f"(d[21]), "+f"(d[22]), "+f"(d[23]), "+f"(d[24]), "+f"(d[25]), "+f"(d[26]), "+f"(d[27]), "+f"(d[28]), "+f"(d[29]), "+f"(d[30]), "+f"(d[31]), "+f"(d[32]), "+f"(d[33]), "+f"(d[34]), "+f"(d[35]), "+f"(d[36]), "+f"(d[37]), "+f"(d[38]), "+f"(d[39]), "+f"(d[40]), "+f"(d[41]), "+f"(d[42]), "+f"(d[43]), "+f"(d[44]), "+f"(d[45]), "+f"(d[46]), "+f"(d[47])
      : "r"(da), "r"(db));
  } else {
    asm volatile("{\n.reg .pred p;\n.reg .b64 da, db;\nsetp.ne.b32 p, 0, 0;\nmov.b64 da, {%48, 96};\nmov.b64 db, {%49, 96};\n"
      "wgmma.mma_async.sync.aligned.m64n96k16.f32.bf16.bf16 {%0, %1, %2, %3, %4, %5, %6, %7, %8, %9, %10, %11, %12, %13, %14, %15, %16, %17, %18, %19, %20, %21, %22, %23, %24, %25, %26, %27, %28, %29, %30, %31, %32, %33, %34, %35, %36, %37, %38, %39, %40, %41, %42, %43, %44, %45, %46, %47}, da, db, p, 1, 1, 0, 1;\n}\n"
      : "=f"(d[0]), "=f"(d[1]), "=f"(d[2]), "=f"(d[3]), "=f"(d[4]), "=f"(d[5]), "=f"(d[6]), "=f"(d[7]), "=f"(d[8]), "=f"(d[9]), "=f"(d[10]), "=f"(d[11]), "=f"(d[12]), "=f"(d[13]), "=f"(d[14]), "=f"(d[15]), "=f"(d[16]), "=f"(d[17]), "=f"(d[18]), "=f"(d[19]), "=f"(d[20]), "=f"(d[21]), "=f"(d[22]), "=f"(d[23]), "=f"(d[24]), "=f"(d[25]), "=f"(d[26]), "=f"(d[27]), "=f"(d[28]), "=f"(d[29]), "=f"(d[30]), "=f"(d[31]), "=f"(d[32]), "=f"(d[33]), "=f"(d[34]), "=f"(d[35]), "=f"(d[36]), "=f"(d[37]), "=f"(d[38]), "=f"(d[39]), "=f"(d[40]), "=f"(d[41]), "=f"(d[42]), "=f"(d[43]), "=f"(d[44]), "=f"(d[45]), "=f"(d[46]), "=f"(d[47])
      : "r"(da), "r"(db));
  }
}
template <int SD> __device__ __forceinline__ void wgmma_rs_n96_t1(float (&d)[48], uint32_t a0, uint32_t a1, uint32_t a2, uint32_t a3, uint32_t db) {
  if constexpr (SD) {
    asm volatile("{\n.reg .pred p;\n.reg .b64 da, db;\nsetp.ne.b32 p, 1, 0;\nmov.b64 db, {%52, 96};\n"
      "wgmma.mma_async.sync.aligned.m64n96k16.f32.bf16.bf16 {%0, %1, %2, %3, %4, %5, %6, %7, %8, %9, %10, %11, %12, %13, %14, %15, %16, %17, %18, %19, %20, %21, %22, %23, %24, %25, %26, %27, %28, %29, %30, %31, %32, %33, %34, %35, %36, %37, %38, %39, %40, %41, %42, %43, %44, %45, %46, %47}, {%48, %49, %50, %51}, db, p, 1, 1, 1;\n}\n"
      : "+f"(d[0]), "+f"(d[1]), "+f"(d[2]), "+f"(d[3]), "+f"(d[4]), "+f"(d[5]), "+f"(d[6]), "+f"(d[7]), "+f"(d[8]), "+f"(d[9]), "+f"(d[10]), "+f"(d[11]), "+f"(d[12]), "+f"(d[13]), "+f"(d[14]), "+f"(d[15]), "+f"(d[16]), "+f"(d[17]), "+f"(d[18]), "+f"(d[19]), "+f"(d[20]), "+f"(d[21]), "+f"(d[22]), "+f"(d[23]), "+f"(d[24]), "+f"(d[25]), "+f"(d[26]), "+f"(d[27]), "+f"(d[28]), "+f"(d[29]), "+f"(d[30]), "+f"(d[31]), "+f"(d[32]), "+f"(d[33]), "+f"(d[34]), "+f"(d[35]), "+f"(d[36]), "+f"(d[37]), "+f"(d[38]), "+f"(d[39]), "+f"(d[40]), "+f"(d[41]), "+f"(d[42]), "+f"(d[43]), "+f"(d[44]), "+f"(d[45]), "+f"(d[46]), "+f"(d[47])
      : "r"(a0), "r"(a1), "r"(a2), "r"(a3), "r"(db));
  } else {
    asm volatile("{\n.reg .pred p;\n.reg .b64 da, db;\nsetp.ne.b32 p, 0, 0;\nmov.b64 db, {%52, 96};\n"
      "wgmma.mma_async.sync.aligned.m64n96k16.f32.bf16.bf16 {%0, %1, %2, %3, %4, %5, %6, %7, %8, %9, %10, %11, %12, %13, %14, %15, %16, %17, %18, %19, %20, %21, %22, %23, %24, %25, %26, %27, %28, %29, %30, %31, %32, %33, %34, %35, %36, %37, %38, %39, %40, %41, %42, %43, %44, %45, %46, %47}, {%48, %49, %50, %51}, db, p, 1, 1, 1;\n}\n"
      : "=f"(d[0]), "=f"(d[1]), "=f"(d[2]), "=f"(d[3]), "=f"(d[4]), "=f"(d[5]), "=f"(d[6]), "=f"(d[7]), "=f"(d[8]), "=f"(d[9]), "=f"(d[10]), "=f"(d[11]), "=f"(d[12]), "=f"(d[13]), "=f"(d[14]), "=f"(d[15]), "=f"(d[16]), "=f"(d[17]), "=f"(d[18]), "=f"(d[19]), "=f"(d[20]), "=f"(d[21]), "=f"(d[22]), "=f"(d[23]), "=f"(d[24]), "=f"(d[25]), "=f"(d[26]), "=f"(d[27]), "=f"(d[28]), "=f"(d[29]), "=f"(d[30]), "=f"(d[31]), "=f"(d[32]), "=f"(d[33]), "=f"(d[34]), "=f"(d[35]), "=f"(d[36]), "=f"(d[37]), "=f"(d[38]), "=f"(d[39]), "=f"(d[40]), "=f"(d[41]), "=f"(d[42]), "=f"(d[43]), "=f"(d[44]), "=f"(d[45]), "=f"(d[46]), "=f"(d[47])
      : "r"(a0), "r"(a1), "r"(a2), "r"(a3), "r"(db));
  }
}
template <int SD> __device__ __forceinline__ void wgmma_rs_n64_t0(float (&d)[32], uint32_t a0, uint32_t a1, uint32_t a2, uint32_t a3, uint32_t db) {
  if constexpr (SD) {
    asm volatile("{\n.reg .pred p;\n.reg .b64 da, db;\nsetp.ne.b32 p, 1, 0;\nmov.b64 db, {%36, 112};\n"
      "wgmma.mma_async.sync.aligned.m64n64k16.f32.bf16.bf16 {%0, %1, %2, %3, %4, %5, %6, %7, %8, %9, %10, %11, %12, %13, %14, %15, %16, %17, %18, %19, %20, %21, %22, %23, %24, %25, %26, %27, %28, %29, %30, %31}, {%32, %33, %34, %35}, db, p, 1, 1, 0;\n}\n"
      : "+f"(d[0]), "+f"(d[1]), "+f"(d[2]), "+f"(d[3]), "+f"(d[4]), "+f"(d[5]), "+f"(d[6]), "+f"(d[7]), "+f"(d[8]), "+f"(d[9]), "+f"(d[10]), "+f"(d[11]), "+f"(d[12]), "+f"(d[13]), "+f"(d[14]), "+f"(d[15]), "+f"(d[16]), "+f"(d[17]), "+f"(d[18]), "+f"(d[19]), "+f"(d[20]), "+f"(d[21]), "+f"(d[22]), "+f"(d[23]), "+f"(d[24]), "+f"(d[25]), "+f"(d[26]), "+f"(d[27]), "+f"(d[28]), "+f"(d[29]), "+f"(d[30]), "+f"(d[31])
      : "r"(a0), "r"(a1), "r"(a2), "r"(a3), "r"(db));
  } else {
    asm volatile("{\n.reg .pred p;\n.reg .b64 da, db;\nsetp.ne.b32 p, 0, 0;\nmov.b64 db, {%36, 112};\n"
      "wgmma.mma_async.sync.aligned.m64n64k16.f32.bf16.bf16 {%0, %1, %2, %3, %4, %5, %6, %7, %8, %9, %10, %11, %12, %13, %14, %15, %16, %17, %18, %19, %20, %21, %22, %23, %24, %25, %26, %27, %28, %29, %30, %31}, {%32, %33, %34, %35}, db, p, 1, 1, 0;\n}\n"
      : "=f"(d[0]), "=f"(d[1]), "=f"(d[2]), "=f"(d[3]), "=f"(d[4]), "=f"(d[5]), "=f"(d[6]), "=f"(d[7]), "=f"(d[8]), "=f"(d[9]), "=f"(d[10]), "=f"(d[11]), "=f"(d[12]), "=f"(d[13]), "=f"(d[14]), "=f"(d[15]), "=f"(d[16]), "=f"(d[17]), "=f"(d[18]), "=f"(d[19]), "=f"(d[20]), "=f"(d[21]), "=f"(d[22]), "=f"(d[23]), "=f"(d[24]), "=f"(d[25]), "=f"(d[26]), "=f"(d[27]), "=f"(d[28]), "=f"(d[29]), "=f"(d[30]), "=f"(d[31])
      : "r"(a0), "r"(a1), "r"(a2), "r"(a3), "r"(db));
  }
}
template <int SD> __device__ __forceinline__ void wgmma_rs_n32_t1(float (&d)[16], uint32_t a0, uint32_t a1, uint32_t a2, uint32_t a3, uint32_t db) {
  if constexpr (SD) {
    asm volatile("{\n.reg .pred p;\n.reg .b64 da, db;\nsetp.ne.b32 p, 1, 0;\nmov.b64 db, {%20, 64};\n"
      "wgmma.mma_async.sync.aligned.m64n32k16.f32.bf16.bf16 {%0, %1, %2, %3, %4, %5, %6, %7, %8, %9, %10, %11, %12, %13, %14, %15}, {%16, %17, %18, %19}, db, p, 1, 1, 1;\n}\n"
      : "+f"(d[0]), "+f"(d[1]), "+f"(d[2]), "+f"(d[3]), "+f"(d[4]), "+f"(d[5]), "+f"(d[6]), "+f"(d[7]), "+f"(d[8]), "+f"(d[9]), "+f"(d[10]), "+f"(d[11]), "+f"(d[12]), "+f"(d[13]), "+f"(d[14]), "+f"(d[15])
      : "r"(a0), "r"(a1), "r"(a2), "r"(a3), "r"(db));
  } else {
    asm volatile("{\n.reg .pred p;\n.reg .b64 da, db;\nsetp.ne.b32 p, 0, 0;\nmov.b64 db, {%20, 64};\n"
      "wgmma.mma_async.sync.aligned.m64n32k16.f32.bf16.bf16 {%0, %1, %2, %3, %4, %5, %6, %7, %8, %9, %10, %11, %12, %13, %14, %15}, {%16, %17, %18, %19}, db, p, 1, 1, 1;\n}\n"
      : "=f"(d[0]), "=f"(d[1]), "=f"(d[2]), "=f"(d[3]), "=f"(d[4]), "=f"(d[5]), "=f"(d[6]), "=f"(d[7]), "=f"(d[8]), "=f"(d[9]), "=f"(d[10]), "=f"(d[11]), "=f"(d[12]), "=f"(d[13]), "=f"(d[14]), "=f"(d[15])
      : "r"(a0), "r"(a1), "r"(a2), "r"(a3), "r"(db));
  }
}


__device__ __forceinline__ void wg_fence()  { asm volatile("wgmma.fence.sync.aligned;" ::: "memory"); }
__device__ __forceinline__ void wg_commit() { asm volatile("wgmma.commit_group.sync.aligned;" ::: "memory"); }
template <int N> __device__ __forceinline__ void wg_wait() { asm volatile("wgmma.wait_group.sync.aligned %0;" :: "n"(N) : "memory"); }
template <int N> __device__ __forceinline__ void fence_regs(float (&d)[N]) {
#pragma unroll
  for (int i = 0; i < N; i++) asm volatile("" : "+f"(d[i]) :: "memory");
}
template <int N> __device__ __forceinline__ void fence_regs_u(uint32_t (&d)[N]) {
#pragma unroll
  for (int i = 0; i < N; i++) asm volatile("" : "+r"(d[i]) :: "memory");
}
__device__ __forceinline__ uint32_t mk_desc(uint32_t addr) { return (addr >> 4) | (8u << 16); }
__device__ __forceinline__ uint32_t pack_bf16(float lo, float hi) {
  uint32_t r; asm("cvt.rn.bf16x2.f32 %0, %1, %2;" : "=r"(r) : "f"(hi), "f"(lo)); return r;
}
__device__ __forceinline__ uint32_t hmul2(uint32_t a, uint32_t b) {
  uint32_t r; asm("mul.rn.bf16x2 %0, %1, %2;" : "=r"(r) : "r"(a), "r"(b)); return r;
}
__device__ __forceinline__ uint32_t hfma2(uint32_t a, uint32_t b, uint32_t c) {
  uint32_t r; asm("fma.rn.bf16x2 %0, %1, %2, %3;" : "=r"(r) : "r"(a), "r"(b), "r"(c)); return r;
}
__device__ __forceinline__ float ex2(float x) { float r; asm("ex2.approx.ftz.f32 %0, %1;" : "=f"(r) : "f"(x)); return r; }
__device__ __forceinline__ float lg2(float x) { float r; asm("lg2.approx.ftz.f32 %0, %1;" : "=f"(r) : "f"(x)); return r; }
__device__ __forceinline__ float rsq(float x) { float r; asm("rsqrt.approx.ftz.f32 %0, %1;" : "=f"(r) : "f"(x)); return r; }
__device__ __forceinline__ float rcp(float x) { float r; asm("rcp.approx.ftz.f32 %0, %1;" : "=f"(r) : "f"(x)); return r; }
__device__ __forceinline__ void mma16816(float (&d)[4], uint32_t a0, uint32_t a1, uint32_t a2, uint32_t a3,
                                         uint32_t b0, uint32_t b1, float c0, float c1, float c2, float c3) {
  asm("mma.sync.aligned.m16n8k16.row.col.f32.bf16.bf16.f32 {%0,%1,%2,%3}, {%4,%5,%6,%7}, {%8,%9}, {%10,%11,%12,%13};"
      : "=f"(d[0]), "=f"(d[1]), "=f"(d[2]), "=f"(d[3])
      : "r"(a0), "r"(a1), "r"(a2), "r"(a3), "r"(b0), "r"(b1), "f"(c0), "f"(c1), "f"(c2), "f"(c3));
}
__device__ __forceinline__ void stsm4(uint32_t addr, uint32_t r0, uint32_t r1, uint32_t r2, uint32_t r3) {
  asm volatile("stmatrix.sync.aligned.m8n8.x4.shared.b16 [%0], {%1,%2,%3,%4};" :: "r"(addr), "r"(r0), "r"(r1), "r"(r2), "r"(r3) : "memory");
}
__device__ __forceinline__ void cp16(uint32_t dst, const void* src) {
  asm volatile("cp.async.cg.shared.global [%0], [%1], 16;" :: "r"(dst), "l"(src) : "memory");
}
__device__ __forceinline__ void cp_commit() { asm volatile("cp.async.commit_group;" ::: "memory"); }
__device__ __forceinline__ void cp_wait_all() { asm volatile("cp.async.wait_group 0;" ::: "memory"); }
__device__ __forceinline__ void fence_async() { asm volatile("fence.proxy.async.shared::cta;" ::: "memory"); }
__device__ __forceinline__ void bar_wg(int id) { asm volatile("bar.sync %0, 128;" :: "r"(id) : "memory"); }
__device__ __forceinline__ bool bar_wg_or(int id, bool v) {
  uint32_t r;
  asm volatile("{\n.reg .pred p, q;\nsetp.ne.u32 q, %2, 0;\nbar.red.or.pred p, %1, 128, q;\nselp.u32 %0, 1, 0, p;\n}\n"
               : "=r"(r) : "r"(id), "r"((uint32_t)v) : "memory");
  return r != 0;
}
__device__ __forceinline__ uint4 lds128(uint32_t addr) {
  uint4 v; asm volatile("ld.shared.v4.u32 {%0,%1,%2,%3}, [%4];" : "=r"(v.x), "=r"(v.y), "=r"(v.z), "=r"(v.w) : "r"(addr)); return v;
}
__device__ __forceinline__ uint4 ldg128_stream(const void* p) {
  uint4 v; asm volatile("ld.global.nc.L1::no_allocate.v4.u32 {%0,%1,%2,%3}, [%4];" : "=r"(v.x), "=r"(v.y), "=r"(v.z), "=r"(v.w) : "l"(p)); return v;
}
__device__ __forceinline__ void stg128(void* p, uint32_t a, uint32_t b, uint32_t c, uint32_t d) {
  asm volatile("st.global.v4.u32 [%0], {%1,%2,%3,%4};" :: "l"(p), "r"(a), "r"(b), "r"(c), "r"(d) : "memory");
}
__device__ __forceinline__ void prefetch_l2(const void* p, uint32_t bytes) {
  asm volatile("cp.async.bulk.prefetch.L2.global [%0], %1;" :: "l"(p), "r"(bytes) : "memory");
}
__device__ __forceinline__ float bf_lo(uint32_t u) { return __uint_as_float(u << 16); }
__device__ __forceinline__ float bf_hi(uint32_t u) { return __uint_as_float(u & 0xFFFF0000u); }
__device__ __forceinline__ float rbf(float x) { return __bfloat162float(__float2bfloat16_rn(x)); }
__device__ __forceinline__ float ldbf(const __nv_bfloat16* p) { return __bfloat162float(*p); }

__device__ __forceinline__ uint32_t pix_off(int win, int warp, int xo) {
  int wy = win / NWX, wx = win - wy * NWX;
  int y = wy * 8 + 4 + 2 * warp; if (y >= IMG) y -= IMG;
  int x = wx * 8 + 4 + xo;       if (x >= IMG) x -= IMG;
  return (uint32_t)(y * IMG + x) * PIXB;
}

__device__ __forceinline__ void softmax_fast(const float (&s)[32], uint32_t (&p)[16], uint32_t eb_addr) {
#pragma unroll
  for (int j = 0; j < 4; j++) {
    const uint4 e = lds128(eb_addr + j * 512);
    p[4 * j + 0] = hmul2(pack_bf16(ex2(s[8 * j + 0]), ex2(s[8 * j + 1])), e.x);
    p[4 * j + 1] = hmul2(pack_bf16(ex2(s[8 * j + 2]), ex2(s[8 * j + 3])), e.y);
    p[4 * j + 2] = hmul2(pack_bf16(ex2(s[8 * j + 4]), ex2(s[8 * j + 5])), e.z);
    p[4 * j + 3] = hmul2(pack_bf16(ex2(s[8 * j + 6]), ex2(s[8 * j + 7])), e.w);
  }
}
__device__ __forceinline__ void softmax_true_max(float (&s)[32], uint32_t (&p)[16], uint32_t eb_addr, bool masked,
                                                 const __nv_bfloat16* mrow) {
#pragma unroll
  for (int j = 0; j < 4; j++) {
    const uint4 e = lds128(eb_addr + j * 512);
    s[8 * j + 0] += lg2(bf_lo(e.x)); s[8 * j + 1] += lg2(bf_hi(e.x));
    s[8 * j + 2] += lg2(bf_lo(e.y)); s[8 * j + 3] += lg2(bf_hi(e.y));
    s[8 * j + 4] += lg2(bf_lo(e.z)); s[8 * j + 5] += lg2(bf_hi(e.z));
    s[8 * j + 6] += lg2(bf_lo(e.w)); s[8 * j + 7] += lg2(bf_hi(e.w));
  }
  if (masked) {
#pragma unroll
    for (int g = 0; g < 8; g++) {
      uint32_t m0 = *reinterpret_cast<const uint32_t*>(mrow + 8 * g);
      uint32_t m1 = *reinterpret_cast<const uint32_t*>(mrow + 8 * 64 + 8 * g);
      s[4 * g + 0] = fmaf(bf_lo(m0), LOG2E, s[4 * g + 0]); s[4 * g + 1] = fmaf(bf_hi(m0), LOG2E, s[4 * g + 1]);
      s[4 * g + 2] = fmaf(bf_lo(m1), LOG2E, s[4 * g + 2]); s[4 * g + 3] = fmaf(bf_hi(m1), LOG2E, s[4 * g + 3]);
    }
  }
  float m0 = s[0], m1 = s[2];
#pragma unroll
  for (int g = 0; g < 8; g++) {
    m0 = fmaxf(m0, fmaxf(s[4 * g + 0], s[4 * g + 1]));
    m1 = fmaxf(m1, fmaxf(s[4 * g + 2], s[4 * g + 3]));
  }
  m0 = fmaxf(m0, __shfl_xor_sync(0xffffffffu, m0, 1)); m0 = fmaxf(m0, __shfl_xor_sync(0xffffffffu, m0, 2));
  m1 = fmaxf(m1, __shfl_xor_sync(0xffffffffu, m1, 1)); m1 = fmaxf(m1, __shfl_xor_sync(0xffffffffu, m1, 2));
#pragma unroll
  for (int g = 0; g < 8; g++) {
    p[2 * g + 0] = pack_bf16(ex2(s[4 * g + 0] - m0), ex2(s[4 * g + 1] - m0));
    p[2 * g + 1] = pack_bf16(ex2(s[4 * g + 2] - m1), ex2(s[4 * g + 3] - m1));
  }
}
template <int H> __device__ __forceinline__ void issue_s(float (&s)[32], const uint32_t (&q)[24], uint32_t dK) {
  constexpr int Q0 = (H == 0 ? 0 : H == 1 ? 4 : H == 2 ? 12 : 16), P0 = (H == 0 ? 0 : H == 1 ? 3 : H == 2 ? 7 : 10);
  wgmma_rs_n64_t0<0>(s, q[Q0], q[Q0 + 1], q[Q0 + 2], q[Q0 + 3], dK + P0 * 8);
  wgmma_rs_n64_t0<1>(s, q[Q0 + 4], q[Q0 + 5], q[Q0 + 6], q[Q0 + 7], dK + P0 * 8 + 16);
}
template <int H> __device__ __forceinline__ void issue_pv(float (&o)[16], const uint32_t (&p)[16], uint32_t dV) {
  constexpr int P0 = (H == 0 ? 0 : H == 1 ? 3 : H == 2 ? 7 : 10);
  wgmma_rs_n32_t1<0>(o, p[0], p[1], p[2], p[3], dV + P0 * 64);
  wgmma_rs_n32_t1<1>(o, p[4], p[5], p[6], p[7], dV + P0 * 64 + 16);
  wgmma_rs_n32_t1<1>(o, p[8], p[9], p[10], p[11], dV + P0 * 64 + 32);
  wgmma_rs_n32_t1<1>(o, p[12], p[13], p[14], p[15], dV + P0 * 64 + 48);
}

__device__ __forceinline__ void normalize_qk(const float (&a)[48], uint32_t (&f)[24], uint32_t selE, uint32_t selO,
                                             float s0, float s1, float s2, float s3, bool scaled) {
#pragma unroll
  for (int i = 0; i < 24; i++) f[i] = pack_bf16(a[2 * i], a[2 * i + 1]);
  uint32_t sq[8];
#pragma unroll
  for (int h = 0; h < 4; h++)
#pragma unroll
    for (int r = 0; r < 2; r++) {
      uint32_t u = f[6 * h + r], v = f[6 * h + 2 + r], w = f[6 * h + 4 + r];
      sq[2 * h + r] = hfma2(w, w, hfma2(v, v, hmul2(u, u)));
    }
  float n01[4], n23[4];
  const float eps = 1e-12f;
  mma16816(n01, sq[0], sq[1], sq[2], sq[3], selE, selO, eps, eps, eps, eps);
  mma16816(n23, sq[4], sq[5], sq[6], sq[7], selE, selO, eps, eps, eps, eps);
  float r[8] = {rsq(n01[0]), rsq(n01[2]), rsq(n01[1]), rsq(n01[3]), rsq(n23[0]), rsq(n23[2]), rsq(n23[1]), rsq(n23[3])};
  if (scaled) { r[0] *= s0; r[1] *= s0; r[2] *= s1; r[3] *= s1; r[4] *= s2; r[5] *= s2; r[6] *= s3; r[7] *= s3; }
#pragma unroll
  for (int h = 0; h < 4; h++)
#pragma unroll
    for (int q = 0; q < 2; q++) {
      uint32_t p = pack_bf16(r[2 * h + q], r[2 * h + q]);
#pragma unroll
      for (int c = 0; c < 3; c++) f[6 * h + 2 * c + q] = hmul2(f[6 * h + 2 * c + q], p);
    }
}

template <int ODD> __device__ __forceinline__ void norm_o(const float (&o)[16], uint32_t* of) {
  constexpr int SO = ODD ? 0 : 12, VO = ODD ? 4 : 0;
  float r0 = rcp(o[SO]), r1 = rcp(o[SO + 2]);
  uint32_t p0 = pack_bf16(r0, r0), p1 = pack_bf16(r1, r1);
#pragma unroll
  for (int g = 0; g < 3; g++) {
    of[2 * g + 0] = hmul2(pack_bf16(o[VO + 4 * g + 0], o[VO + 4 * g + 1]), p0);
    of[2 * g + 1] = hmul2(pack_bf16(o[VO + 4 * g + 2], o[VO + 4 * g + 3]), p1);
  }
}

template <int H> __device__ __forceinline__ void slow_head(const uint32_t (&q)[24], uint32_t* of, uint32_t dK, uint32_t dV, uint32_t eb_base,
                                                           bool true_max, bool masked, const __nv_bfloat16* mrow) {
  float s[32], o[16]; uint32_t p[16];
  wg_fence(); issue_s<H>(s, q, dK); wg_commit();
  wg_wait<0>(); fence_regs(s);
  if (true_max) softmax_true_max(s, p, eb_base + H * 8192, masked, mrow); else softmax_fast(s, p, eb_base + H * 8192);
  wg_fence(); issue_pv<H>(o, p, dV); wg_commit();
  wg_wait<0>(); fence_regs(o);
  norm_o<H & 1>(o, of + 6 * H);
}

__global__ void __launch_bounds__(384, 1)
swin_kernel(const __nv_bfloat16* __restrict__ x, const __nv_bfloat16* __restrict__ wqkv, const __nv_bfloat16* __restrict__ wo,
            const __nv_bfloat16* __restrict__ logit_scale, const __nv_bfloat16* __restrict__ w1, const __nv_bfloat16* __restrict__ w2,
            const __nv_bfloat16* __restrict__ coords, const int* __restrict__ rel_idx, const __nv_bfloat16* __restrict__ mask,
            __nv_bfloat16* __restrict__ out) {
  extern __shared__ __align__(1024) uint8_t smem[];
  constexpr uint32_t sb = 1024;
  if ((uint32_t)__cvta_generic_to_shared(smem) != sb) __trap();
  const int tid = threadIdx.x, lane = tid & 31;
  const int warp = __shfl_sync(0xffffffffu, (tid >> 5) & 3, 0), wg = __shfl_sync(0xffffffffu, tid >> 7, 0);
  const int g = lane >> 2, t = lane & 3;
  const int stride = 3 * gridDim.x;
  int win = wg * gridDim.x + blockIdx.x;
  const uint32_t wgb = sb + SM_WG + wg * WG_SZ;
  const char* xb = reinterpret_cast<const char*>(x);
  const char* mb = reinterpret_cast<const char*>(mask);

  const uint32_t x_dst = wgb + WG_X + (2 * warp) * 1536 + (lane >> 3) * 128 + (lane & 7) * 16;
  auto load_x = [&](int w) {
    const char* src = xb + pix_off(w, warp, lane & 7) + (lane >> 3) * 16;
#pragma unroll
    for (int r = 0; r < 2; r++)
#pragma unroll
      for (int j = 0; j < 3; j++) cp16(x_dst + r * 1536 + j * 512, src + r * ROWB + j * 64);
    cp_commit();
  };
  auto mask_word = [&](int w) -> uint32_t {
    const char* src = mb + (size_t)w * 8192 + warp * 2048 + lane * 16;
    uint4 a = ldg128_stream(src), b = ldg128_stream(src + 512), c = ldg128_stream(src + 1024), d = ldg128_stream(src + 1536);
    return (a.x | a.y | a.z | a.w | b.x | b.y | b.z | b.w) | (c.x | c.y | c.z | c.w | d.x | d.y | d.z | d.w);
  };

  if (win < NWIN) load_x(win);
  {
    const int wid = tid >> 5;
#pragma unroll
    for (int i = 0; i < 9; i++) {
      int task = wid * 9 + i;
      int kb = task / 9, nq = task - kb * 9;
      int nb = nq * 4 + (lane >> 3), k = kb * 8 + (lane & 7);
      cp16(sb + SM_W + nb * 1536 + kb * 128 + (lane & 7) * 16, reinterpret_cast<const char*>(wqkv) + k * 576 + nb * 16);
    }
    cp_commit();
  }
  uint32_t mword = (win < NWIN) ? mask_word(win) : 0u;
  if (lane == 0 && warp == 0 && win + stride < NWIN) prefetch_l2(mb + (size_t)(win + stride) * 8192, 8192);
  float* tab = reinterpret_cast<float*>(smem + SM_TAB);
  if (tid < 96) {
    uint4 v[12];
#pragma unroll
    for (int i = 0; i < 12; i++) v[i] = *reinterpret_cast<const uint4*>(wo + tid * 96 + i * 8);
    float sum = 0.f;
#pragma unroll
    for (int i = 0; i < 12; i++)
      sum += (bf_lo(v[i].x) + bf_hi(v[i].x)) + (bf_lo(v[i].y) + bf_hi(v[i].y)) + (bf_lo(v[i].z) + bf_hi(v[i].z)) + (bf_lo(v[i].w) + bf_hi(v[i].w));
    const float mu = sum * (1.f / 96.f);
    auto cen = [&](uint32_t u) { return pack_bf16(bf_lo(u) - mu, bf_hi(u) - mu); };
    uint8_t* dst = smem + SM_WO + (tid >> 3) * 128 + (tid & 7) * 16;
#pragma unroll
    for (int j = 0; j < 3; j++) {
      *reinterpret_cast<uint4*>(dst + (4 * j + 0) * 1536) = make_uint4(cen(v[4 * j].x), cen(v[4 * j + 1].x), cen(v[4 * j + 2].x), cen(v[4 * j + 3].x));
      *reinterpret_cast<uint4*>(dst + (4 * j + 1) * 1536) = make_uint4(cen(v[4 * j].y), cen(v[4 * j + 1].y), cen(v[4 * j + 2].y), cen(v[4 * j + 3].y));
      *reinterpret_cast<uint4*>(dst + (4 * j + 2) * 1536) = make_uint4(cen(v[4 * j].z), cen(v[4 * j + 1].z), cen(v[4 * j + 2].z), cen(v[4 * j + 3].z));
      *reinterpret_cast<uint4*>(dst + (4 * j + 3) * 1536) = make_uint4(cen(v[4 * j].w), cen(v[4 * j + 1].w), cen(v[4 * j + 2].w), cen(v[4 * j + 3].w));
    }
  } else if (tid >= 128 && tid < 128 + 225) {
    const int i = tid - 128;
    const float c0 = ldbf(coords + 2 * i), c1 = ldbf(coords + 2 * i + 1);
    float z[4] = {0.f, 0.f, 0.f, 0.f};
#pragma unroll
    for (int j = 0; j < 16; j++) {
      float h = rbf(fmaf(c1, ldbf(w1 + 16 + j), c0 * ldbf(w1 + j)));
      h = h > 0.f ? h : h * 0.f;
#pragma unroll
      for (int q = 0; q < 4; q++) z[q] = fmaf(h, ldbf(w2 + 4 * j + q), z[q]);
    }
#pragma unroll
    for (int q = 0; q < 4; q++) tab[4 * i + q] = 16.f * rbf(1.f / (1.f + __expf(-rbf(z[q]))));
  }
  {
    const int i = tid & 127;
    uint8_t* vt = smem + SM_WG + wg * WG_SZ + WG_V;
    *reinterpret_cast<uint4*>(vt + (i < 64 ? 3 : 10) * 1024 + (i & 63) * 16) = make_uint4(0x3F803F80u, 0x3F803F80u, 0x3F803F80u, 0x3F803F80u);
    uint8_t* kt = smem + SM_WG + wg * WG_SZ + WG_K;
    *reinterpret_cast<uint4*>(kt + (i >> 4) * 1792 + ((i & 8) ? 10 : 3) * 128 + (i & 7) * 16) = make_uint4(0u, 0u, 0u, 0u);
  }
  float tau[4]; uint32_t slow_heads = 0;
#pragma unroll
  for (int h = 0; h < 4; h++) {
    tau[h] = rbf(expf(fminf(fmaxf(ldbf(logit_scale + h), -100.f), 4.59375f)));
    if (!(tau[h] * (2.04f * LOG2E) <= 80.f)) slow_heads |= 1u << h;
  }
  slow_heads = __shfl_sync(0xffffffffu, slow_heads, 0);
  if (tid == 0) *reinterpret_cast<float4*>(smem + SM_MISC) = make_float4(tau[0] * LOG2E, tau[1] * LOG2E, tau[2] * LOG2E, tau[3] * LOG2E);
  __syncthreads();
  if (tid >= 128) {
    const int task = (tid >> 5) - 4, w = task >> 1, r = task & 1;
    const int row = 16 * w + 8 * r + g;
    float b[16][4];
#pragma unroll
    for (int G = 0; G < 8; G++) {
      int2 id = *reinterpret_cast<const int2*>(rel_idx + row * 64 + 8 * G + 2 * t);
      float4 u = *reinterpret_cast<const float4*>(tab + 4 * id.x), v = *reinterpret_cast<const float4*>(tab + 4 * id.y);
      b[2 * G][0] = u.x; b[2 * G][1] = u.y; b[2 * G][2] = u.z; b[2 * G][3] = u.w;
      b[2 * G + 1][0] = v.x; b[2 * G + 1][1] = v.y; b[2 * G + 1][2] = v.z; b[2 * G + 1][3] = v.w;
    }
#pragma unroll
    for (int h = 0; h < 4; h++) {
      float m = b[0][h];
#pragma unroll
      for (int i = 1; i < 16; i++) m = fmaxf(m, b[i][h]);
      m = fmaxf(m, __shfl_xor_sync(0xffffffffu, m, 1));
      m = fmaxf(m, __shfl_xor_sync(0xffffffffu, m, 2));
      if (!((slow_heads >> h) & 1)) m += 1.02f * tau[h];
#pragma unroll
      for (int G = 0; G < 8; G++) {
        uint32_t e = pack_bf16(exp2f((b[2 * G][h] - m) * LOG2E), exp2f((b[2 * G + 1][h] - m) * LOG2E));
        *reinterpret_cast<uint32_t*>(smem + SM_EB + ((h * 4 + w) * 4 + (G >> 1)) * 512 + lane * 16 + ((G & 1) * 2 + r) * 4) = e;
      }
    }
  }
  cp_wait_all();
  fence_async();
  __syncthreads();

  const uint32_t ONES = 0x3F803F80u;
  const uint32_t selE = (g & 1) ? 0u : ONES, selO = (g & 1) ? ONES : 0u;
  const uint32_t dX = mk_desc(wgb + WG_X);
  const uint32_t dW = mk_desc(sb + SM_W);
  const uint32_t dWo = mk_desc(sb + SM_WO);
  const uint32_t dK = mk_desc(wgb + WG_K);
  const uint32_t dV = mk_desc(wgb + WG_V);
  const uint32_t k_dst = wgb + WG_K + (2 * warp + ((lane >> 3) & 1)) * 1792 + (lane >> 4) * 896 + (lane & 7) * 16;
  const uint32_t v_dst = wgb + WG_V + (lane >> 4) * 7168 + (2 * warp + ((lane >> 3) & 1)) * 128 + (lane & 7) * 16;
  const uint32_t eb_base = sb + SM_EB + warp * 2048 + lane * 16;
  const int bar_id = 1 + wg;

  bool masked = bar_wg_or(bar_id + 4, (mword & 0x7FFF7FFFu) != 0u);
  for (; win < NWIN; win += stride) {
    const int nxt = win + stride;

    float qq[48], kk[48], vv[48];
    wg_fence();
#pragma unroll
    for (int s = 0; s < 6; s++) {
      if (s == 0) wgmma_ss_n96_t1<0>(vv, dX, dW + 24 * 96); else wgmma_ss_n96_t1<1>(vv, dX + s * 16, dW + 24 * 96 + s * 16);
    }
    wg_commit();
#pragma unroll
    for (int s = 0; s < 6; s++) {
      if (s == 0) wgmma_ss_n96_t1<0>(kk, dX, dW + 12 * 96); else wgmma_ss_n96_t1<1>(kk, dX + s * 16, dW + 12 * 96 + s * 16);
    }
    wg_commit();
    wg_wait<1>();
    fence_regs(vv);
#pragma unroll
    for (int i = 0; i < 6; i++)
      stsm4(v_dst + (i + (i >= 3)) * 1024, pack_bf16(vv[4 * i], vv[4 * i + 1]), pack_bf16(vv[4 * i + 2], vv[4 * i + 3]),
            pack_bf16(vv[24 + 4 * i], vv[24 + 4 * i + 1]), pack_bf16(vv[24 + 4 * i + 2], vv[24 + 4 * i + 3]));
    wg_fence();
#pragma unroll
    for (int s = 0; s < 6; s++) {
      if (s == 0) wgmma_ss_n96_t1<0>(qq, dX, dW); else wgmma_ss_n96_t1<1>(qq, dX + s * 16, dW + s * 16);
    }
    wg_commit();
    wg_wait<1>();
    fence_regs(kk);
    uint32_t qa[24];
    normalize_qk(kk, qa, selE, selO, 1.f, 1.f, 1.f, 1.f, false);
#pragma unroll
    for (int i = 0; i < 6; i++) stsm4(k_dst + (i + (i >= 3)) * 128, qa[2 * i], qa[2 * i + 1], qa[12 + 2 * i], qa[12 + 2 * i + 1]);
    wg_wait<0>();
    fence_regs(qq);
    fence_async();
    bar_wg(bar_id);
    if (nxt < NWIN) load_x(nxt);
    if (lane == 0 && warp == 0 && nxt + stride < NWIN) prefetch_l2(mb + (size_t)(nxt + stride) * 8192, 8192);
    {
      const uint4 qs = lds128(sb + SM_MISC);
      normalize_qk(qq, qa, selE, selO, __uint_as_float(qs.x), __uint_as_float(qs.y), __uint_as_float(qs.z), __uint_as_float(qs.w), true);
    }

    uint32_t of[24];
    if (!masked && slow_heads == 0) {
      float sA[32], sB[32], oA[16], oB[16];
      uint32_t pA[16], pB[16];
      wg_fence();
      issue_s<0>(sA, qa, dK); wg_commit();
      issue_s<1>(sB, qa, dK); wg_commit();
      wg_wait<1>(); fence_regs(sA);
      softmax_fast(sA, pA, eb_base);
      wg_fence();
      issue_pv<0>(oA, pA, dV); wg_commit();
      issue_s<2>(sA, qa, dK); wg_commit();
      wg_wait<2>(); fence_regs(sB);
      softmax_fast(sB, pB, eb_base + 8192);
      wg_fence();
      issue_pv<1>(oB, pB, dV); wg_commit();
      issue_s<3>(sB, qa, dK); wg_commit();
      wg_wait<2>(); fence_regs(sA); fence_regs(oA);
      norm_o<0>(oA, of);
      softmax_fast(sA, pA, eb_base + 2 * 8192);
      wg_fence();
      issue_pv<2>(oA, pA, dV); wg_commit();
      wg_wait<1>(); fence_regs(sB); fence_regs(oB);
      norm_o<1>(oB, of + 6);
      softmax_fast(sB, pB, eb_base + 3 * 8192);
      wg_fence();
      issue_pv<3>(oB, pB, dV); wg_commit();
      wg_wait<1>(); fence_regs(oA);
      norm_o<0>(oA, of + 12);
      wg_wait<0>(); fence_regs(oB);
      norm_o<1>(oB, of + 18);
    } else {
      const __nv_bfloat16* mrow = mask + (size_t)win * 4096 + (16 * warp + g) * 64 + 2 * t;
      const uint32_t tm = masked ? 0xFu : slow_heads;
      slow_head<0>(qa, of, dK, dV, eb_base, tm & 1, masked, mrow);
      slow_head<1>(qa, of, dK, dV, eb_base, tm & 2, masked, mrow);
      slow_head<2>(qa, of, dK, dV, eb_base, tm & 4, masked, mrow);
      slow_head<3>(qa, of, dK, dV, eb_base, tm & 8, masked, mrow);
    }

    float y[48];
    wg_fence();
#pragma unroll
    for (int s = 0; s < 6; s++) {
      if (s == 0) wgmma_rs_n96_t1<0>(y, of[0], of[1], of[2], of[3], dWo);
      else wgmma_rs_n96_t1<1>(y, of[4 * s], of[4 * s + 1], of[4 * s + 2], of[4 * s + 3], dWo + s * 16);
    }
    wg_commit();
    mword = (nxt < NWIN) ? mask_word(nxt) : 0u;
    char* optr = reinterpret_cast<char*>(out) + pix_off(win, warp, g) + t * 16;
    wg_wait<0>(); fence_regs(y);
    uint32_t yb[24];
#pragma unroll
    for (int i = 0; i < 24; i++) yb[i] = pack_bf16(y[2 * i], y[2 * i + 1]);
    uint32_t sy[8];
#pragma unroll
    for (int c = 0; c < 4; c++)
#pragma unroll
      for (int r = 0; r < 2; r++) {
        uint32_t a = yb[6 * c + r], b = yb[6 * c + 2 + r], d = yb[6 * c + 4 + r];
        sy[2 * c + r] = hfma2(d, d, hfma2(b, b, hmul2(a, a)));
      }
    float v0[4], v1[4];
    mma16816(v0, sy[0], sy[1], sy[2], sy[3], ONES, ONES, 0.f, 0.f, 0.f, 0.f);
    mma16816(v1, sy[4], sy[5], sy[6], sy[7], ONES, ONES, 0.f, 0.f, 0.f, 0.f);
    const float r0 = rsq(fmaf(v0[0] + v1[0], 1.f / 96.f, 1e-5f)), r1 = rsq(fmaf(v0[2] + v1[2], 1.f / 96.f, 1e-5f));
    const uint32_t n0 = pack_bf16(r0, r0), n1 = pack_bf16(r1, r1);
#pragma unroll
    for (int j = 0; j < 3; j++) {
      stg128(optr + j * 64, hmul2(yb[8 * j], n0), hmul2(yb[8 * j + 2], n0), hmul2(yb[8 * j + 4], n0), hmul2(yb[8 * j + 6], n0));
      stg128(optr + ROWB + j * 64, hmul2(yb[8 * j + 1], n1), hmul2(yb[8 * j + 3], n1), hmul2(yb[8 * j + 5], n1), hmul2(yb[8 * j + 7], n1));
    }
    cp_wait_all();
    fence_async();
    masked = bar_wg_or(bar_id + 4, (mword & 0x7FFF7FFFu) != 0u);
  }
}

}

extern "C" void kernel_launch(void* const* d_in, const int* in_sizes, int n_in, void* d_out, int out_size) {
  static int sms = 0;
  if (sms == 0) {
    int dev = 0;
    cudaGetDevice(&dev);
    cudaDeviceGetAttribute(&sms, cudaDevAttrMultiProcessorCount, dev);
    cudaFuncSetAttribute(swin_kernel, cudaFuncAttributeMaxDynamicSharedMemorySize, SM_TOTAL);
  }
  swin_kernel<<<sms, 384, SM_TOTAL>>>(
      (const __nv_bfloat16*)d_in[0], (const __nv_bfloat16*)d_in[1], (const __nv_bfloat16*)d_in[2], (const __nv_bfloat16*)d_in[3],
      (const __nv_bfloat16*)d_in[4], (const __nv_bfloat16*)d_in[5], (const __nv_bfloat16*)d_in[6], (const int*)d_in[7],
      (const __nv_bfloat16*)d_in[8], (__nv_bfloat16*)d_out);
}
```

```cpp
#include <cuda_runtime.h>
#include <cuda.h>
#include <cuda_bf16.h>
#include <stdint.h>

namespace {

constexpr int IMG   = 384;
constexpr int NWX   = 48;
constexpr int NWIN  = NWX * NWX;
constexpr int PIXB  = 192;
constexpr int ROWB  = IMG * PIXB;
constexpr float LOG2E = 1.4426950408889634f;

constexpr int SM_W    = 0;
constexpr int SM_WO   = SM_W + 9 * 6144;
constexpr int SM_EB   = SM_WO + 12 * 1536;
constexpr int SM_WG   = SM_EB + 32768;
constexpr int WG_X    = 0;
constexpr int WG_K    = 12288;
constexpr int WG_V    = WG_K + 14336;
constexpr int WG_SZ   = WG_V + 14336;
constexpr int SM_TAB  = SM_WG + WG_V + 4096;
constexpr int SM_SEL  = SM_WG + 3 * WG_SZ;
constexpr int SM_MISC = SM_SEL + 256;
constexpr int SM_BAR  = SM_MISC + 16;
constexpr int SM_TOTAL = SM_BAR + 32;

template <int SD> __device__ __forceinline__ void wgmma_ss_n192_t1(float (&d)[96], uint32_t da, uint32_t db) {
  if constexpr (SD) {
    asm volatile("{\n.reg .pred p;\n.reg .b64 da, db;\nsetp.ne.b32 p, 1, 0;\nmov.b64 da, {%96, 0x80000020};\nmov.b64 db, {%97, 0x80000020};\n"
      "wgmma.mma_async.sync.aligned.m64n192k16.f32.bf16.bf16 {%0, %1, %2, %3, %4, %5, %6, %7, %8, %9, %10, %11, %12, %13, %14, %15, %16, %17, %18, %19, %20, %21, %22, %23, %24, %25, %26, %27, %28, %29, %30, %31, %32, %33, %34, %35, %36, %37, %38, %39, %40, %41, %42, %43, %44, %45, %46, %47, %48, %49, %50, %51, %52, %53, %54, %55, %56, %57, %58, %59, %60, %61, %62, %63, %64, %65, %66, %67, %68, %69, %70, %71, %72, %73, %74, %75, %76, %77, %78, %79, %80, %81, %82, %83, %84, %85, %86, %87, %88, %89, %90, %91, %92, %93, %94, %95}, da, db, p, 1, 1, 0, 1;\n}\n"
      : "+f"(d[0]), "+f"(d[1]), "+f"(d[2]), "+f"(d[3]), "+f"(d[4]), "+f"(d[5]), "+f"(d[6]), "+f"(d[7]), "+f"(d[8]), "+f"(d[9]), "+f"(d[10]), "+f"(d[11]), "+f"(d[12]), "+f"(d[13]), "+f"(d[14]), "+f"(d[15]), "+f"(d[16]), "+f"(d[17]), "+f"(d[18]), "+f"(d[19]), "+f"(d[20]), "+f"(d[21]), "+f"(d[22]), "+f"(d[23]), "+f"(d[24]), "+f"(d[25]), "+f"(d[26]), "+f"(d[27]), "+f"(d[28]), "+f"(d[29]), "+f"(d[30]), "+f"(d[31]), "+f"(d[32]), "+f"(d[33]), "+f"(d[34]), "+f"(d[35]), "+f"(d[36]), "+f"(d[37]), "+f"(d[38]), "+f"(d[39]), "+f"(d[40]), "+f"(d[41]), "+f"(d[42]), "+f"(d[43]), "+f"(d[44]), "+f"(d[45]), "+f"(d[46]), "+f"(d[47]), "+f"(d[48]), "+f"(d[49]), "+f"(d[50]), "+f"(d[51]), "+f"(d[52]), "+f"(d[53]), "+f"(d[54]), "+f"(d[55]), "+f"(d[56]), "+f"(d[57]), "+f"(d[58]), "+f"(d[59]), "+f"(d[60]), "+f"(d[61]), "+f"(d[62]), "+f"(d[63]), "+f"(d[64]), "+f"(d[65]), "+f"(d[66]), "+f"(d[67]), "+f"(d[68]), "+f"(d[69]), "+f"(d[70]), "+f"(d[71]), "+f"(d[72]), "+f"(d[73]), "+f"(d[74]), "+f"(d[75]), "+f"(d[76]), "+f"(d[77]), "+f"(d[78]), "+f"(d[79]), "+f"(d[80]), "+f"(d[81]), "+f"(d[82]), "+f"(d[83]), "+f"(d[84]), "+f"(d[85]), "+f"(d[86]), "+f"(d[87]), "+f"(d[88]), "+f"(d[89]), "+f"(d[90]), "+f"(d[91]), "+f"(d[92]), "+f"(d[93]), "+f"(d[94]), "+f"(d[95])
      : "r"(da), "r"(db));
  } else {
    asm volatile("{\n.reg .pred p;\n.reg .b64 da, db;\nsetp.ne.b32 p, 0, 0;\nmov.b64 da, {%96, 0x80000020};\nmov.b64 db, {%97, 0x80000020};\n"
      "wgmma.mma_async.sync.aligned.m64n192k16.f32.bf16.bf16 {%0, %1, %2, %3, %4, %5, %6, %7, %8, %9, %10, %11, %12, %13, %14, %15, %16, %17, %18, %19, %20, %21, %22, %23, %24, %25, %26, %27, %28, %29, %30, %31, %32, %33, %34, %35, %36, %37, %38, %39, %40, %41, %42, %43, %44, %45, %46, %47, %48, %49, %50, %51, %52, %53, %54, %55, %56, %57, %58, %59, %60, %61, %62, %63, %64, %65, %66, %67, %68, %69, %70, %71, %72, %73, %74, %75, %76, %77, %78, %79, %80, %81, %82, %83, %84, %85, %86, %87, %88, %89, %90, %91, %92, %93, %94, %95}, da, db, p, 1, 1, 0, 1;\n}\n"
      : "=f"(d[0]), "=f"(d[1]), "=f"(d[2]), "=f"(d[3]), "=f"(d[4]), "=f"(d[5]), "=f"(d[6]), "=f"(d[7]), "=f"(d[8]), "=f"(d[9]), "=f"(d[10]), "=f"(d[11]), "=f"(d[12]), "=f"(d[13]), "=f"(d[14]), "=f"(d[15]), "=f"(d[16]), "=f"(d[17]), "=f"(d[18]), "=f"(d[19]), "=f"(d[20]), "=f"(d[21]), "=f"(d[22]), "=f"(d[23]), "=f"(d[24]), "=f"(d[25]), "=f"(d[26]), "=f"(d[27]), "=f"(d[28]), "=f"(d[29]), "=f"(d[30]), "=f"(d[31]), "=f"(d[32]), "=f"(d[33]), "=f"(d[34]), "=f"(d[35]), "=f"(d[36]), "=f"(d[37]), "=f"(d[38]), "=f"(d[39]), "=f"(d[40]), "=f"(d[41]), "=f"(d[42]), "=f"(d[43]), "=f"(d[44]), "=f"(d[45]), "=f"(d[46]), "=f"(d[47]), "=f"(d[48]), "=f"(d[49]), "=f"(d[50]), "=f"(d[51]), "=f"(d[52]), "=f"(d[53]), "=f"(d[54]), "=f"(d[55]), "=f"(d[56]), "=f"(d[57]), "=f"(d[58]), "=f"(d[59]), "=f"(d[60]), "=f"(d[61]), "=f"(d[62]), "=f"(d[63]), "=f"(d[64]), "=f"(d[65]), "=f"(d[66]), "=f"(d[67]), "=f"(d[68]), "=f"(d[69]), "=f"(d[70]), "=f"(d[71]), "=f"(d[72]), "=f"(d[73]), "=f"(d[74]), "=f"(d[75]), "=f"(d[76]), "=f"(d[77]), "=f"(d[78]), "=f"(d[79]), "=f"(d[80]), "=f"(d[81]), "=f"(d[82]), "=f"(d[83]), "=f"(d[84]), "=f"(d[85]), "=f"(d[86]), "=f"(d[87]), "=f"(d[88]), "=f"(d[89]), "=f"(d[90]), "=f"(d[91]), "=f"(d[92]), "=f"(d[93]), "=f"(d[94]), "=f"(d[95])
      : "r"(da), "r"(db));
  }
}
template <int SD> __device__ __forceinline__ void wgmma_ss_n96_t1(float (&d)[48], uint32_t da, uint32_t db) {
  if constexpr (SD) {
    asm volatile("{\n.reg .pred p;\n.reg .b64 da, db;\nsetp.ne.b32 p, 1, 0;\nmov.b64 da, {%48, 0x80000020};\nmov.b64 db, {%49, 0x80000020};\n"
      "wgmma.mma_async.sync.aligned.m64n96k16.f32.bf16.bf16 {%0, %1, %2, %3, %4, %5, %6, %7, %8, %9, %10, %11, %12, %13, %14, %15, %16, %17, %18, %19, %20, %21, %22, %23, %24, %25, %26, %27, %28, %29, %30, %31, %32, %33, %34, %35, %36, %37, %38, %39, %40, %41, %42, %43, %44, %45, %46, %47}, da, db, p, 1, 1, 0, 1;\n}\n"
      : "+f"(d[0]), "+f"(d[1]), "+f"(d[2]), "+f"(d[3]), "+f"(d[4]), "+f"(d[5]), "+f"(d[6]), "+f"(d[7]), "+f"(d[8]), "+f"(d[9]), "+f"(d[10]), "+f"(d[11]), "+f"(d[12]), "+f"(d[13]), "+f"(d[14]), "+f"(d[15]), "+f"(d[16]), "+f"(d[17]), "+f"(d[18]), "+f"(d[19]), "+f"(d[20]), "+f"(d[21]), "+f"(d[22]), "+f"(d[23]), "+f"(d[24]), "+f"(d[25]), "+f"(d[26]), "+f"(d[27]), "+f"(d[28]), "+f"(d[29]), "+f"(d[30]), "+f"(d[31]), "+f"(d[32]), "+f"(d[33]), "+f"(d[34]), "+f"(d[35]), "+f"(d[36]), "+f"(d[37]), "+f"(d[38]), "+f"(d[39]), "+f"(d[40]), "+f"(d[41]), "+f"(d[42]), "+f"(d[43]), "+f"(d[44]), "+f"(d[45]), "+f"(d[46]), "+f"(d[47])
      : "r"(da), "r"(db));
  } else {
    asm volatile("{\n.reg .pred p;\n.reg .b64 da, db;\nsetp.ne.b32 p, 0, 0;\nmov.b64 da, {%48, 0x80000020};\nmov.b64 db, {%49, 0x80000020};\n"
      "wgmma.mma_async.sync.aligned.m64n96k16.f32.bf16.bf16 {%0, %1, %2, %3, %4, %5, %6, %7, %8, %9, %10, %11, %12, %13, %14, %15, %16, %17, %18, %19, %20, %21, %22, %23, %24, %25, %26, %27, %28, %29, %30, %31, %32, %33, %34, %35, %36, %37, %38, %39, %40, %41, %42, %43, %44, %45, %46, %47}, da, db, p, 1, 1, 0, 1;\n}\n"
      : "=f"(d[0]), "=f"(d[1]), "=f"(d[2]), "=f"(d[3]), "=f"(d[4]), "=f"(d[5]), "=f"(d[6]), "=f"(d[7]), "=f"(d[8]), "=f"(d[9]), "=f"(d[10]), "=f"(d[11]), "=f"(d[12]), "=f"(d[13]), "=f"(d[14]), "=f"(d[15]), "=f"(d[16]), "=f"(d[17]), "=f"(d[18]), "=f"(d[19]), "=f"(d[20]), "=f"(d[21]), "=f"(d[22]), "=f"(d[23]), "=f"(d[24]), "=f"(d[25]), "=f"(d[26]), "=f"(d[27]), "=f"(d[28]), "=f"(d[29]), "=f"(d[30]), "=f"(d[31]), "=f"(d[32]), "=f"(d[33]), "=f"(d[34]), "=f"(d[35]), "=f"(d[36]), "=f"(d[37]), "=f"(d[38]), "=f"(d[39]), "=f"(d[40]), "=f"(d[41]), "=f"(d[42]), "=f"(d[43]), "=f"(d[44]), "=f"(d[45]), "=f"(d[46]), "=f"(d[47])
      : "r"(da), "r"(db));
  }
}
template <int SD> __device__ __forceinline__ void wgmma_rs_n96_t1(float (&d)[48], uint32_t a0, uint32_t a1, uint32_t a2, uint32_t a3, uint32_t db) {
  if constexpr (SD) {
    asm volatile("{\n.reg .pred p;\n.reg .b64 da, db;\nsetp.ne.b32 p, 1, 0;\nmov.b64 db, {%52, 96};\n"
      "wgmma.mma_async.sync.aligned.m64n96k16.f32.bf16.bf16 {%0, %1, %2, %3, %4, %5, %6, %7, %8, %9, %10, %11, %12, %13, %14, %15, %16, %17, %18, %19, %20, %21, %22, %23, %24, %25, %26, %27, %28, %29, %30, %31, %32, %33, %34, %35, %36, %37, %38, %39, %40, %41, %42, %43, %44, %45, %46, %47}, {%48, %49, %50, %51}, db, p, 1, 1, 1;\n}\n"
      : "+f"(d[0]), "+f"(d[1]), "+f"(d[2]), "+f"(d[3]), "+f"(d[4]), "+f"(d[5]), "+f"(d[6]), "+f"(d[7]), "+f"(d[8]), "+f"(d[9]), "+f"(d[10]), "+f"(d[11]), "+f"(d[12]), "+f"(d[13]), "+f"(d[14]), "+f"(d[15]), "+f"(d[16]), "+f"(d[17]), "+f"(d[18]), "+f"(d[19]), "+f"(d[20]), "+f"(d[21]), "+f"(d[22]), "+f"(d[23]), "+f"(d[24]), "+f"(d[25]), "+f"(d[26]), "+f"(d[27]), "+f"(d[28]), "+f"(d[29]), "+f"(d[30]), "+f"(d[31]), "+f"(d[32]), "+f"(d[33]), "+f"(d[34]), "+f"(d[35]), "+f"(d[36]), "+f"(d[37]), "+f"(d[38]), "+f"(d[39]), "+f"(d[40]), "+f"(d[41]), "+f"(d[42]), "+f"(d[43]), "+f"(d[44]), "+f"(d[45]), "+f"(d[46]), "+f"(d[47])
      : "r"(a0), "r"(a1), "r"(a2), "r"(a3), "r"(db));
  } else {
    asm volatile("{\n.reg .pred p;\n.reg .b64 da, db;\nsetp.ne.b32 p, 0, 0;\nmov.b64 db, {%52, 96};\n"
      "wgmma.mma_async.sync.aligned.m64n96k16.f32.bf16.bf16 {%0, %1, %2, %3, %4, %5, %6, %7, %8, %9, %10, %11, %12, %13, %14, %15, %16, %17, %18, %19, %20, %21, %22, %23, %24, %25, %26, %27, %28, %29, %30, %31, %32, %33, %34, %35, %36, %37, %38, %39, %40, %41, %42, %43, %44, %45, %46, %47}, {%48, %49, %50, %51}, db, p, 1, 1, 1;\n}\n"
      : "=f"(d[0]), "=f"(d[1]), "=f"(d[2]), "=f"(d[3]), "=f"(d[4]), "=f"(d[5]), "=f"(d[6]), "=f"(d[7]), "=f"(d[8]), "=f"(d[9]), "=f"(d[10]), "=f"(d[11]), "=f"(d[12]), "=f"(d[13]), "=f"(d[14]), "=f"(d[15]), "=f"(d[16]), "=f"(d[17]), "=f"(d[18]), "=f"(d[19]), "=f"(d[20]), "=f"(d[21]), "=f"(d[22]), "=f"(d[23]), "=f"(d[24]), "=f"(d[25]), "=f"(d[26]), "=f"(d[27]), "=f"(d[28]), "=f"(d[29]), "=f"(d[30]), "=f"(d[31]), "=f"(d[32]), "=f"(d[33]), "=f"(d[34]), "=f"(d[35]), "=f"(d[36]), "=f"(d[37]), "=f"(d[38]), "=f"(d[39]), "=f"(d[40]), "=f"(d[41]), "=f"(d[42]), "=f"(d[43]), "=f"(d[44]), "=f"(d[45]), "=f"(d[46]), "=f"(d[47])
      : "r"(a0), "r"(a1), "r"(a2), "r"(a3), "r"(db));
  }
}
template <int SD> __device__ __forceinline__ void wgmma_rs_n64_t0(float (&d)[32], uint32_t a0, uint32_t a1, uint32_t a2, uint32_t a3, uint32_t db) {
  if constexpr (SD) {
    asm volatile("{\n.reg .pred p;\n.reg .b64 da, db;\nsetp.ne.b32 p, 1, 0;\nmov.b64 db, {%36, 112};\n"
      "wgmma.mma_async.sync.aligned.m64n64k16.f32.bf16.bf16 {%0, %1, %2, %3, %4, %5, %6, %7, %8, %9, %10, %11, %12, %13, %14, %15, %16, %17, %18, %19, %20, %21, %22, %23, %24, %25, %26, %27, %28, %29, %30, %31}, {%32, %33, %34, %35}, db, p, 1, 1, 0;\n}\n"
      : "+f"(d[0]), "+f"(d[1]), "+f"(d[2]), "+f"(d[3]), "+f"(d[4]), "+f"(d[5]), "+f"(d[6]), "+f"(d[7]), "+f"(d[8]), "+f"(d[9]), "+f"(d[10]), "+f"(d[11]), "+f"(d[12]), "+f"(d[13]), "+f"(d[14]), "+f"(d[15]), "+f"(d[16]), "+f"(d[17]), "+f"(d[18]), "+f"(d[19]), "+f"(d[20]), "+f"(d[21]), "+f"(d[22]), "+f"(d[23]), "+f"(d[24]), "+f"(d[25]), "+f"(d[26]), "+f"(d[27]), "+f"(d[28]), "+f"(d[29]), "+f"(d[30]), "+f"(d[31])
      : "r"(a0), "r"(a1), "r"(a2), "r"(a3), "r"(db));
  } else {
    asm volatile("{\n.reg .pred p;\n.reg .b64 da, db;\nsetp.ne.b32 p, 0, 0;\nmov.b64 db, {%36, 112};\n"
      "wgmma.mma_async.sync.aligned.m64n64k16.f32.bf16.bf16 {%0, %1, %2, %3, %4, %5, %6, %7, %8, %9, %10, %11, %12, %13, %14, %15, %16, %17, %18, %19, %20, %21, %22, %23, %24, %25, %26, %27, %28, %29, %30, %31}, {%32, %33, %34, %35}, db, p, 1, 1, 0;\n}\n"
      : "=f"(d[0]), "=f"(d[1]), "=f"(d[2]), "=f"(d[3]), "=f"(d[4]), "=f"(d[5]), "=f"(d[6]), "=f"(d[7]), "=f"(d[8]), "=f"(d[9]), "=f"(d[10]), "=f"(d[11]), "=f"(d[12]), "=f"(d[13]), "=f"(d[14]), "=f"(d[15]), "=f"(d[16]), "=f"(d[17]), "=f"(d[18]), "=f"(d[19]), "=f"(d[20]), "=f"(d[21]), "=f"(d[22]), "=f"(d[23]), "=f"(d[24]), "=f"(d[25]), "=f"(d[26]), "=f"(d[27]), "=f"(d[28]), "=f"(d[29]), "=f"(d[30]), "=f"(d[31])
      : "r"(a0), "r"(a1), "r"(a2), "r"(a3), "r"(db));
  }
}
template <int SD> __device__ __forceinline__ void wgmma_rs_n32_t1(float (&d)[16], uint32_t a0, uint32_t a1, uint32_t a2, uint32_t a3, uint32_t db) {
  if constexpr (SD) {
    asm volatile("{\n.reg .pred p;\n.reg .b64 da, db;\nsetp.ne.b32 p, 1, 0;\nmov.b64 db, {%20, 64};\n"
      "wgmma.mma_async.sync.aligned.m64n32k16.f32.bf16.bf16 {%0, %1, %2, %3, %4, %5, %6, %7, %8, %9, %10, %11, %12, %13, %14, %15}, {%16, %17, %18, %19}, db, p, 1, 1, 1;\n}\n"
      : "+f"(d[0]), "+f"(d[1]), "+f"(d[2]), "+f"(d[3]), "+f"(d[4]), "+f"(d[5]), "+f"(d[6]), "+f"(d[7]), "+f"(d[8]), "+f"(d[9]), "+f"(d[10]), "+f"(d[11]), "+f"(d[12]), "+f"(d[13]), "+f"(d[14]), "+f"(d[15])
      : "r"(a0), "r"(a1), "r"(a2), "r"(a3), "r"(db));
  } else {
    asm volatile("{\n.reg .pred p;\n.reg .b64 da, db;\nsetp.ne.b32 p, 0, 0;\nmov.b64 db, {%20, 64};\n"
      "wgmma.mma_async.sync.aligned.m64n32k16.f32.bf16.bf16 {%0, %1, %2, %3, %4, %5, %6, %7, %8, %9, %10, %11, %12, %13, %14, %15}, {%16, %17, %18, %19}, db, p, 1, 1, 1;\n}\n"
      : "=f"(d[0]), "=f"(d[1]), "=f"(d[2]), "=f"(d[3]), "=f"(d[4]), "=f"(d[5]), "=f"(d[6]), "=f"(d[7]), "=f"(d[8]), "=f"(d[9]), "=f"(d[10]), "=f"(d[11]), "=f"(d[12]), "=f"(d[13]), "=f"(d[14]), "=f"(d[15])
      : "r"(a0), "r"(a1), "r"(a2), "r"(a3), "r"(db));
  }
}
template <int SD> __device__ __forceinline__ void wgmma_rs_n8_t0(float (&d)[4], uint32_t a0, uint32_t a1, uint32_t a2, uint32_t a3, uint32_t db) {
  if constexpr (SD) {
    asm volatile("{\n.reg .pred p;\n.reg .b64 da, db;\nsetp.ne.b32 p, 1, 0;\nmov.b64 db, {%8, 16};\n"
      "wgmma.mma_async.sync.aligned.m64n8k16.f32.bf16.bf16 {%0, %1, %2, %3}, {%4, %5, %6, %7}, db, p, 1, 1, 0;\n}\n"
      : "+f"(d[0]), "+f"(d[1]), "+f"(d[2]), "+f"(d[3])
      : "r"(a0), "r"(a1), "r"(a2), "r"(a3), "r"(db));
  } else {
    asm volatile("{\n.reg .pred p;\n.reg .b64 da, db;\nsetp.ne.b32 p, 0, 0;\nmov.b64 db, {%8, 16};\n"
      "wgmma.mma_async.sync.aligned.m64n8k16.f32.bf16.bf16 {%0, %1, %2, %3}, {%4, %5, %6, %7}, db, p, 1, 1, 0;\n}\n"
      : "=f"(d[0]), "=f"(d[1]), "=f"(d[2]), "=f"(d[3])
      : "r"(a0), "r"(a1), "r"(a2), "r"(a3), "r"(db));
  }
}

__device__ __forceinline__ void wg_fence()  { asm volatile("wgmma.fence.sync.aligned;" ::: "memory"); }
__device__ __forceinline__ void wg_commit() { asm volatile("wgmma.commit_group.sync.aligned;" ::: "memory"); }
template <int N> __device__ __forceinline__ void wg_wait() { asm volatile("wgmma.wait_group.sync.aligned %0;" :: "n"(N) : "memory"); }
template <int N> __device__ __forceinline__ void fence_regs(float (&d)[N]) {
#pragma unroll
  for (int i = 0; i < N; i++) asm volatile("" : "+f"(d[i]) :: "memory");
}
__device__ __forceinline__ constexpr uint32_t mk_desc(uint32_t addr, uint32_t lbo) { return (addr >> 4) | ((lbo >> 4) << 16); }
__device__ __forceinline__ uint32_t pack_bf16(float lo, float hi) {
  uint32_t r; asm("cvt.rn.bf16x2.f32 %0, %1, %2;" : "=r"(r) : "f"(hi), "f"(lo)); return r;
}
__device__ __forceinline__ uint32_t hmul2(uint32_t a, uint32_t b) {
  uint32_t r; asm("mul.rn.bf16x2 %0, %1, %2;" : "=r"(r) : "r"(a), "r"(b)); return r;
}
__device__ __forceinline__ uint32_t hfma2(uint32_t a, uint32_t b, uint32_t c) {
  uint32_t r; asm("fma.rn.bf16x2 %0, %1, %2, %3;" : "=r"(r) : "r"(a), "r"(b), "r"(c)); return r;
}
__device__ __forceinline__ float ex2(float x) { float r; asm("ex2.approx.ftz.f32 %0, %1;" : "=f"(r) : "f"(x)); return r; }
__device__ __forceinline__ float lg2(float x) { float r; asm("lg2.approx.ftz.f32 %0, %1;" : "=f"(r) : "f"(x)); return r; }
__device__ __forceinline__ float rsq(float x) { float r; asm("rsqrt.approx.ftz.f32 %0, %1;" : "=f"(r) : "f"(x)); return r; }
__device__ __forceinline__ float rcp(float x) { float r; asm("rcp.approx.ftz.f32 %0, %1;" : "=f"(r) : "f"(x)); return r; }
__device__ __forceinline__ void stsm4(uint32_t addr, uint32_t r0, uint32_t r1, uint32_t r2, uint32_t r3) {
  asm volatile("stmatrix.sync.aligned.m8n8.x4.shared.b16 [%0], {%1,%2,%3,%4};" :: "r"(addr), "r"(r0), "r"(r1), "r"(r2), "r"(r3) : "memory");
}
__device__ __forceinline__ void fence_async() { asm volatile("fence.proxy.async.shared::cta;" ::: "memory"); }
__device__ __forceinline__ void bar_wg(int id) { asm volatile("bar.sync %0, 128;" :: "r"(id) : "memory"); }
__device__ __forceinline__ bool bar_wg_or(int id, bool v) {
  uint32_t r;
  asm volatile("{\n.reg .pred p, q;\nsetp.ne.u32 q, %2, 0;\nbar.red.or.pred p, %1, 128, q;\nselp.u32 %0, 1, 0, p;\n}\n"
               : "=r"(r) : "r"(id), "r"((uint32_t)v) : "memory");
  return r != 0;
}
__device__ __forceinline__ void mbar_init(uint32_t bar, uint32_t cnt) { asm volatile("mbarrier.init.shared::cta.b64 [%0], %1;" :: "r"(bar), "r"(cnt) : "memory"); }
__device__ __forceinline__ void mbar_expect(uint32_t bar, uint32_t bytes) {
  asm volatile("mbarrier.arrive.expect_tx.shared::cta.b64 _, [%0], %1;" :: "r"(bar), "r"(bytes) : "memory");
}
__device__ __forceinline__ void mbar_wait(uint32_t bar, uint32_t parity) {
  uint32_t ok, spins = 0;
  do {
    asm volatile("{\n.reg .pred p;\nmbarrier.try_wait.parity.shared::cta.b64 p, [%1], %2;\nselp.u32 %0, 1, 0, p;\n}\n"
                 : "=r"(ok) : "r"(bar), "r"(parity) : "memory");
    if (!ok && ++spins > (1u << 22)) __trap();
  } while (!ok);
}
__device__ __forceinline__ void tma5(uint32_t dst, const CUtensorMap* m, uint32_t bar, int c0, int c1, int c2, int c3, int c4) {
  asm volatile("cp.async.bulk.tensor.5d.shared::cluster.global.mbarrier::complete_tx::bytes [%0], [%1, {%3, %4, %5, %6, %7}], [%2];"
               :: "r"(dst), "l"(m), "r"(bar), "r"(c0), "r"(c1), "r"(c2), "r"(c3), "r"(c4) : "memory");
}
__device__ __forceinline__ void tma3(uint32_t dst, const CUtensorMap* m, uint32_t bar, int c0, int c1, int c2) {
  asm volatile("cp.async.bulk.tensor.3d.shared::cluster.global.mbarrier::complete_tx::bytes [%0], [%1, {%3, %4, %5}], [%2];"
               :: "r"(dst), "l"(m), "r"(bar), "r"(c0), "r"(c1), "r"(c2) : "memory");
}
__device__ __forceinline__ uint4 lds128(uint32_t addr) {
  uint4 v; asm volatile("ld.shared.v4.u32 {%0,%1,%2,%3}, [%4];" : "=r"(v.x), "=r"(v.y), "=r"(v.z), "=r"(v.w) : "r"(addr)); return v;
}
__device__ __forceinline__ uint4 ldg128_stream(const void* p) {
  uint4 v; asm volatile("ld.global.nc.L1::no_allocate.v4.u32 {%0,%1,%2,%3}, [%4];" : "=r"(v.x), "=r"(v.y), "=r"(v.z), "=r"(v.w) : "l"(p)); return v;
}
__device__ __forceinline__ void stg128(void* p, uint32_t a, uint32_t b, uint32_t c, uint32_t d) {
  asm volatile("st.global.v4.u32 [%0], {%1,%2,%3,%4};" :: "l"(p), "r"(a), "r"(b), "r"(c), "r"(d) : "memory");
}
__device__ __forceinline__ void prefetch_l2(const void* p, uint32_t bytes) {
  asm volatile("cp.async.bulk.prefetch.L2.global [%0], %1;" :: "l"(p), "r"(bytes) : "memory");
}
__device__ __forceinline__ float bf_lo(uint32_t u) { return __uint_as_float(u << 16); }
__device__ __forceinline__ float bf_hi(uint32_t u) { return __uint_as_float(u & 0xFFFF0000u); }
__device__ __forceinline__ float rbf(float x) { return __bfloat162float(__float2bfloat16_rn(x)); }
__device__ __forceinline__ int orig_tok(int r) { return ((r & 31) >> 2) * 8 + (r >> 5) * 4 + (r & 3); }

__device__ __forceinline__ void softmax_fast(const float (&s)[32], uint32_t (&p)[16], uint32_t eb_addr) {
#pragma unroll
  for (int j = 0; j < 4; j++) {
    const uint4 e = lds128(eb_addr + j * 512);
    p[4 * j + 0] = hmul2(pack_bf16(ex2(s[8 * j + 0]), ex2(s[8 * j + 1])), e.x);
    p[4 * j + 1] = hmul2(pack_bf16(ex2(s[8 * j + 2]), ex2(s[8 * j + 3])), e.y);
    p[4 * j + 2] = hmul2(pack_bf16(ex2(s[8 * j + 4]), ex2(s[8 * j + 5])), e.z);
    p[4 * j + 3] = hmul2(pack_bf16(ex2(s[8 * j + 6]), ex2(s[8 * j + 7])), e.w);
  }
}
__device__ __forceinline__ void softmax_true_max(float (&s)[32], uint32_t (&p)[16], uint32_t eb_addr, bool masked,
                                                 const __nv_bfloat16* mrow) {
#pragma unroll
  for (int j = 0; j < 4; j++) {
    const uint4 e = lds128(eb_addr + j * 512);
    s[8 * j + 0] += lg2(bf_lo(e.x)); s[8 * j + 1] += lg2(bf_hi(e.x));
    s[8 * j + 2] += lg2(bf_lo(e.y)); s[8 * j + 3] += lg2(bf_hi(e.y));
    s[8 * j + 4] += lg2(bf_lo(e.z)); s[8 * j + 5] += lg2(bf_hi(e.z));
    s[8 * j + 6] += lg2(bf_lo(e.w)); s[8 * j + 7] += lg2(bf_hi(e.w));
  }
  if (masked) {
#pragma unroll
    for (int g = 0; g < 8; g++) {
      const int co = (g & 3) * 16 + (g >> 2) * 4;
      uint32_t m0 = *reinterpret_cast<const uint32_t*>(mrow + co);
      uint32_t m1 = *reinterpret_cast<const uint32_t*>(mrow + 16 * 64 + co);
      s[4 * g + 0] = fmaf(bf_lo(m0), LOG2E, s[4 * g + 0]); s[4 * g + 1] = fmaf(bf_hi(m0), LOG2E, s[4 * g + 1]);
      s[4 * g + 2] = fmaf(bf_lo(m1), LOG2E, s[4 * g + 2]); s[4 * g + 3] = fmaf(bf_hi(m1), LOG2E, s[4 * g + 3]);
    }
  }
  float m0 = s[0], m1 = s[2];
#pragma unroll
  for (int g = 0; g < 8; g++) {
    m0 = fmaxf(m0, fmaxf(s[4 * g + 0], s[4 * g + 1]));
    m1 = fmaxf(m1, fmaxf(s[4 * g + 2], s[4 * g + 3]));
  }
  m0 = fmaxf(m0, __shfl_xor_sync(0xffffffffu, m0, 1)); m0 = fmaxf(m0, __shfl_xor_sync(0xffffffffu, m0, 2));
  m1 = fmaxf(m1, __shfl_xor_sync(0xffffffffu, m1, 1)); m1 = fmaxf(m1, __shfl_xor_sync(0xffffffffu, m1, 2));
#pragma unroll
  for (int g = 0; g < 8; g++) {
    p[2 * g + 0] = pack_bf16(ex2(s[4 * g + 0] - m0), ex2(s[4 * g + 1] - m0));
    p[2 * g + 1] = pack_bf16(ex2(s[4 * g + 2] - m1), ex2(s[4 * g + 3] - m1));
  }
}
template <int H> __device__ __forceinline__ void issue_s(float (&s)[32], const uint32_t (&q)[24], uint32_t dK) {
  constexpr int Q0 = (H == 0 ? 0 : H == 1 ? 4 : H == 2 ? 12 : 16), P0 = (H == 0 ? 0 : H == 1 ? 3 : H == 2 ? 7 : 10);
  wgmma_rs_n64_t0<0>(s, q[Q0], q[Q0 + 1], q[Q0 + 2], q[Q0 + 3], dK + P0 * 8);
  wgmma_rs_n64_t0<1>(s, q[Q0 + 4], q[Q0 + 5], q[Q0 + 6], q[Q0 + 7], dK + P0 * 8 + 16);
}
template <int H> __device__ __forceinline__ void issue_pv(float (&o)[16], const uint32_t (&p)[16], uint32_t dV) {
  constexpr int P0 = (H == 0 ? 0 : H == 1 ? 3 : H == 2 ? 7 : 10);
  wgmma_rs_n32_t1<0>(o, p[0], p[1], p[2], p[3], dV + P0 * 64);
  wgmma_rs_n32_t1<1>(o, p[4], p[5], p[6], p[7], dV + P0 * 64 + 16);
  wgmma_rs_n32_t1<1>(o, p[8], p[9], p[10], p[11], dV + P0 * 64 + 32);
  wgmma_rs_n32_t1<1>(o, p[12], p[13], p[14], p[15], dV + P0 * 64 + 48);
}
__device__ __forceinline__ void sumsq(const uint32_t (&f)[24], uint32_t (&sq)[8], uint32_t init) {
#pragma unroll
  for (int h = 0; h < 4; h++)
#pragma unroll
    for (int r = 0; r < 2; r++) {
      uint32_t u = f[6 * h + r], v = f[6 * h + 2 + r], w = f[6 * h + 4 + r];
      sq[2 * h + r] = hfma2(w, w, hfma2(v, v, hfma2(u, u, init)));
    }
}
__device__ __forceinline__ void scale_heads(uint32_t (&f)[24], const float (&r)[8]) {
#pragma unroll
  for (int h = 0; h < 4; h++)
#pragma unroll
    for (int q = 0; q < 2; q++) {
      uint32_t p = pack_bf16(r[2 * h + q], r[2 * h + q]);
#pragma unroll
      for (int c = 0; c < 3; c++) f[6 * h + 2 * c + q] = hmul2(f[6 * h + 2 * c + q], p);
    }
}
template <int ODD> __device__ __forceinline__ void norm_o(const float (&o)[16], uint32_t* of) {
  constexpr int SO = ODD ? 0 : 12, VO = ODD ? 4 : 0;
  float r0 = rcp(o[SO]), r1 = rcp(o[SO + 2]);
  uint32_t p0 = pack_bf16(r0, r0), p1 = pack_bf16(r1, r1);
#pragma unroll
  for (int g = 0; g < 3; g++) {
    of[2 * g + 0] = hmul2(pack_bf16(o[VO + 4 * g + 0], o[VO + 4 * g + 1]), p0);
    of[2 * g + 1] = hmul2(pack_bf16(o[VO + 4 * g + 2], o[VO + 4 * g + 3]), p1);
  }
}
template <int H> __device__ __forceinline__ void slow_head(const uint32_t (&q)[24], uint32_t* of, uint32_t dK, uint32_t dV, uint32_t eb_base,
                                                           bool true_max, bool masked, const __nv_bfloat16* mrow) {
  float s[32], o[16]; uint32_t p[16];
  wg_fence(); issue_s<H>(s, q, dK); wg_commit();
  wg_wait<0>(); fence_regs(s);
  if (true_max) softmax_true_max(s, p, eb_base + H * 8192, masked, mrow); else softmax_fast(s, p, eb_base + H * 8192);
  wg_fence(); issue_pv<H>(o, p, dV); wg_commit();
  wg_wait<0>(); fence_regs(o);
  norm_o<H & 1>(o, of + 6 * H);
}

#define TL(i)

__global__ void __launch_bounds__(384, 1)
swin_kernel(const __grid_constant__ CUtensorMap tm_x, const __grid_constant__ CUtensorMap tm_xq, const __grid_constant__ CUtensorMap tm_w,
            const __nv_bfloat16* __restrict__ wo,
            const __nv_bfloat16* __restrict__ logit_scale, const __nv_bfloat16* __restrict__ w1, const __nv_bfloat16* __restrict__ w2,
            const __nv_bfloat16* __restrict__ coords, const int* __restrict__ rel_idx, const __nv_bfloat16* __restrict__ mask,
            __nv_bfloat16* __restrict__ out) {
  extern __shared__ __align__(1024) uint8_t smem[];
  constexpr uint32_t sb = 1024;
  if ((uint32_t)__cvta_generic_to_shared(smem) != sb) __trap();
  const int tid = threadIdx.x, lane = tid & 31;
  const int warp = __shfl_sync(0xffffffffu, (tid >> 5) & 3, 0), wg = __shfl_sync(0xffffffffu, tid >> 7, 0);
  const int g = lane >> 2, t = lane & 3;
  const int stride = 3 * gridDim.x;
  int win = wg * gridDim.x + blockIdx.x;
  const uint32_t wgb = sb + SM_WG + wg * WG_SZ;
  const uint32_t bar_x = sb + SM_BAR + 8 + 8 * wg;
  const char* mb = reinterpret_cast<const char*>(mask);
  TL(0);

  auto load_x = [&](int w) {
    const int wy = w / NWX, wx = w - wy * NWX;
    mbar_expect(bar_x, 12288);
    if (wy != NWX - 1 && wx != NWX - 1) {
      tma5(wgb + WG_X, &tm_x, bar_x, 0, 0, wy * 8 + 4, wx * 2 + 1, 0);
    } else {
      for (int q = 0; q < 4; q++) {
        int y = wy * 8 + 4 + (q & 1) * 4; if (y >= IMG) y -= IMG;
        int xq = wx * 2 + 1 + (q >> 1);   if (xq >= IMG / 4) xq -= IMG / 4;
        for (int c = 0; c < 3; c++) tma5(wgb + WG_X + c * 4096 + q * 1024, &tm_xq, bar_x, 0, 0, y, xq, c);
      }
    }
  };
  auto mask_word = [&](int w) -> uint32_t {
    const char* src = mb + (size_t)w * 8192 + (tid & 127) * 16;
    uint4 a = ldg128_stream(src), b = ldg128_stream(src + 2048), c = ldg128_stream(src + 4096), d = ldg128_stream(src + 6144);
    return (a.x | a.y | a.z | a.w | b.x | b.y | b.z | b.w) | (c.x | c.y | c.z | c.w | d.x | d.y | d.z | d.w);
  };

  if ((tid & 127) == 0) {
    mbar_init(bar_x, 1);
    if (wg == 0) mbar_init(sb + SM_BAR, 1);
    fence_async();
    if (win < NWIN) load_x(win);
    if (wg == 0) { mbar_expect(sb + SM_BAR, 9 * 6144); tma3(sb + SM_W, &tm_w, sb + SM_BAR, 0, 0, 0); }
    if (win + stride < NWIN) prefetch_l2(mb + (size_t)(win + stride) * 8192, 8192);
  }
  uint32_t mword = (win < NWIN) ? mask_word(win) : 0u;
  float* tab = reinterpret_cast<float*>(smem + SM_TAB);
  const uint2 lsw = *reinterpret_cast<const uint2*>(logit_scale);
  int2 rid[8];
  if (tid >= 128) {
    const int task = (tid >> 5) - 4;
    const int* rrow = rel_idx + orig_tok(16 * (task >> 1) + 8 * (task & 1) + g) * 64 + (t >> 1) * 8 + (t & 1) * 2;
#pragma unroll
    for (int G = 0; G < 8; G++) rid[G] = *reinterpret_cast<const int2*>(rrow + (G & 3) * 16 + (G >> 2) * 4);
  }
  if (tid < 96) {
    uint4 v[12];
#pragma unroll
    for (int i = 0; i < 12; i++) v[i] = *reinterpret_cast<const uint4*>(wo + tid * 96 + i * 8);
    float sum = 0.f;
#pragma unroll
    for (int i = 0; i < 12; i++)
      sum += (bf_lo(v[i].x) + bf_hi(v[i].x)) + (bf_lo(v[i].y) + bf_hi(v[i].y)) + (bf_lo(v[i].z) + bf_hi(v[i].z)) + (bf_lo(v[i].w) + bf_hi(v[i].w));
    const float mu = sum * (1.f / 96.f);
    auto cen = [&](uint32_t u) { return pack_bf16(bf_lo(u) - mu, bf_hi(u) - mu); };
    uint8_t* dst = smem + SM_WO + (tid >> 3) * 128 + (tid & 7) * 16;
#pragma unroll
    for (int j = 0; j < 3; j++) {
      *reinterpret_cast<uint4*>(dst + (4 * j + 0) * 1536) = make_uint4(cen(v[4 * j].x), cen(v[4 * j + 1].x), cen(v[4 * j + 2].x), cen(v[4 * j + 3].x));
      *reinterpret_cast<uint4*>(dst + (4 * j + 1) * 1536) = make_uint4(cen(v[4 * j].y), cen(v[4 * j + 1].y), cen(v[4 * j + 2].y), cen(v[4 * j + 3].y));
      *reinterpret_cast<uint4*>(dst + (4 * j + 2) * 1536) = make_uint4(cen(v[4 * j].z), cen(v[4 * j + 1].z), cen(v[4 * j + 2].z), cen(v[4 * j + 3].z));
      *reinterpret_cast<uint4*>(dst + (4 * j + 3) * 1536) = make_uint4(cen(v[4 * j].w), cen(v[4 * j + 1].w), cen(v[4 * j + 2].w), cen(v[4 * j + 3].w));
    }
  } else if (tid < 112) {
    const int i = tid - 96;
    const uint32_t v = (((i >> 3) ^ i) & 1) ? 0u : 0x3F803F80u;
    *reinterpret_cast<uint4*>(smem + SM_SEL + i * 16) = make_uint4(v, v, v, v);
  } else if (tid >= 128 && tid < 128 + 225) {
    const int i = tid - 128;
    const uint32_t cw = *reinterpret_cast<const uint32_t*>(coords + 2 * i);
    uint32_t a[16], b[32];
#pragma unroll
    for (int j = 0; j < 4; j++) *reinterpret_cast<uint4*>(a + 4 * j) = *reinterpret_cast<const uint4*>(w1 + 8 * j);
#pragma unroll
    for (int j = 0; j < 8; j++) *reinterpret_cast<uint4*>(b + 4 * j) = *reinterpret_cast<const uint4*>(w2 + 8 * j);
    const float c0 = bf_lo(cw), c1 = bf_hi(cw);
    float z[4] = {0.f, 0.f, 0.f, 0.f};
#pragma unroll
    for (int j = 0; j < 16; j++) {
      const float u = (j & 1) ? bf_hi(a[j >> 1]) : bf_lo(a[j >> 1]), v = (j & 1) ? bf_hi(a[8 + (j >> 1)]) : bf_lo(a[8 + (j >> 1)]);
      float h = rbf(fmaf(c1, v, c0 * u));
      h = h > 0.f ? h : h * 0.f;
      z[0] = fmaf(h, bf_lo(b[2 * j]), z[0]); z[1] = fmaf(h, bf_hi(b[2 * j]), z[1]);
      z[2] = fmaf(h, bf_lo(b[2 * j + 1]), z[2]); z[3] = fmaf(h, bf_hi(b[2 * j + 1]), z[3]);
    }
    float4 r;
    r.x = 16.f * rbf(rcp(1.f + ex2(-LOG2E * rbf(z[0])))); r.y = 16.f * rbf(rcp(1.f + ex2(-LOG2E * rbf(z[1]))));
    r.z = 16.f * rbf(rcp(1.f + ex2(-LOG2E * rbf(z[2])))); r.w = 16.f * rbf(rcp(1.f + ex2(-LOG2E * rbf(z[3]))));
    *reinterpret_cast<float4*>(tab + 4 * i) = r;
  }
  {
    const int i = tid & 127;
    uint8_t* vt = smem + SM_WG + wg * WG_SZ + WG_V;
    *reinterpret_cast<uint4*>(vt + (i < 64 ? 3 : 10) * 1024 + (i & 63) * 16) = make_uint4(0x3F803F80u, 0x3F803F80u, 0x3F803F80u, 0x3F803F80u);
    uint8_t* kt = smem + SM_WG + wg * WG_SZ + WG_K;
    *reinterpret_cast<uint4*>(kt + (i >> 4) * 1792 + ((i & 8) ? 10 : 3) * 128 + (i & 7) * 16) = make_uint4(0u, 0u, 0u, 0u);
  }
  float tau[4]; uint32_t slow_heads = 0;
  {
    const float ls[4] = {bf_lo(lsw.x), bf_hi(lsw.x), bf_lo(lsw.y), bf_hi(lsw.y)};
#pragma unroll
    for (int h = 0; h < 4; h++) {
      const float c = ls[h] < -100.f ? -100.f : (ls[h] > 4.59375f ? 4.59375f : ls[h]);
      tau[h] = rbf(expf(c)) * LOG2E;
      if (!(tau[h] * 2.04f <= 80.f)) slow_heads |= 1u << h;
    }
  }
  slow_heads = __shfl_sync(0xffffffffu, slow_heads, 0);
  if (tid == 0) *reinterpret_cast<float4*>(smem + SM_MISC) = make_float4(tau[0], tau[1], tau[2], tau[3]);
  __syncthreads();
  if (tid >= 128) {
    const int task = (tid >> 5) - 4, w = task >> 1, r = task & 1;
    float b[16][4];
#pragma unroll
    for (int G = 0; G < 8; G++) {
      float4 u = *reinterpret_cast<const float4*>(tab + 4 * rid[G].x), v = *reinterpret_cast<const float4*>(tab + 4 * rid[G].y);
      b[2 * G][0] = u.x; b[2 * G][1] = u.y; b[2 * G][2] = u.z; b[2 * G][3] = u.w;
      b[2 * G + 1][0] = v.x; b[2 * G + 1][1] = v.y; b[2 * G + 1][2] = v.z; b[2 * G + 1][3] = v.w;
    }
#pragma unroll
    for (int h = 0; h < 4; h++) {
      float m = b[0][h];
#pragma unroll
      for (int i = 1; i < 16; i++) m = fmaxf(m, b[i][h]);
      m = fmaxf(m, __shfl_xor_sync(0xffffffffu, m, 1));
      m = fmaxf(m, __shfl_xor_sync(0xffffffffu, m, 2));
      m *= LOG2E;
      if (!((slow_heads >> h) & 1)) m += 1.02f * tau[h];
#pragma unroll
      for (int G = 0; G < 8; G++) {
        uint32_t e = pack_bf16(ex2(fmaf(b[2 * G][h], LOG2E, -m)), ex2(fmaf(b[2 * G + 1][h], LOG2E, -m)));
        *reinterpret_cast<uint32_t*>(smem + SM_EB + ((h * 4 + w) * 4 + (G >> 1)) * 512 + lane * 16 + ((G & 1) * 2 + r) * 4) = e;
      }
    }
  }
  fence_async();
  __syncthreads();
  TL(1);
  mbar_wait(sb + SM_BAR, 0);
  TL(2);

  const uint32_t dX  = mk_desc(wgb + WG_X, 16);
  constexpr uint32_t dW   = mk_desc(sb + SM_W, 6144);
  constexpr uint32_t dWo  = mk_desc(sb + SM_WO, 128);
  constexpr uint32_t dSel = mk_desc(sb + SM_SEL, 128);
  constexpr uint32_t dOne = mk_desc(sb + SM_WG + WG_V + 3 * 1024, 128);
  const uint32_t dK  = mk_desc(wgb + WG_K, 128);
  const uint32_t dV  = mk_desc(wgb + WG_V, 128);
  const uint32_t k_dst = wgb + WG_K + (2 * warp + ((lane >> 3) & 1)) * 1792 + (lane >> 4) * 896 + (lane & 7) * 16;
  const uint32_t v_dst = wgb + WG_V + (lane >> 4) * 7168 + (2 * warp + ((lane >> 3) & 1)) * 128 + (lane & 7) * 16;
  const uint32_t eb_base = sb + SM_EB + warp * 2048 + lane * 16;
  const int bar_id = 1 + wg;
  uint32_t xphase = 0;

  for (; win < NWIN; win += stride) {
    const int nxt = win + stride;
    TL(0);
    mbar_wait(bar_x, xphase); xphase ^= 1;
    TL(1);
    float qk[96], vv[48];
    wg_fence();
#pragma unroll
    for (int s = 0; s < 6; s++) {
      const uint32_t a = dX + (s >> 1) * 256 + (s & 1) * 2, b = dW + s * 64;
      if (s == 0) wgmma_ss_n192_t1<0>(qk, a, b); else wgmma_ss_n192_t1<1>(qk, a, b);
    }
    wg_commit();
    const bool masked = bar_wg_or(bar_id + 4, (mword & 0x7FFF7FFFu) != 0u);
    wg_wait<0>();
    fence_regs(qk);
    TL(2);
    uint32_t qa[24], ka[24];
#pragma unroll
    for (int i = 0; i < 24; i++) { qa[i] = pack_bf16(qk[2 * i], qk[2 * i + 1]); ka[i] = pack_bf16(qk[48 + 2 * i], qk[48 + 2 * i + 1]); }
    {
      uint32_t sq[8], sk[8];
      const uint32_t EPS8 = 0x2A0D2A0Du;
      sumsq(ka, sk, EPS8);
      sumsq(qa, sq, EPS8);
      float k01[4], k23[4], q01[4], q23[4];
      wg_fence();
      wgmma_rs_n8_t0<0>(k01, sk[0], sk[1], sk[2], sk[3], dSel);
      wgmma_rs_n8_t0<0>(k23, sk[4], sk[5], sk[6], sk[7], dSel);
      wgmma_rs_n8_t0<0>(q01, sq[0], sq[1], sq[2], sq[3], dSel);
      wgmma_rs_n8_t0<0>(q23, sq[4], sq[5], sq[6], sq[7], dSel);
      wg_commit();
#pragma unroll
      for (int s = 0; s < 6; s++) {
        const uint32_t a = dX + (s >> 1) * 256 + (s & 1) * 2, b = dW + 6 * 384 + s * 64;
        if (s == 0) wgmma_ss_n96_t1<0>(vv, a, b); else wgmma_ss_n96_t1<1>(vv, a, b);
      }
      wg_commit();
      const uint4 qs = lds128(sb + SM_MISC);
      wg_wait<1>();
      fence_regs(k01); fence_regs(k23); fence_regs(q01); fence_regs(q23);
      TL(3);
      const float rk[8] = {rsq(k01[0]), rsq(k01[2]), rsq(k01[1]), rsq(k01[3]), rsq(k23[0]), rsq(k23[2]), rsq(k23[1]), rsq(k23[3])};
      scale_heads(ka, rk);
#pragma unroll
      for (int i = 0; i < 6; i++) stsm4(k_dst + (i + (i >= 3)) * 128, ka[2 * i], ka[2 * i + 1], ka[12 + 2 * i], ka[12 + 2 * i + 1]);
      const float s0 = __uint_as_float(qs.x), s1 = __uint_as_float(qs.y), s2 = __uint_as_float(qs.z), s3 = __uint_as_float(qs.w);
      const float rq[8] = {rsq(q01[0]) * s0, rsq(q01[2]) * s0, rsq(q01[1]) * s1, rsq(q01[3]) * s1,
                           rsq(q23[0]) * s2, rsq(q23[2]) * s2, rsq(q23[1]) * s3, rsq(q23[3]) * s3};
      scale_heads(qa, rq);
    }
    TL(4);
    wg_wait<0>();
    fence_regs(vv);
    TL(5);
#pragma unroll
    for (int i = 0; i < 6; i++)
      stsm4(v_dst + (i + (i >= 3)) * 1024, pack_bf16(vv[4 * i], vv[4 * i + 1]), pack_bf16(vv[4 * i + 2], vv[4 * i + 3]),
            pack_bf16(vv[24 + 4 * i], vv[24 + 4 * i + 1]), pack_bf16(vv[24 + 4 * i + 2], vv[24 + 4 * i + 3]));
    fence_async();
    bar_wg(bar_id);
    TL(6);
    if ((tid & 127) == 0) {
      if (nxt < NWIN) load_x(nxt);
      if (nxt + stride < NWIN) prefetch_l2(mb + (size_t)(nxt + stride) * 8192, 8192);
    }
    __syncwarp();

    uint32_t of[24];
    if (!masked && slow_heads == 0) {
      float sA[32], sB[32], oA[16], oB[16];
      uint32_t pA[16], pB[16];
      wg_fence();
      issue_s<0>(sA, qa, dK); wg_commit();
      issue_s<1>(sB, qa, dK); wg_commit();
      wg_wait<1>(); fence_regs(sA);
      TL(7);
      softmax_fast(sA, pA, eb_base);
      wg_fence();
      issue_pv<0>(oA, pA, dV); wg_commit();
      issue_s<2>(sA, qa, dK); wg_commit();
      wg_wait<2>(); fence_regs(sB);
      TL(8);
      softmax_fast(sB, pB, eb_base + 8192);
      wg_fence();
      issue_pv<1>(oB, pB, dV); wg_commit();
      issue_s<3>(sB, qa, dK); wg_commit();
      wg_wait<2>(); fence_regs(sA); fence_regs(oA);
      TL(9);
      norm_o<0>(oA, of);
      softmax_fast(sA, pA, eb_base + 2 * 8192);
      wg_fence();
      issue_pv<2>(oA, pA, dV); wg_commit();
      wg_wait<1>(); fence_regs(sB); fence_regs(oB);
      TL(10);
      norm_o<1>(oB, of + 6);
      softmax_fast(sB, pB, eb_base + 3 * 8192);
      wg_fence();
      issue_pv<3>(oB, pB, dV); wg_commit();
      wg_wait<1>(); fence_regs(oA);
      norm_o<0>(oA, of + 12);
      wg_wait<0>(); fence_regs(oB);
      norm_o<1>(oB, of + 18);
    } else {
      const __nv_bfloat16* mrow = mask + (size_t)win * 4096 + orig_tok(16 * warp + g) * 64 + (t >> 1) * 8 + (t & 1) * 2;
      const uint32_t tm = masked ? 0xFu : slow_heads;
      slow_head<0>(qa, of, dK, dV, eb_base, tm & 1, masked, mrow);
      slow_head<1>(qa, of, dK, dV, eb_base, tm & 2, masked, mrow);
      slow_head<2>(qa, of, dK, dV, eb_base, tm & 4, masked, mrow);
      slow_head<3>(qa, of, dK, dV, eb_base, tm & 8, masked, mrow);
    }
    TL(11);

    float y[48];
    wg_fence();
#pragma unroll
    for (int s = 0; s < 6; s++) {
      if (s == 0) wgmma_rs_n96_t1<0>(y, of[0], of[1], of[2], of[3], dWo);
      else wgmma_rs_n96_t1<1>(y, of[4 * s], of[4 * s + 1], of[4 * s + 2], of[4 * s + 3], dWo + s * 16);
    }
    wg_commit();
    mword = (nxt < NWIN) ? mask_word(nxt) : 0u;
    char* optr;
    {
      const int wy = win / NWX, wx = win - wy * NWX;
      int py = wy * 8 + 4 + (warp & 1) * 4;  if (py >= IMG) py -= IMG;
      int px = wx * 8 + 4 + (warp >> 1) * 4; if (px >= IMG) px -= IMG;
      optr = reinterpret_cast<char*>(out) + (uint32_t)((py + (g >> 2)) * IMG + px + (g & 3)) * PIXB + t * 16;
    }
    wg_wait<0>(); fence_regs(y);
    TL(12);
    uint32_t yb[24], sy[8];
#pragma unroll
    for (int i = 0; i < 24; i++) yb[i] = pack_bf16(y[2 * i], y[2 * i + 1]);
    sumsq(yb, sy, 0u);
    float var[4];
    wg_fence();
    wgmma_rs_n8_t0<0>(var, sy[0], sy[1], sy[2], sy[3], dOne);
    wgmma_rs_n8_t0<1>(var, sy[4], sy[5], sy[6], sy[7], dOne);
    wg_commit();
    wg_wait<0>(); fence_regs(var);
    TL(13);
    const float r0 = rsq(fmaf(var[0], 1.f / 96.f, 1e-5f)), r1 = rsq(fmaf(var[2], 1.f / 96.f, 1e-5f));
    const uint32_t n0 = pack_bf16(r0, r0), n1 = pack_bf16(r1, r1);
#pragma unroll
    for (int j = 0; j < 3; j++) {
      stg128(optr + j * 64, hmul2(yb[8 * j], n0), hmul2(yb[8 * j + 2], n0), hmul2(yb[8 * j + 4], n0), hmul2(yb[8 * j + 6], n0));
      stg128(optr + 2 * ROWB + j * 64, hmul2(yb[8 * j + 1], n1), hmul2(yb[8 * j + 3], n1), hmul2(yb[8 * j + 5], n1), hmul2(yb[8 * j + 7], n1));
    }
    TL(14);
  }
}

typedef CUresult (*EncodeFn)(CUtensorMap*, CUtensorMapDataType, cuuint32_t, void*, const cuuint64_t*, const cuuint64_t*,
                             const cuuint32_t*, const cuuint32_t*, CUtensorMapInterleave, CUtensorMapSwizzle,
                             CUtensorMapL2promotion, CUtensorMapFloatOOBfill);

}

extern "C" void kernel_launch(void* const* d_in, const int* in_sizes, int n_in, void* d_out, int out_size) {
  static int sms = 0;
  static EncodeFn encode = nullptr;
  if (sms == 0) {
    int dev = 0;
    cudaGetDevice(&dev);
    cudaDeviceGetAttribute(&sms, cudaDevAttrMultiProcessorCount, dev);
    cudaFuncSetAttribute(swin_kernel, cudaFuncAttributeMaxDynamicSharedMemorySize, SM_TOTAL);
    cudaDriverEntryPointQueryResult qr;
    void* fn = nullptr;
    cudaGetDriverEntryPoint("cuTensorMapEncodeTiled", &fn, cudaEnableDefault, &qr);
    encode = (EncodeFn)fn;
  }
  CUtensorMap tm_x, tm_xq, tm_w;
  {
    cuuint64_t dims[5] = {32, 4, IMG, IMG / 4, 3};
    cuuint64_t strides[4] = {PIXB, ROWB, 4 * PIXB, 64};
    cuuint32_t es[5] = {1, 1, 1, 1, 1};
    cuuint32_t box[5] = {32, 4, 8, 2, 3}, boxq[5] = {32, 4, 4, 1, 1};
    encode(&tm_x, CU_TENSOR_MAP_DATA_TYPE_BFLOAT16, 5, d_in[0], dims, strides, box, es, CU_TENSOR_MAP_INTERLEAVE_NONE,
           CU_TENSOR_MAP_SWIZZLE_64B, CU_TENSOR_MAP_L2_PROMOTION_L2_128B, CU_TENSOR_MAP_FLOAT_OOB_FILL_NONE);
    encode(&tm_xq, CU_TENSOR_MAP_DATA_TYPE_BFLOAT16, 5, d_in[0], dims, strides, boxq, es, CU_TENSOR_MAP_INTERLEAVE_NONE,
           CU_TENSOR_MAP_SWIZZLE_64B, CU_TENSOR_MAP_L2_PROMOTION_L2_128B, CU_TENSOR_MAP_FLOAT_OOB_FILL_NONE);
    cuuint64_t wd[3] = {32, 96, 9};
    cuuint64_t ws[2] = {576, 64};
    cuuint32_t wb[3] = {32, 96, 9};
    encode(&tm_w, CU_TENSOR_MAP_DATA_TYPE_BFLOAT16, 3, d_in[1], wd, ws, wb, es, CU_TENSOR_MAP_INTERLEAVE_NONE,
           CU_TENSOR_MAP_SWIZZLE_64B, CU_TENSOR_MAP_L2_PROMOTION_L2_128B, CU_TENSOR_MAP_FLOAT_OOB_FILL_NONE);
  }
  swin_kernel<<<sms, 384, SM_TOTAL>>>(
      tm_x, tm_xq, tm_w, (const __nv_bfloat16*)d_in[2], (const __nv_bfloat16*)d_in[3],
      (const __nv_bfloat16*)d_in[4], (const __nv_bfloat16*)d_in[5], (const __nv_bfloat16*)d_in[6], (const int*)d_in[7],
      (const __nv_bfloat16*)d_in[8], (__nv_bfloat16*)d_out);
}
```

```cpp
#include <cuda_runtime.h>
#include <cuda.h>
#include <cuda_bf16.h>
#include <stdint.h>

namespace {

constexpr int IMG   = 384;
constexpr int NWX   = 48;
constexpr int NWIN  = NWX * NWX;
constexpr int PIXB  = 192;
constexpr int ROWB  = IMG * PIXB;
constexpr float LOG2E = 1.4426950408889634f;

constexpr int SM_W    = 0;
constexpr int SM_WO   = SM_W + 9 * 6144;
constexpr int SM_EB   = SM_WO + 12 * 1536;
constexpr int SM_WG   = SM_EB + 32768;
constexpr int WG_X    = 0;
constexpr int WG_K    = 12288;
constexpr int WG_V    = WG_K + 14336;
constexpr int WG_SZ   = WG_V + 14336;
constexpr int SM_TAB  = SM_WG + 2 * WG_SZ + WG_V + 4096;
constexpr int SM_SEL  = SM_WG + 3 * WG_SZ;
constexpr int SM_MISC = SM_SEL + 256;
constexpr int SM_BAR  = SM_MISC + 16;
constexpr int SM_TOTAL = SM_BAR + 32;

template <int SD> __device__ __forceinline__ void wgmma_ss_n192_t1(float (&d)[96], uint32_t da, uint32_t db) {
  if constexpr (SD) {
    asm volatile("{\n.reg .pred p;\n.reg .b64 da, db;\nsetp.ne.b32 p, 1, 0;\nmov.b64 da, {%96, 0x80000020};\nmov.b64 db, {%97, 0x80000020};\n"
      "wgmma.mma_async.sync.aligned.m64n192k16.f32.bf16.bf16 {%0, %1, %2, %3, %4, %5, %6, %7, %8, %9, %10, %11, %12, %13, %14, %15, %16, %17, %18, %19, %20, %21, %22, %23, %24, %25, %26, %27, %28, %29, %30, %31, %32, %33, %34, %35, %36, %37, %38, %39, %40, %41, %42, %43, %44, %45, %46, %47, %48, %49, %50, %51, %52, %53, %54, %55, %56, %57, %58, %59, %60, %61, %62, %63, %64, %65, %66, %67, %68, %69, %70, %71, %72, %73, %74, %75, %76, %77, %78, %79, %80, %81, %82, %83, %84, %85, %86, %87, %88, %89, %90, %91, %92, %93, %94, %95}, da, db, p, 1, 1, 0, 1;\n}\n"
      : "+f"(d[0]), "+f"(d[1]), "+f"(d[2]), "+f"(d[3]), "+f"(d[4]), "+f"(d[5]), "+f"(d[6]), "+f"(d[7]), "+f"(d[8]), "+f"(d[9]), "+f"(d[10]), "+f"(d[11]), "+f"(d[12]), "+f"(d[13]), "+f"(d[14]), "+f"(d[15]), "+f"(d[16]), "+f"(d[17]), "+f"(d[18]), "+f"(d[19]), "+f"(d[20]), "+f"(d[21]), "+f"(d[22]), "+f"(d[23]), "+f"(d[24]), "+f"(d[25]), "+f"(d[26]), "+f"(d[27]), "+f"(d[28]), "+f"(d[29]), "+f"(d[30]), "+f"(d[31]), "+f"(d[32]), "+f"(d[33]), "+f"(d[34]), "+f"(d[35]), "+f"(d[36]), "+f"(d[37]), "+f"(d[38]), "+f"(d[39]), "+f"(d[40]), "+f"(d[41]), "+f"(d[42]), "+f"(d[43]), "+f"(d[44]), "+f"(d[45]), "+f"(d[46]), "+f"(d[47]), "+f"(d[48]), "+f"(d[49]), "+f"(d[50]), "+f"(d[51]), "+f"(d[52]), "+f"(d[53]), "+f"(d[54]), "+f"(d[55]), "+f"(d[56]), "+f"(d[57]), "+f"(d[58]), "+f"(d[59]), "+f"(d[60]), "+f"(d[61]), "+f"(d[62]), "+f"(d[63]), "+f"(d[64]), "+f"(d[65]), "+f"(d[66]), "+f"(d[67]), "+f"(d[68]), "+f"(d[69]), "+f"(d[70]), "+f"(d[71]), "+f"(d[72]), "+f"(d[73]), "+f"(d[74]), "+f"(d[75]), "+f"(d[76]), "+f"(d[77]), "+f"(d[78]), "+f"(d[79]), "+f"(d[80]), "+f"(d[81]), "+f"(d[82]), "+f"(d[83]), "+f"(d[84]), "+f"(d[85]), "+f"(d[86]), "+f"(d[87]), "+f"(d[88]), "+f"(d[89]), "+f"(d[90]), "+f"(d[91]), "+f"(d[92]), "+f"(d[93]), "+f"(d[94]), "+f"(d[95])
      : "r"(da), "r"(db));
  } else {
    asm volatile("{\n.reg .pred p;\n.reg .b64 da, db;\nsetp.ne.b32 p, 0, 0;\nmov.b64 da, {%96, 0x80000020};\nmov.b64 db, {%97, 0x80000020};\n"
      "wgmma.mma_async.sync.aligned.m64n192k16.f32.bf16.bf16 {%0, %1, %2, %3, %4, %5, %6, %7, %8, %9, %10, %11, %12, %13, %14, %15, %16, %17, %18, %19, %20, %21, %22, %23, %24, %25, %26, %27, %28, %29, %30, %31, %32, %33, %34, %35, %36, %37, %38, %39, %40, %41, %42, %43, %44, %45, %46, %47, %48, %49, %50, %51, %52, %53, %54, %55, %56, %57, %58, %59, %60, %61, %62, %63, %64, %65, %66, %67, %68, %69, %70, %71, %72, %73, %74, %75, %76, %77, %78, %79, %80, %81, %82, %83, %84, %85, %86, %87, %88, %89, %90, %91, %92, %93, %94, %95}, da, db, p, 1, 1, 0, 1;\n}\n"
      : "=f"(d[0]), "=f"(d[1]), "=f"(d[2]), "=f"(d[3]), "=f"(d[4]), "=f"(d[5]), "=f"(d[6]), "=f"(d[7]), "=f"(d[8]), "=f"(d[9]), "=f"(d[10]), "=f"(d[11]), "=f"(d[12]), "=f"(d[13]), "=f"(d[14]), "=f"(d[15]), "=f"(d[16]), "=f"(d[17]), "=f"(d[18]), "=f"(d[19]), "=f"(d[20]), "=f"(d[21]), "=f"(d[22]), "=f"(d[23]), "=f"(d[24]), "=f"(d[25]), "=f"(d[26]), "=f"(d[27]), "=f"(d[28]), "=f"(d[29]), "=f"(d[30]), "=f"(d[31]), "=f"(d[32]), "=f"(d[33]), "=f"(d[34]), "=f"(d[35]), "=f"(d[36]), "=f"(d[37]), "=f"(d[38]), "=f"(d[39]), "=f"(d[40]), "=f"(d[41]), "=f"(d[42]), "=f"(d[43]), "=f"(d[44]), "=f"(d[45]), "=f"(d[46]), "=f"(d[47]), "=f"(d[48]), "=f"(d[49]), "=f"(d[50]), "=f"(d[51]), "=f"(d[52]), "=f"(d[53]), "=f"(d[54]), "=f"(d[55]), "=f"(d[56]), "=f"(d[57]), "=f"(d[58]), "=f"(d[59]), "=f"(d[60]), "=f"(d[61]), "=f"(d[62]), "=f"(d[63]), "=f"(d[64]), "=f"(d[65]), "=f"(d[66]), "=f"(d[67]), "=f"(d[68]), "=f"(d[69]), "=f"(d[70]), "=f"(d[71]), "=f"(d[72]), "=f"(d[73]), "=f"(d[74]), "=f"(d[75]), "=f"(d[76]), "=f"(d[77]), "=f"(d[78]), "=f"(d[79]), "=f"(d[80]), "=f"(d[81]), "=f"(d[82]), "=f"(d[83]), "=f"(d[84]), "=f"(d[85]), "=f"(d[86]), "=f"(d[87]), "=f"(d[88]), "=f"(d[89]), "=f"(d[90]), "=f"(d[91]), "=f"(d[92]), "=f"(d[93]), "=f"(d[94]), "=f"(d[95])
      : "r"(da), "r"(db));
  }
}
template <int SD> __device__ __forceinline__ void wgmma_ss_n96_t1(float (&d)[48], uint32_t da, uint32_t db) {
  if constexpr (SD) {
    asm volatile("{\n.reg .pred p;\n.reg .b64 da, db;\nsetp.ne.b32 p, 1, 0;\nmov.b64 da, {%48, 0x80000020};\nmov.b64 db, {%49, 0x80000020};\n"
      "wgmma.mma_async.sync.aligned.m64n96k16.f32.bf16.bf16 {%0, %1, %2, %3, %4, %5, %6, %7, %8, %9, %10, %11, %12, %13, %14, %15, %16, %17, %18, %19, %20, %21, %22, %23, %24, %25, %26, %27, %28, %29, %30, %31, %32, %33, %34, %35, %36, %37, %38, %39, %40, %41, %42, %43, %44, %45, %46, %47}, da, db, p, 1, 1, 0, 1;\n}\n"
      : "+f"(d[0]), "+f"(d[1]), "+f"(d[2]), "+f"(d[3]), "+f"(d[4]), "+f"(d[5]), "+f"(d[6]), "+f"(d[7]), "+f"(d[8]), "+f"(d[9]), "+f"(d[10]), "+f"(d[11]), "+f"(d[12]), "+f"(d[13]), "+f"(d[14]), "+f"(d[15]), "+f"(d[16]), "+f"(d[17]), "+f"(d[18]), "+f"(d[19]), "+f"(d[20]), "+f"(d[21]), "+f"(d[22]), "+f"(d[23]), "+f"(d[24]), "+f"(d[25]), "+f"(d[26]), "+f"(d[27]), "+f"(d[28]), "+f"(d[29]), "+f"(d[30]), "+f"(d[31]), "+f"(d[32]), "+f"(d[33]), "+f"(d[34]), "+f"(d[35]), "+f"(d[36]), "+f"(d[37]), "+f"(d[38]), "+f"(d[39]), "+f"(d[40]), "+f"(d[41]), "+f"(d[42]), "+f"(d[43]), "+f"(d[44]), "+f"(d[45]), "+f"(d[46]), "+f"(d[47])
      : "r"(da), "r"(db));
  } else {
    asm volatile("{\n.reg .pred p;\n.reg .b64 da, db;\nsetp.ne.b32 p, 0, 0;\nmov.b64 da, {%48, 0x80000020};\nmov.b64 db, {%49, 0x80000020};\n"
      "wgmma.mma_async.sync.aligned.m64n96k16.f32.bf16.bf16 {%0, %1, %2, %3, %4, %5, %6, %7, %8, %9, %10, %11, %12, %13, %14, %15, %16, %17, %18, %19, %20, %21, %22, %23, %24, %25, %26, %27, %28, %29, %30, %31, %32, %33, %34, %35, %36, %37, %38, %39, %40, %41, %42, %43, %44, %45, %46, %47}, da, db, p, 1, 1, 0, 1;\n}\n"
      : "=f"(d[0]), "=f"(d[1]), "=f"(d[2]), "=f"(d[3]), "=f"(d[4]), "=f"(d[5]), "=f"(d[6]), "=f"(d[7]), "=f"(d[8]), "=f"(d[9]), "=f"(d[10]), "=f"(d[11]), "=f"(d[12]), "=f"(d[13]), "=f"(d[14]), "=f"(d[15]), "=f"(d[16]), "=f"(d[17]), "=f"(d[18]), "=f"(d[19]), "=f"(d[20]), "=f"(d[21]), "=f"(d[22]), "=f"(d[23]), "=f"(d[24]), "=f"(d[25]), "=f"(d[26]), "=f"(d[27]), "=f"(d[28]), "=f"(d[29]), "=f"(d[30]), "=f"(d[31]), "=f"(d[32]), "=f"(d[33]), "=f"(d[34]), "=f"(d[35]), "=f"(d[36]), "=f"(d[37]), "=f"(d[38]), "=f"(d[39]), "=f"(d[40]), "=f"(d[41]), "=f"(d[42]), "=f"(d[43]), "=f"(d[44]), "=f"(d[45]), "=f"(d[46]), "=f"(d[47])
      : "r"(da), "r"(db));
  }
}
template <int SD> __device__ __forceinline__ void wgmma_rs_n96_t1(float (&d)[48], uint32_t a0, uint32_t a1, uint32_t a2, uint32_t a3, uint32_t db) {
  if constexpr (SD) {
    asm volatile("{\n.reg .pred p;\n.reg .b64 da, db;\nsetp.ne.b32 p, 1, 0;\nmov.b64 db, {%52, 96};\n"
      "wgmma.mma_async.sync.aligned.m64n96k16.f32.bf16.bf16 {%0, %1, %2, %3, %4, %5, %6, %7, %8, %9, %10, %11, %12, %13, %14, %15, %16, %17, %18, %19, %20, %21, %22, %23, %24, %25, %26, %27, %28, %29, %30, %31, %32, %33, %34, %35, %36, %37, %38, %39, %40, %41, %42, %43, %44, %45, %46, %47}, {%48, %49, %50, %51}, db, p, 1, 1, 1;\n}\n"
      : "+f"(d[0]), "+f"(d[1]), "+f"(d[2]), "+f"(d[3]), "+f"(d[4]), "+f"(d[5]), "+f"(d[6]), "+f"(d[7]), "+f"(d[8]), "+f"(d[9]), "+f"(d[10]), "+f"(d[11]), "+f"(d[12]), "+f"(d[13]), "+f"(d[14]), "+f"(d[15]), "+f"(d[16]), "+f"(d[17]), "+f"(d[18]), "+f"(d[19]), "+f"(d[20]), "+f"(d[21]), "+f"(d[22]), "+f"(d[23]), "+f"(d[24]), "+f"(d[25]), "+f"(d[26]), "+f"(d[27]), "+f"(d[28]), "+f"(d[29]), "+f"(d[30]), "+f"(d[31]), "+f"(d[32]), "+f"(d[33]), "+f"(d[34]), "+f"(d[35]), "+f"(d[36]), "+f"(d[37]), "+f"(d[38]), "+f"(d[39]), "+f"(d[40]), "+f"(d[41]), "+f"(d[42]), "+f"(d[43]), "+f"(d[44]), "+f"(d[45]), "+f"(d[46]), "+f"(d[47])
      : "r"(a0), "r"(a1), "r"(a2), "r"(a3), "r"(db));
  } else {
    asm volatile("{\n.reg .pred p;\n.reg .b64 da, db;\nsetp.ne.b32 p, 0, 0;\nmov.b64 db, {%52, 96};\n"
      "wgmma.mma_async.sync.aligned.m64n96k16.f32.bf16.bf16 {%0, %1, %2, %3, %4, %5, %6, %7, %8, %9, %10, %11, %12, %13, %14, %15, %16, %17, %18, %19, %20, %21, %22, %23, %24, %25, %26, %27, %28, %29, %30, %31, %32, %33, %34, %35, %36, %37, %38, %39, %40, %41, %42, %43, %44, %45, %46, %47}, {%48, %49, %50, %51}, db, p, 1, 1, 1;\n}\n"
      : "=f"(d[0]), "=f"(d[1]), "=f"(d[2]), "=f"(d[3]), "=f"(d[4]), "=f"(d[5]), "=f"(d[6]), "=f"(d[7]), "=f"(d[8]), "=f"(d[9]), "=f"(d[10]), "=f"(d[11]), "=f"(d[12]), "=f"(d[13]), "=f"(d[14]), "=f"(d[15]), "=f"(d[16]), "=f"(d[17]), "=f"(d[18]), "=f"(d[19]), "=f"(d[20]), "=f"(d[21]), "=f"(d[22]), "=f"(d[23]), "=f"(d[24]), "=f"(d[25]), "=f"(d[26]), "=f"(d[27]), "=f"(d[28]), "=f"(d[29]), "=f"(d[30]), "=f"(d[31]), "=f"(d[32]), "=f"(d[33]), "=f"(d[34]), "=f"(d[35]), "=f"(d[36]), "=f"(d[37]), "=f"(d[38]), "=f"(d[39]), "=f"(d[40]), "=f"(d[41]), "=f"(d[42]), "=f"(d[43]), "=f"(d[44]), "=f"(d[45]), "=f"(d[46]), "=f"(d[47])
      : "r"(a0), "r"(a1), "r"(a2), "r"(a3), "r"(db));
  }
}
template <int SD> __device__ __forceinline__ void wgmma_rs_n64_t0(float (&d)[32], uint32_t a0, uint32_t a1, uint32_t a2, uint32_t a3, uint32_t db) {
  if constexpr (SD) {
    asm volatile("{\n.reg .pred p;\n.reg .b64 da, db;\nsetp.ne.b32 p, 1, 0;\nmov.b64 db, {%36, 8};\n"
      "wgmma.mma_async.sync.aligned.m64n64k16.f32.bf16.bf16 {%0, %1, %2, %3, %4, %5, %6, %7, %8, %9, %10, %11, %12, %13, %14, %15, %16, %17, %18, %19, %20, %21, %22, %23, %24, %25, %26, %27, %28, %29, %30, %31}, {%32, %33, %34, %35}, db, p, 1, 1, 0;\n}\n"
      : "+f"(d[0]), "+f"(d[1]), "+f"(d[2]), "+f"(d[3]), "+f"(d[4]), "+f"(d[5]), "+f"(d[6]), "+f"(d[7]), "+f"(d[8]), "+f"(d[9]), "+f"(d[10]), "+f"(d[11]), "+f"(d[12]), "+f"(d[13]), "+f"(d[14]), "+f"(d[15]), "+f"(d[16]), "+f"(d[17]), "+f"(d[18]), "+f"(d[19]), "+f"(d[20]), "+f"(d[21]), "+f"(d[22]), "+f"(d[23]), "+f"(d[24]), "+f"(d[25]), "+f"(d[26]), "+f"(d[27]), "+f"(d[28]), "+f"(d[29]), "+f"(d[30]), "+f"(d[31])
      : "r"(a0), "r"(a1), "r"(a2), "r"(a3), "r"(db));
  } else {
    asm volatile("{\n.reg .pred p;\n.reg .b64 da, db;\nsetp.ne.b32 p, 0, 0;\nmov.b64 db, {%36, 8};\n"
      "wgmma.mma_async.sync.aligned.m64n64k16.f32.bf16.bf16 {%0, %1, %2, %3, %4, %5, %6, %7, %8, %9, %10, %11, %12, %13, %14, %15, %16, %17, %18, %19, %20, %21, %22, %23, %24, %25, %26, %27, %28, %29, %30, %31}, {%32, %33, %34, %35}, db, p, 1, 1, 0;\n}\n"
      : "=f"(d[0]), "=f"(d[1]), "=f"(d[2]), "=f"(d[3]), "=f"(d[4]), "=f"(d[5]), "=f"(d[6]), "=f"(d[7]), "=f"(d[8]), "=f"(d[9]), "=f"(d[10]), "=f"(d[11]), "=f"(d[12]), "=f"(d[13]), "=f"(d[14]), "=f"(d[15]), "=f"(d[16]), "=f"(d[17]), "=f"(d[18]), "=f"(d[19]), "=f"(d[20]), "=f"(d[21]), "=f"(d[22]), "=f"(d[23]), "=f"(d[24]), "=f"(d[25]), "=f"(d[26]), "=f"(d[27]), "=f"(d[28]), "=f"(d[29]), "=f"(d[30]), "=f"(d[31])
      : "r"(a0), "r"(a1), "r"(a2), "r"(a3), "r"(db));
  }
}
template <int SD> __device__ __forceinline__ void wgmma_rs_n32_t1(float (&d)[16], uint32_t a0, uint32_t a1, uint32_t a2, uint32_t a3, uint32_t db) {
  if constexpr (SD) {
    asm volatile("{\n.reg .pred p;\n.reg .b64 da, db;\nsetp.ne.b32 p, 1, 0;\nmov.b64 db, {%20, 64};\n"
      "wgmma.mma_async.sync.aligned.m64n32k16.f32.bf16.bf16 {%0, %1, %2, %3, %4, %5, %6, %7, %8, %9, %10, %11, %12, %13, %14, %15}, {%16, %17, %18, %19}, db, p, 1, 1, 1;\n}\n"
      : "+f"(d[0]), "+f"(d[1]), "+f"(d[2]), "+f"(d[3]), "+f"(d[4]), "+f"(d[5]), "+f"(d[6]), "+f"(d[7]), "+f"(d[8]), "+f"(d[9]), "+f"(d[10]), "+f"(d[11]), "+f"(d[12]), "+f"(d[13]), "+f"(d[14]), "+f"(d[15])
      : "r"(a0), "r"(a1), "r"(a2), "r"(a3), "r"(db));
  } else {
    asm volatile("{\n.reg .pred p;\n.reg .b64 da, db;\nsetp.ne.b32 p, 0, 0;\nmov.b64 db, {%20, 64};\n"
      "wgmma.mma_async.sync.aligned.m64n32k16.f32.bf16.bf16 {%0, %1, %2, %3, %4, %5, %6, %7, %8, %9, %10, %11, %12, %13, %14, %15}, {%16, %17, %18, %19}, db, p, 1, 1, 1;\n}\n"
      : "=f"(d[0]), "=f"(d[1]), "=f"(d[2]), "=f"(d[3]), "=f"(d[4]), "=f"(d[5]), "=f"(d[6]), "=f"(d[7]), "=f"(d[8]), "=f"(d[9]), "=f"(d[10]), "=f"(d[11]), "=f"(d[12]), "=f"(d[13]), "=f"(d[14]), "=f"(d[15])
      : "r"(a0), "r"(a1), "r"(a2), "r"(a3), "r"(db));
  }
}
template <int SD> __device__ __forceinline__ void wgmma_rs_n8_t0(float (&d)[4], uint32_t a0, uint32_t a1, uint32_t a2, uint32_t a3, uint32_t db) {
  if constexpr (SD) {
    asm volatile("{\n.reg .pred p;\n.reg .b64 da, db;\nsetp.ne.b32 p, 1, 0;\nmov.b64 db, {%8, 16};\n"
      "wgmma.mma_async.sync.aligned.m64n8k16.f32.bf16.bf16 {%0, %1, %2, %3}, {%4, %5, %6, %7}, db, p, 1, 1, 0;\n}\n"
      : "+f"(d[0]), "+f"(d[1]), "+f"(d[2]), "+f"(d[3])
      : "r"(a0), "r"(a1), "r"(a2), "r"(a3), "r"(db));
  } else {
    asm volatile("{\n.reg .pred p;\n.reg .b64 da, db;\nsetp.ne.b32 p, 0, 0;\nmov.b64 db, {%8, 16};\n"
      "wgmma.mma_async.sync.aligned.m64n8k16.f32.bf16.bf16 {%0, %1, %2, %3}, {%4, %5, %6, %7}, db, p, 1, 1, 0;\n}\n"
      : "=f"(d[0]), "=f"(d[1]), "=f"(d[2]), "=f"(d[3])
      : "r"(a0), "r"(a1), "r"(a2), "r"(a3), "r"(db));
  }
}

__device__ __forceinline__ void wg_fence()  { asm volatile("wgmma.fence.sync.aligned;" ::: "memory"); }
__device__ __forceinline__ void wg_commit() { asm volatile("wgmma.commit_group.sync.aligned;" ::: "memory"); }
template <int N> __device__ __forceinline__ void wg_wait() { asm volatile("wgmma.wait_group.sync.aligned %0;" :: "n"(N) : "memory"); }
template <int N> __device__ __forceinline__ void fence_regs(float (&d)[N]) {
#pragma unroll
  for (int i = 0; i < N; i++) asm volatile("" : "+f"(d[i]) :: "memory");
}
__device__ __forceinline__ constexpr uint32_t mk_desc(uint32_t addr, uint32_t lbo) { return (addr >> 4) | ((lbo >> 4) << 16); }
__device__ __forceinline__ uint32_t pack_bf16(float lo, float hi) {
  uint32_t r; asm("cvt.rn.bf16x2.f32 %0, %1, %2;" : "=r"(r) : "f"(hi), "f"(lo)); return r;
}
__device__ __forceinline__ uint32_t hmul2(uint32_t a, uint32_t b) {
  uint32_t r; asm("mul.rn.bf16x2 %0, %1, %2;" : "=r"(r) : "r"(a), "r"(b)); return r;
}
__device__ __forceinline__ uint32_t hfma2(uint32_t a, uint32_t b, uint32_t c) {
  uint32_t r; asm("fma.rn.bf16x2 %0, %1, %2, %3;" : "=r"(r) : "r"(a), "r"(b), "r"(c)); return r;
}
__device__ __forceinline__ float ex2(float x) { float r; asm("ex2.approx.ftz.f32 %0, %1;" : "=f"(r) : "f"(x)); return r; }
__device__ __forceinline__ float lg2(float x) { float r; asm("lg2.approx.ftz.f32 %0, %1;" : "=f"(r) : "f"(x)); return r; }
__device__ __forceinline__ float rsq(float x) { float r; asm("rsqrt.approx.ftz.f32 %0, %1;" : "=f"(r) : "f"(x)); return r; }
__device__ __forceinline__ float rcp(float x) { float r; asm("rcp.approx.ftz.f32 %0, %1;" : "=f"(r) : "f"(x)); return r; }
__device__ __forceinline__ void stsm4(uint32_t addr, uint32_t r0, uint32_t r1, uint32_t r2, uint32_t r3) {
  asm volatile("stmatrix.sync.aligned.m8n8.x4.shared.b16 [%0], {%1,%2,%3,%4};" :: "r"(addr), "r"(r0), "r"(r1), "r"(r2), "r"(r3) : "memory");
}
__device__ __forceinline__ void fence_async() { asm volatile("fence.proxy.async.shared::cta;" ::: "memory"); }
__device__ __forceinline__ void bar_wg(int id) { asm volatile("bar.sync %0, 128;" :: "r"(id) : "memory"); }
__device__ __forceinline__ void bar_sync_n(int id, int n) { asm volatile("bar.sync %0, %1;" :: "r"(id), "r"(n) : "memory"); }
__device__ __forceinline__ void bar_arrive_n(int id, int n) { asm volatile("bar.arrive %0, %1;" :: "r"(id), "r"(n) : "memory"); }
__device__ __forceinline__ bool bar_wg_or(int id, bool v) {
  uint32_t r;
  asm volatile("{\n.reg .pred p, q;\nsetp.ne.u32 q, %2, 0;\nbar.red.or.pred p, %1, 128, q;\nselp.u32 %0, 1, 0, p;\n}\n"
               : "=r"(r) : "r"(id), "r"((uint32_t)v) : "memory");
  return r != 0;
}
__device__ __forceinline__ void mbar_init(uint32_t bar, uint32_t cnt) { asm volatile("mbarrier.init.shared::cta.b64 [%0], %1;" :: "r"(bar), "r"(cnt) : "memory"); }
__device__ __forceinline__ void mbar_expect(uint32_t bar, uint32_t bytes) {
  asm volatile("mbarrier.arrive.expect_tx.shared::cta.b64 _, [%0], %1;" :: "r"(bar), "r"(bytes) : "memory");
}
__device__ __forceinline__ void mbar_wait(uint32_t bar, uint32_t parity) {
  uint32_t ok, spins = 0;
  do {
    asm volatile("{\n.reg .pred p;\nmbarrier.try_wait.parity.shared::cta.b64 p, [%1], %2;\nselp.u32 %0, 1, 0, p;\n}\n"
                 : "=r"(ok) : "r"(bar), "r"(parity) : "memory");
    if (!ok && ++spins > (1u << 22)) __trap();
  } while (!ok);
}
__device__ __forceinline__ void tma5(uint32_t dst, const CUtensorMap* m, uint32_t bar, int c0, int c1, int c2, int c3, int c4) {
  asm volatile("cp.async.bulk.tensor.5d.shared::cluster.global.mbarrier::complete_tx::bytes [%0], [%1, {%3, %4, %5, %6, %7}], [%2];"
               :: "r"(dst), "l"(m), "r"(bar), "r"(c0), "r"(c1), "r"(c2), "r"(c3), "r"(c4) : "memory");
}
__device__ __forceinline__ void tma3(uint32_t dst, const CUtensorMap* m, uint32_t bar, int c0, int c1, int c2) {
  asm volatile("cp.async.bulk.tensor.3d.shared::cluster.global.mbarrier::complete_tx::bytes [%0], [%1, {%3, %4, %5}], [%2];"
               :: "r"(dst), "l"(m), "r"(bar), "r"(c0), "r"(c1), "r"(c2) : "memory");
}
__device__ __forceinline__ uint4 lds128(uint32_t addr) {
  uint4 v; asm volatile("ld.shared.v4.u32 {%0,%1,%2,%3}, [%4];" : "=r"(v.x), "=r"(v.y), "=r"(v.z), "=r"(v.w) : "r"(addr)); return v;
}
__device__ __forceinline__ uint4 ldg128_stream(const void* p) {
  uint4 v; asm volatile("ld.global.nc.L1::no_allocate.v4.u32 {%0,%1,%2,%3}, [%4];" : "=r"(v.x), "=r"(v.y), "=r"(v.z), "=r"(v.w) : "l"(p)); return v;
}
__device__ __forceinline__ void stg128(void* p, uint32_t a, uint32_t b, uint32_t c, uint32_t d) {
  asm volatile("st.global.v4.u32 [%0], {%1,%2,%3,%4};" :: "l"(p), "r"(a), "r"(b), "r"(c), "r"(d) : "memory");
}
__device__ __forceinline__ void prefetch_l2(const void* p, uint32_t bytes) {
  asm volatile("cp.async.bulk.prefetch.L2.global [%0], %1;" :: "l"(p), "r"(bytes) : "memory");
}
__device__ __forceinline__ float bf_lo(uint32_t u) { return __uint_as_float(u << 16); }
__device__ __forceinline__ float bf_hi(uint32_t u) { return __uint_as_float(u & 0xFFFF0000u); }
__device__ __forceinline__ float rbf(float x) { return __bfloat162float(__float2bfloat16_rn(x)); }
__device__ __forceinline__ int orig_tok(int r) { return ((r & 31) >> 2) * 8 + (r >> 5) * 4 + (r & 3); }

__device__ __forceinline__ int slot_window(int s, int G) {
  int wy, wx;
  if (G == 132) {
    constexpr int A0 = 396 + 60, A1 = A0 + 72, B0 = 3 * 396 + 132 + 60, B1 = B0 + 23;
    int k = -1, i = s;
    if (s >= B1) i = s - 95; else if (s >= B0) k = s - B0 + 72; else if (s >= A1) i = s - 72; else if (s >= A0) k = s - A0;
    if (k < 0) { wy = i / 47; wx = i - wy * 47; }
    else if (k < 48) { wy = 47; wx = k; }
    else { wy = k - 48; wx = 47; }
  } else {
    wy = s / NWX; wx = s - wy * NWX;
  }
  return wy << 8 | wx;
}

__device__ __forceinline__ void softmax_fast(const float (&s)[32], uint32_t (&p)[16], uint32_t eb_addr) {
#pragma unroll
  for (int j = 0; j < 4; j++) {
    const uint4 e = lds128(eb_addr + j * 2048);
    p[4 * j + 0] = hmul2(pack_bf16(ex2(s[8 * j + 0]), ex2(s[8 * j + 1])), e.x);
    p[4 * j + 1] = hmul2(pack_bf16(ex2(s[8 * j + 2]), ex2(s[8 * j + 3])), e.y);
    p[4 * j + 2] = hmul2(pack_bf16(ex2(s[8 * j + 4]), ex2(s[8 * j + 5])), e.z);
    p[4 * j + 3] = hmul2(pack_bf16(ex2(s[8 * j + 6]), ex2(s[8 * j + 7])), e.w);
  }
}
__device__ __forceinline__ void softmax_true_max(float (&s)[32], uint32_t (&p)[16], uint32_t eb_addr, const uint32_t (&mk)[16]) {
#pragma unroll
  for (int j = 0; j < 4; j++) {
    const uint4 e = lds128(eb_addr + j * 2048);
    s[8 * j + 0] += lg2(bf_lo(e.x)); s[8 * j + 1] += lg2(bf_hi(e.x));
    s[8 * j + 2] += lg2(bf_lo(e.y)); s[8 * j + 3] += lg2(bf_hi(e.y));
    s[8 * j + 4] += lg2(bf_lo(e.z)); s[8 * j + 5] += lg2(bf_hi(e.z));
    s[8 * j + 6] += lg2(bf_lo(e.w)); s[8 * j + 7] += lg2(bf_hi(e.w));
  }
#pragma unroll
  for (int i = 0; i < 16; i++) {
    s[2 * i] = fmaf(bf_lo(mk[i]), LOG2E, s[2 * i]); s[2 * i + 1] = fmaf(bf_hi(mk[i]), LOG2E, s[2 * i + 1]);
  }
  float m0 = s[0], m1 = s[2];
#pragma unroll
  for (int g = 0; g < 8; g++) {
    m0 = fmaxf(m0, fmaxf(s[4 * g + 0], s[4 * g + 1]));
    m1 = fmaxf(m1, fmaxf(s[4 * g + 2], s[4 * g + 3]));
  }
  m0 = fmaxf(m0, __shfl_xor_sync(0xffffffffu, m0, 1)); m0 = fmaxf(m0, __shfl_xor_sync(0xffffffffu, m0, 2));
  m1 = fmaxf(m1, __shfl_xor_sync(0xffffffffu, m1, 1)); m1 = fmaxf(m1, __shfl_xor_sync(0xffffffffu, m1, 2));
#pragma unroll
  for (int g = 0; g < 8; g++) {
    p[2 * g + 0] = pack_bf16(ex2(s[4 * g + 0] - m0), ex2(s[4 * g + 1] - m0));
    p[2 * g + 1] = pack_bf16(ex2(s[4 * g + 2] - m1), ex2(s[4 * g + 3] - m1));
  }
}
template <int H> __device__ __forceinline__ void issue_s(float (&s)[32], const uint32_t (&q)[24], uint32_t dK) {
  constexpr int Q0 = (H == 0 ? 0 : H == 1 ? 4 : H == 2 ? 12 : 16), P0 = (H == 0 ? 0 : H == 1 ? 3 : H == 2 ? 7 : 10);
  wgmma_rs_n64_t0<0>(s, q[Q0], q[Q0 + 1], q[Q0 + 2], q[Q0 + 3], dK + P0 * 64);
  wgmma_rs_n64_t0<1>(s, q[Q0 + 4], q[Q0 + 5], q[Q0 + 6], q[Q0 + 7], dK + P0 * 64 + 128);
}
template <int H> __device__ __forceinline__ void issue_pv(float (&o)[16], const uint32_t (&p)[16], uint32_t dV) {
  constexpr int P0 = (H == 0 ? 0 : H == 1 ? 3 : H == 2 ? 7 : 10);
  wgmma_rs_n32_t1<0>(o, p[0], p[1], p[2], p[3], dV + P0 * 64);
  wgmma_rs_n32_t1<1>(o, p[4], p[5], p[6], p[7], dV + P0 * 64 + 16);
  wgmma_rs_n32_t1<1>(o, p[8], p[9], p[10], p[11], dV + P0 * 64 + 32);
  wgmma_rs_n32_t1<1>(o, p[12], p[13], p[14], p[15], dV + P0 * 64 + 48);
}
__device__ __forceinline__ void sumsq(const uint32_t (&f)[24], uint32_t (&sq)[8], uint32_t init) {
#pragma unroll
  for (int h = 0; h < 4; h++)
#pragma unroll
    for (int r = 0; r < 2; r++) {
      uint32_t u = f[6 * h + r], v = f[6 * h + 2 + r], w = f[6 * h + 4 + r];
      sq[2 * h + r] = hfma2(w, w, hfma2(v, v, hfma2(u, u, init)));
    }
}
__device__ __forceinline__ void scale_heads(uint32_t (&f)[24], const float (&r)[8]) {
#pragma unroll
  for (int h = 0; h < 4; h++)
#pragma unroll
    for (int q = 0; q < 2; q++) {
      uint32_t p = pack_bf16(r[2 * h + q], r[2 * h + q]);
#pragma unroll
      for (int c = 0; c < 3; c++) f[6 * h + 2 * c + q] = hmul2(f[6 * h + 2 * c + q], p);
    }
}
template <int ODD> __device__ __forceinline__ void norm_o(const float (&o)[16], uint32_t* of) {
  constexpr int SO = ODD ? 0 : 12, VO = ODD ? 4 : 0;
  float r0 = rcp(o[SO]), r1 = rcp(o[SO + 2]);
  uint32_t p0 = pack_bf16(r0, r0), p1 = pack_bf16(r1, r1);
#pragma unroll
  for (int g = 0; g < 3; g++) {
    of[2 * g + 0] = hmul2(pack_bf16(o[VO + 4 * g + 0], o[VO + 4 * g + 1]), p0);
    of[2 * g + 1] = hmul2(pack_bf16(o[VO + 4 * g + 2], o[VO + 4 * g + 3]), p1);
  }
}
#define TL(i)
#define TG(i)

__global__ void __launch_bounds__(384, 1)
swin_kernel(const __grid_constant__ CUtensorMap tm_x, const __grid_constant__ CUtensorMap tm_xq, const __grid_constant__ CUtensorMap tm_w,
            const __nv_bfloat16* __restrict__ wo,
            const __nv_bfloat16* __restrict__ logit_scale, const __nv_bfloat16* __restrict__ w1, const __nv_bfloat16* __restrict__ w2,
            const __nv_bfloat16* __restrict__ coords, const int* __restrict__ rel_idx, const __nv_bfloat16* __restrict__ mask,
            __nv_bfloat16* __restrict__ out) {
  extern __shared__ __align__(1024) uint8_t smem[];
  constexpr uint32_t sb = 1024;
  if ((uint32_t)__cvta_generic_to_shared(smem) != sb) __trap();
  const int tid = threadIdx.x, lane = tid & 31;
  const int warp = __shfl_sync(0xffffffffu, (tid >> 5) & 3, 0), wg = __shfl_sync(0xffffffffu, tid >> 7, 0);
  const int g = lane >> 2, t = lane & 3;
  const uint32_t t16 = (tid & 127) * 16;
  const int stride = 3 * gridDim.x;
  int slot = wg * gridDim.x + blockIdx.x;
  const uint32_t wgb = sb + SM_WG + wg * WG_SZ;
  const uint32_t bar_x = sb + SM_BAR + 8 + 8 * wg;
  const char* mb = reinterpret_cast<const char*>(mask);
  TL(0); TG(14);

  auto load_x = [&](int w) {
    const int wy = w >> 8, wx = w & 255;
    mbar_expect(bar_x, 12288);
    if (wy != NWX - 1 && wx != NWX - 1) {
      tma5(wgb + WG_X, &tm_x, bar_x, 0, 0, wy * 8 + 4, wx * 2 + 1, 0);
    } else {
      for (int q = 0; q < 4; q++) {
        int y = wy * 8 + 4 + (q & 1) * 4; if (y >= IMG) y -= IMG;
        int xq = wx * 2 + 1 + (q >> 1);   if (xq >= IMG / 4) xq -= IMG / 4;
        for (int c = 0; c < 3; c++) tma5(wgb + WG_X + c * 4096 + q * 1024, &tm_xq, bar_x, 0, 0, y, xq, c);
      }
    }
  };
  auto mask_ptr = [&](int w) { return mb + (uint32_t)((w >> 8) * NWX + (w & 255)) * 8192u; };
  uint4 mw[4];
  auto load_mask = [&](int w) {
    const char* src = mask_ptr(w) + t16;
#pragma unroll
    for (int i = 0; i < 4; i++) mw[i] = ldg128_stream(src + i * 2048);
  };

  int win = slot_window(slot, gridDim.x);
  if ((tid & 127) == 0) {
    mbar_init(bar_x, 1);
    if (wg == 0) mbar_init(sb + SM_BAR, 1);
    fence_async();
    if (wg == 0) { mbar_expect(sb + SM_BAR, 9 * 6144); tma3(sb + SM_W, &tm_w, sb + SM_BAR, 0, 0, 0); load_x(win); }
  }
  const uint2 lsw = *reinterpret_cast<const uint2*>(logit_scale);
  float tau[4]; uint32_t slow_heads = 0;
  auto head_scales = [&]() {
    const float ls[4] = {bf_lo(lsw.x), bf_hi(lsw.x), bf_lo(lsw.y), bf_hi(lsw.y)};
#pragma unroll
    for (int h = 0; h < 4; h++) {
      const float c = ls[h] < -100.f ? -100.f : (ls[h] > 4.59375f ? 4.59375f : ls[h]);
      tau[h] = rbf(expf(c)) * LOG2E;
      if (!(tau[h] * 2.04f <= 80.f)) slow_heads |= 1u << h;
    }
    slow_heads = __shfl_sync(0xffffffffu, slow_heads, 0);
  };
  auto const_tiles = [&]() {
    const int i = tid & 127;
    uint8_t* vt = smem + SM_WG + wg * WG_SZ + WG_V;
    *reinterpret_cast<uint4*>(vt + (i < 64 ? 3 : 10) * 1024 + (i & 63) * 16) = make_uint4(0x3F803F80u, 0x3F803F80u, 0x3F803F80u, 0x3F803F80u);
    *reinterpret_cast<uint4*>(vt - 14336 + (i < 64 ? 3 : 10) * 1024 + (i & 63) * 16) = make_uint4(0u, 0u, 0u, 0u);
  };
  if (wg == 0) {
    const_tiles();
    if (tid < 16) {
      const uint32_t v = (((tid >> 3) ^ tid) & 1) ? 0u : 0x3F803F80u;
      *reinterpret_cast<uint4*>(smem + SM_SEL + tid * 16) = make_uint4(v, v, v, v);
    }
    head_scales();
    if (tid == 0) *reinterpret_cast<float4*>(smem + SM_MISC) = make_float4(tau[0], tau[1], tau[2], tau[3]);
    fence_async();
    load_mask(win);
    TL(3);
    bar_arrive_n(11, 384);
    bar_wg(1);
  } else {
    float* tab = reinterpret_cast<float*>(smem + SM_TAB);
    const int i = tid - 128;
    uint32_t cw = 0, a[16], b[32];
    if (i < 225) cw = *reinterpret_cast<const uint32_t*>(coords + 2 * i);
#pragma unroll
    for (int j = 0; j < 4; j++) *reinterpret_cast<uint4*>(a + 4 * j) = *reinterpret_cast<const uint4*>(w1 + 8 * j);
#pragma unroll
    for (int j = 0; j < 8; j++) *reinterpret_cast<uint4*>(b + 4 * j) = *reinterpret_cast<const uint4*>(w2 + 8 * j);
    int2 rid[16];
    {
      const int* rrow = rel_idx + orig_tok(16 * warp + g) * 64 + (t >> 1) * 8 + (t & 1) * 2;
#pragma unroll
      for (int G = 0; G < 8; G++) {
        rid[2 * G] = *reinterpret_cast<const int2*>(rrow + (G & 3) * 16 + (G >> 2) * 4);
        rid[2 * G + 1] = *reinterpret_cast<const int2*>(rrow + 16 * 64 + (G & 3) * 16 + (G >> 2) * 4);
      }
    }
    uint4 v[6];
    if (i < 192) {
#pragma unroll
      for (int c = 0; c < 6; c++) v[c] = *reinterpret_cast<const uint4*>(wo + (i >> 1) * 96 + ((c >> 1) * 4 + (i & 1) * 2 + (c & 1)) * 8);
    }
    if ((tid & 127) == 0) load_x(win);
    TL(3);
    const_tiles();
    head_scales();
    if (i < 225) {
      const float c0 = bf_lo(cw), c1 = bf_hi(cw);
      float z[4] = {0.f, 0.f, 0.f, 0.f};
#pragma unroll
      for (int j = 0; j < 16; j++) {
        const float u = (j & 1) ? bf_hi(a[j >> 1]) : bf_lo(a[j >> 1]), w = (j & 1) ? bf_hi(a[8 + (j >> 1)]) : bf_lo(a[8 + (j >> 1)]);
        float h = rbf(fmaf(c1, w, c0 * u));
        h = h > 0.f ? h : h * 0.f;
        z[0] = fmaf(h, bf_lo(b[2 * j]), z[0]); z[1] = fmaf(h, bf_hi(b[2 * j]), z[1]);
        z[2] = fmaf(h, bf_lo(b[2 * j + 1]), z[2]); z[3] = fmaf(h, bf_hi(b[2 * j + 1]), z[3]);
      }
      float e[4];
#pragma unroll
      for (int q = 0; q < 4; q++) e[q] = ex2((16.f * LOG2E) * rbf(rcp(1.f + ex2(-LOG2E * rbf(z[q])))));
      *reinterpret_cast<float4*>(tab + 4 * i) = make_float4(e[0], e[1], e[2], e[3]);
    }
    TL(4);
    load_mask(win);
    bar_sync_n(12, 256);
    TL(5);
    {
      const int hp = wg - 1;
      float2 e[32];
#pragma unroll
      for (int j = 0; j < 16; j++) {
        e[2 * j] = *reinterpret_cast<const float2*>(tab + 4 * rid[j].x + 2 * hp);
        e[2 * j + 1] = *reinterpret_cast<const float2*>(tab + 4 * rid[j].y + 2 * hp);
      }
      float m[4] = {0.f, 0.f, 0.f, 0.f};
#pragma unroll
      for (int j = 0; j < 16; j++) {
        m[(j & 1) * 2] = fmaxf(m[(j & 1) * 2], fmaxf(e[2 * j].x, e[2 * j + 1].x));
        m[(j & 1) * 2 + 1] = fmaxf(m[(j & 1) * 2 + 1], fmaxf(e[2 * j].y, e[2 * j + 1].y));
      }
      const float t0 = hp ? tau[2] : tau[0], t1 = hp ? tau[3] : tau[1];
      const float sh0 = ((slow_heads >> (2 * hp)) & 1) ? 1.f : ex2(-1.02f * t0), sh1 = ((slow_heads >> (2 * hp + 1)) & 1) ? 1.f : ex2(-1.02f * t1);
#pragma unroll
      for (int q = 0; q < 4; q++) {
        m[q] = fmaxf(m[q], __shfl_xor_sync(0xffffffffu, m[q], 1));
        m[q] = fmaxf(m[q], __shfl_xor_sync(0xffffffffu, m[q], 2));
        m[q] = rcp(m[q]) * ((q & 1) ? sh1 : sh0);
      }
      uint8_t* dst = smem + SM_EB + 2 * hp * 8192 + t16;
#pragma unroll
      for (int j = 0; j < 4; j++) {
        const float2* f = e + 8 * j;
        *reinterpret_cast<uint4*>(dst + j * 2048) =
            make_uint4(pack_bf16(f[0].x * m[0], f[1].x * m[0]), pack_bf16(f[2].x * m[2], f[3].x * m[2]),
                       pack_bf16(f[4].x * m[0], f[5].x * m[0]), pack_bf16(f[6].x * m[2], f[7].x * m[2]));
        *reinterpret_cast<uint4*>(dst + 8192 + j * 2048) =
            make_uint4(pack_bf16(f[0].y * m[1], f[1].y * m[1]), pack_bf16(f[2].y * m[3], f[3].y * m[3]),
                       pack_bf16(f[4].y * m[1], f[5].y * m[1]), pack_bf16(f[6].y * m[3], f[7].y * m[3]));
      }
    }
    TL(6);
    {
      float sum = 0.f;
      if (i < 192) {
#pragma unroll
        for (int c = 0; c < 6; c++)
          sum += (bf_lo(v[c].x) + bf_hi(v[c].x)) + (bf_lo(v[c].y) + bf_hi(v[c].y)) + (bf_lo(v[c].z) + bf_hi(v[c].z)) + (bf_lo(v[c].w) + bf_hi(v[c].w));
      }
      sum += __shfl_xor_sync(0xffffffffu, sum, 1);
      if (i < 192) {
        const float mu = sum * (1.f / 96.f);
        auto cen = [&](uint32_t u) { return pack_bf16(bf_lo(u) - mu, bf_hi(u) - mu); };
        const int k = i >> 1;
        uint8_t* dst = smem + SM_WO + (k >> 3) * 128 + (k & 7) * 16 + (i & 1) * 8;
#pragma unroll
        for (int j = 0; j < 3; j++) {
          *reinterpret_cast<uint2*>(dst + (4 * j + 0) * 1536) = make_uint2(cen(v[2 * j].x), cen(v[2 * j + 1].x));
          *reinterpret_cast<uint2*>(dst + (4 * j + 1) * 1536) = make_uint2(cen(v[2 * j].y), cen(v[2 * j + 1].y));
          *reinterpret_cast<uint2*>(dst + (4 * j + 2) * 1536) = make_uint2(cen(v[2 * j].z), cen(v[2 * j + 1].z));
          *reinterpret_cast<uint2*>(dst + (4 * j + 3) * 1536) = make_uint2(cen(v[2 * j].w), cen(v[2 * j + 1].w));
        }
      }
    }
    fence_async();
    TL(7);
    bar_sync_n(11, 384);
    if (wg == 2) bar_arrive_n(8, 256);
  }
  TL(1);
  mbar_wait(sb + SM_BAR, 0);
  TL(2);

  constexpr uint32_t dW   = mk_desc(sb + SM_W, 6144);
  constexpr uint32_t dWo  = mk_desc(sb + SM_WO, 128);
  constexpr uint32_t dSel = mk_desc(sb + SM_SEL, 128);
  constexpr uint32_t dOne = mk_desc(sb + SM_WG + WG_V + 3 * 1024, 128);
  const uint32_t k_dst = wgb + WG_K + (lane >> 4) * 7168 + warp * 256 + (lane & 15) * 16;
  const uint32_t v_dst = k_dst + (WG_V - WG_K);
  const uint32_t eb_base = sb + SM_EB + t16;
  const uint32_t out_off = ((g >> 2) * IMG + (g & 3)) * PIXB + t * 16;
  const int bar_id = 1 + wg;
  const int tok_next = wg == 2 ? 8 : 9 + wg;
  uint32_t xphase = 0;

  for (; slot < NWIN; slot += stride) {
    const bool more = slot + stride < NWIN;
    const int nxt = more ? slot_window(slot + stride, gridDim.x) : win;
    const uint32_t dbase = (wgb >> 4) + (slot >> 20);
    const uint32_t dX = dbase + mk_desc(WG_X, 16), dK = dbase + mk_desc(WG_K, 1024), dV = dbase + mk_desc(WG_V, 128);
    TL(0);
    mbar_wait(bar_x, xphase); xphase ^= 1;
    TL(1);
    float qk[96], vv[48];
    wg_fence();
#pragma unroll
    for (int s = 0; s < 6; s++) {
      const uint32_t a = dX + (s >> 1) * 256 + (s & 1) * 2, b = dW + s * 64;
      if (s == 0) wgmma_ss_n192_t1<0>(qk, a, b); else wgmma_ss_n192_t1<1>(qk, a, b);
    }
    wg_commit();
    const uint32_t mword = (mw[0].x | mw[0].y | mw[0].z | mw[0].w | mw[1].x | mw[1].y | mw[1].z | mw[1].w) |
                           (mw[2].x | mw[2].y | mw[2].z | mw[2].w | mw[3].x | mw[3].y | mw[3].z | mw[3].w);
    const bool masked = bar_wg_or(bar_id + 4, (mword & 0x7FFF7FFFu) != 0u);
    wg_wait<0>();
    fence_regs(qk);
    TL(2);
    uint32_t qa[24], ka[24];
#pragma unroll
    for (int i = 0; i < 24; i++) { qa[i] = pack_bf16(qk[2 * i], qk[2 * i + 1]); ka[i] = pack_bf16(qk[48 + 2 * i], qk[48 + 2 * i + 1]); }
    {
      uint32_t sq[8], sk[8];
      const uint32_t EPS8 = 0x2A0D2A0Du;
      sumsq(ka, sk, EPS8);
      sumsq(qa, sq, EPS8);
      float k01[4], k23[4], q01[4], q23[4];
      wg_fence();
      wgmma_rs_n8_t0<0>(k01, sk[0], sk[1], sk[2], sk[3], dSel);
      wgmma_rs_n8_t0<0>(k23, sk[4], sk[5], sk[6], sk[7], dSel);
      wgmma_rs_n8_t0<0>(q01, sq[0], sq[1], sq[2], sq[3], dSel);
      wgmma_rs_n8_t0<0>(q23, sq[4], sq[5], sq[6], sq[7], dSel);
      wg_commit();
#pragma unroll
      for (int s = 0; s < 6; s++) {
        const uint32_t a = dX + (s >> 1) * 256 + (s & 1) * 2, b = dW + 6 * 384 + s * 64;
        if (s == 0) wgmma_ss_n96_t1<0>(vv, a, b); else wgmma_ss_n96_t1<1>(vv, a, b);
      }
      wg_commit();
      const uint4 qs = lds128(sb + SM_MISC);
      wg_wait<1>();
      fence_regs(k01); fence_regs(k23); fence_regs(q01); fence_regs(q23);
      TL(3);
      const float rk[8] = {rsq(k01[0]), rsq(k01[2]), rsq(k01[1]), rsq(k01[3]), rsq(k23[0]), rsq(k23[2]), rsq(k23[1]), rsq(k23[3])};
      scale_heads(ka, rk);
#pragma unroll
      for (int i = 0; i < 6; i++) stsm4(k_dst + (i + (i >= 3)) * 1024, ka[2 * i], ka[2 * i + 1], ka[12 + 2 * i], ka[12 + 2 * i + 1]);
      const float s0 = __uint_as_float(qs.x), s1 = __uint_as_float(qs.y), s2 = __uint_as_float(qs.z), s3 = __uint_as_float(qs.w);
      const float rq[8] = {rsq(q01[0]) * s0, rsq(q01[2]) * s0, rsq(q01[1]) * s1, rsq(q01[3]) * s1,
                           rsq(q23[0]) * s2, rsq(q23[2]) * s2, rsq(q23[1]) * s3, rsq(q23[3]) * s3};
      scale_heads(qa, rq);
    }
    TL(4);
    wg_wait<0>();
    fence_regs(vv);
    TL(5);
#pragma unroll
    for (int i = 0; i < 6; i++)
      stsm4(v_dst + (i + (i >= 3)) * 1024, pack_bf16(vv[4 * i], vv[4 * i + 1]), pack_bf16(vv[4 * i + 2], vv[4 * i + 3]),
            pack_bf16(vv[24 + 4 * i], vv[24 + 4 * i + 1]), pack_bf16(vv[24 + 4 * i + 2], vv[24 + 4 * i + 3]));
    fence_async();
    bar_wg(bar_id);
    TL(6);
    if ((tid & 127) == 0) {
      if (more) { load_x(nxt); prefetch_l2(mask_ptr(nxt), 8192); }
    }
    __syncwarp();

    const bool pass_token = (wg == 2 ? slot + stride - 2 * (int)gridDim.x : slot + (int)gridDim.x) < NWIN;
    uint32_t of[24];
    if (!masked && slow_heads == 0) {
      float sA[32], sB[32], oA[16], oB[16];
      uint32_t pA[16], pB[16];
      wg_fence();
      issue_s<0>(sA, qa, dK);
      issue_s<1>(sB, qa, dK); wg_commit();
      bar_sync_n(8 + wg, 256);
      wg_wait<0>(); fence_regs(sA); fence_regs(sB);
      TL(7);
      softmax_fast(sA, pA, eb_base);
      wg_fence();
      issue_pv<0>(oA, pA, dV);
      issue_s<2>(sA, qa, dK); wg_commit();
      TL(8);
      softmax_fast(sB, pB, eb_base + 8192);
      wg_wait<0>(); fence_regs(sA); fence_regs(oA);
      wg_fence();
      issue_pv<1>(oB, pB, dV);
      issue_s<3>(sB, qa, dK); wg_commit();
      TL(9);
      norm_o<0>(oA, of);
      softmax_fast(sA, pA, eb_base + 2 * 8192);
      wg_wait<0>(); fence_regs(sB); fence_regs(oB);
      wg_fence();
      issue_pv<2>(oA, pA, dV); wg_commit();
      TL(10);
      norm_o<1>(oB, of + 6);
      softmax_fast(sB, pB, eb_base + 3 * 8192);
      if (pass_token) bar_arrive_n(tok_next, 256);
      wg_fence();
      issue_pv<3>(oB, pB, dV); wg_commit();
      wg_wait<1>(); fence_regs(oA);
      norm_o<0>(oA, of + 12);
      wg_wait<0>(); fence_regs(oB);
      norm_o<1>(oB, of + 18);
    } else {
      uint32_t mk[16];
      const char* mrow = mask_ptr(win) + (orig_tok(16 * warp + g) * 64 + (t >> 1) * 8 + (t & 1) * 2) * 2;
#pragma unroll
      for (int G = 0; G < 8; G++) {
        mk[2 * G] = *reinterpret_cast<const uint32_t*>(mrow + ((G & 3) * 16 + (G >> 2) * 4) * 2);
        mk[2 * G + 1] = *reinterpret_cast<const uint32_t*>(mrow + (16 * 64 + (G & 3) * 16 + (G >> 2) * 4) * 2);
      }
      bar_sync_n(8 + wg, 256);
      if (pass_token) bar_arrive_n(tok_next, 256);
      const uint32_t tm = masked ? 0xFu : slow_heads;
#pragma unroll
      for (int i = 0; i < 24; i++) of[i] = 0;
#pragma unroll 1
      for (int h = 0; h < 4; h++) {
        float sc[32], o[16]; uint32_t p[16];
        const uint32_t po = (h * 3 + (h >> 1)) * 64;
        wg_fence(); issue_s<0>(sc, qa, dK + po); wg_commit();
        wg_wait<0>(); fence_regs(sc);
        if ((tm >> h) & 1) softmax_true_max(sc, p, eb_base + h * 8192, mk); else softmax_fast(sc, p, eb_base + h * 8192);
        wg_fence(); issue_pv<0>(o, p, dV + po); wg_commit();
#pragma unroll
        for (int i = 0; i < 20; i++) qa[i] = (h & 1) ? (i < 16 ? qa[i + 8] : 0u) : qa[i + 4];
#pragma unroll
        for (int i = 0; i < 18; i++) of[i] = of[i + 6];
        wg_wait<0>(); fence_regs(o);
        if (h & 1) norm_o<1>(o, of + 18); else norm_o<0>(o, of + 18);
      }
    }
    TL(11);

    float y[48];
    wg_fence();
#pragma unroll
    for (int s = 0; s < 6; s++) {
      if (s == 0) wgmma_rs_n96_t1<0>(y, of[0], of[1], of[2], of[3], dWo);
      else wgmma_rs_n96_t1<1>(y, of[4 * s], of[4 * s + 1], of[4 * s + 2], of[4 * s + 3], dWo + s * 16);
    }
    wg_commit();
    load_mask(nxt);
    char* optr;
    {
      const int wy = win >> 8, wx = win & 255;
      int py = wy * 8 + 4 + (warp & 1) * 4;  if (py >= IMG) py -= IMG;
      int px = wx * 8 + 4 + (warp >> 1) * 4; if (px >= IMG) px -= IMG;
      optr = reinterpret_cast<char*>(out) + ((uint32_t)(py * IMG + px) * PIXB + out_off);
    }
    wg_wait<0>(); fence_regs(y);
    TL(12);
    uint32_t yb[24], sy[8];
#pragma unroll
    for (int i = 0; i < 24; i++) yb[i] = pack_bf16(y[2 * i], y[2 * i + 1]);
    sumsq(yb, sy, 0u);
    float var[4];
    wg_fence();
    wgmma_rs_n8_t0<0>(var, sy[0], sy[1], sy[2], sy[3], dOne);
    wgmma_rs_n8_t0<1>(var, sy[4], sy[5], sy[6], sy[7], dOne);
    wg_commit();
    wg_wait<0>(); fence_regs(var);
    TL(13);
    const float r0 = rsq(fmaf(var[0], 1.f / 96.f, 1e-5f)), r1 = rsq(fmaf(var[2], 1.f / 96.f, 1e-5f));
    const uint32_t n0 = pack_bf16(r0, r0), n1 = pack_bf16(r1, r1);
#pragma unroll
    for (int j = 0; j < 3; j++) {
      stg128(optr + j * 64, hmul2(yb[8 * j], n0), hmul2(yb[8 * j + 2], n0), hmul2(yb[8 * j + 4], n0), hmul2(yb[8 * j + 6], n0));
      stg128(optr + 2 * ROWB + j * 64, hmul2(yb[8 * j + 1], n1), hmul2(yb[8 * j + 3], n1), hmul2(yb[8 * j + 5], n1), hmul2(yb[8 * j + 7], n1));
    }
    win = nxt;
    TL(14);
  }
  TG(15);
}

typedef CUresult (*EncodeFn)(CUtensorMap*, CUtensorMapDataType, cuuint32_t, void*, const cuuint64_t*, const cuuint64_t*,
                             const cuuint32_t*, const cuuint32_t*, CUtensorMapInterleave, CUtensorMapSwizzle,
                             CUtensorMapL2promotion, CUtensorMapFloatOOBfill);

}

extern "C" void kernel_launch(void* const* d_in, const int* in_sizes, int n_in, void* d_out, int out_size) {
  static int sms = 0;
  static EncodeFn encode = nullptr;
  if (sms == 0) {
    int dev = 0;
    cudaGetDevice(&dev);
    cudaDeviceGetAttribute(&sms, cudaDevAttrMultiProcessorCount, dev);
    cudaFuncSetAttribute(swin_kernel, cudaFuncAttributeMaxDynamicSharedMemorySize, SM_TOTAL);
    cudaDriverEntryPointQueryResult qr;
    void* fn = nullptr;
    cudaGetDriverEntryPoint("cuTensorMapEncodeTiled", &fn, cudaEnableDefault, &qr);
    encode = (EncodeFn)fn;
  }
  CUtensorMap tm_x, tm_xq, tm_w;
  {
    cuuint64_t dims[5] = {32, 4, IMG, IMG / 4, 3};
    cuuint64_t strides[4] = {PIXB, ROWB, 4 * PIXB, 64};
    cuuint32_t es[5] = {1, 1, 1, 1, 1};
    cuuint32_t box[5] = {32, 4, 8, 2, 3}, boxq[5] = {32, 4, 4, 1, 1};
    encode(&tm_x, CU_TENSOR_MAP_DATA_TYPE_BFLOAT16, 5, d_in[0], dims, strides, box, es, CU_TENSOR_MAP_INTERLEAVE_NONE,
           CU_TENSOR_MAP_SWIZZLE_64B, CU_TENSOR_MAP_L2_PROMOTION_L2_128B, CU_TENSOR_MAP_FLOAT_OOB_FILL_NONE);
    encode(&tm_xq, CU_TENSOR_MAP_DATA_TYPE_BFLOAT16, 5, d_in[0], dims, strides, boxq, es, CU_TENSOR_MAP_INTERLEAVE_NONE,
           CU_TENSOR_MAP_SWIZZLE_64B, CU_TENSOR_MAP_L2_PROMOTION_L2_128B, CU_TENSOR_MAP_FLOAT_OOB_FILL_NONE);
    cuuint64_t wd[3] = {32, 96, 9};
    cuuint64_t ws[2] = {576, 64};
    cuuint32_t wb[3] = {32, 96, 9};
    encode(&tm_w, CU_TENSOR_MAP_DATA_TYPE_BFLOAT16, 3, d_in[1], wd, ws, wb, es, CU_TENSOR_MAP_INTERLEAVE_NONE,
           CU_TENSOR_MAP_SWIZZLE_64B, CU_TENSOR_MAP_L2_PROMOTION_L2_128B, CU_TENSOR_MAP_FLOAT_OOB_FILL_NONE);
  }
  swin_kernel<<<sms, 384, SM_TOTAL>>>(
      tm_x, tm_xq, tm_w, (const __nv_bfloat16*)d_in[2], (const __nv_bfloat16*)d_in[3],
      (const __nv_bfloat16*)d_in[4], (const __nv_bfloat16*)d_in[5], (const __nv_bfloat16*)d_in[6], (const int*)d_in[7],
      (const __nv_bfloat16*)d_in[8], (__nv_bfloat16*)d_out);
}
```

```cpp
#include <cuda_runtime.h>
#include <cuda.h>
#include <cuda_bf16.h>
#include <stdint.h>

#define TOKEN 3
namespace {

constexpr int IMG   = 384;
constexpr int NWX   = 48;
constexpr int NWIN  = NWX * NWX;
constexpr int PIXB  = 192;
constexpr int ROWB  = IMG * PIXB;
constexpr float LOG2E = 1.4426950408889634f;

constexpr int SM_W    = 0;
constexpr int SM_WO   = SM_W + 9 * 6144;
constexpr int SM_EB   = SM_WO + 12 * 1536;
constexpr int SM_WG   = SM_EB + 32768;
constexpr int WG_X    = 0;
constexpr int WG_K    = 12288;
constexpr int WG_V    = WG_K + 14336;
constexpr int WG_SZ   = WG_V + 14336;
constexpr int SM_TAB  = SM_WG + 2 * WG_SZ + WG_V + 4096;
constexpr int SM_SEL  = SM_WG + 3 * WG_SZ;
constexpr int SM_MISC = SM_SEL + 256;
constexpr int SM_BAR  = SM_MISC + 16;
constexpr int SM_TOTAL = SM_BAR + 32;

template <int SD> __device__ __forceinline__ void wgmma_ss_n96_t1(float (&d)[48], uint64_t da, uint64_t db) {
  if constexpr (SD) {
    asm volatile("{\n.reg .pred p;\nsetp.ne.b32 p, 1, 0;\n"
      "wgmma.mma_async.sync.aligned.m64n96k16.f32.bf16.bf16 {%0, %1, %2, %3, %4, %5, %6, %7, %8, %9, %10, %11, %12, %13, %14, %15, %16, %17, %18, %19, %20, %21, %22, %23, %24, %25, %26, %27, %28, %29, %30, %31, %32, %33, %34, %35, %36, %37, %38, %39, %40, %41, %42, %43, %44, %45, %46, %47}, %48, %49, p, 1, 1, 0, 1;\n}\n"
      : "+f"(d[0]), "+f"(d[1]), "+f"(d[2]), "+f"(d[3]), "+f"(d[4]), "+f"(d[5]), "+f"(d[6]), "+f"(d[7]), "+f"(d[8]), "+f"(d[9]), "+f"(d[10]), "+f"(d[11]), "+f"(d[12]), "+f"(d[13]), "+f"(d[14]), "+f"(d[15]), "+f"(d[16]), "+f"(d[17]), "+f"(d[18]), "+f"(d[19]), "+f"(d[20]), "+f"(d[21]), "+f"(d[22]), "+f"(d[23]), "+f"(d[24]), "+f"(d[25]), "+f"(d[26]), "+f"(d[27]), "+f"(d[28]), "+f"(d[29]), "+f"(d[30]), "+f"(d[31]), "+f"(d[32]), "+f"(d[33]), "+f"(d[34]), "+f"(d[35]), "+f"(d[36]), "+f"(d[37]), "+f"(d[38]), "+f"(d[39]), "+f"(d[40]), "+f"(d[41]), "+f"(d[42]), "+f"(d[43]), "+f"(d[44]), "+f"(d[45]), "+f"(d[46]), "+f"(d[47])
      : "l"(da), "l"(db));
  } else {
    asm volatile("{\n.reg .pred p;\nsetp.ne.b32 p, 0, 0;\n"
      "wgmma.mma_async.sync.aligned.m64n96k16.f32.bf16.bf16 {%0, %1, %2, %3, %4, %5, %6, %7, %8, %9, %10, %11, %12, %13, %14, %15, %16, %17, %18, %19, %20, %21, %22, %23, %24, %25, %26, %27, %28, %29, %30, %31, %32, %33, %34, %35, %36, %37, %38, %39, %40, %41, %42, %43, %44, %45, %46, %47}, %48, %49, p, 1, 1, 0, 1;\n}\n"
      : "=f"(d[0]), "=f"(d[1]), "=f"(d[2]), "=f"(d[3]), "=f"(d[4]), "=f"(d[5]), "=f"(d[6]), "=f"(d[7]), "=f"(d[8]), "=f"(d[9]), "=f"(d[10]), "=f"(d[11]), "=f"(d[12]), "=f"(d[13]), "=f"(d[14]), "=f"(d[15]), "=f"(d[16]), "=f"(d[17]), "=f"(d[18]), "=f"(d[19]), "=f"(d[20]), "=f"(d[21]), "=f"(d[22]), "=f"(d[23]), "=f"(d[24]), "=f"(d[25]), "=f"(d[26]), "=f"(d[27]), "=f"(d[28]), "=f"(d[29]), "=f"(d[30]), "=f"(d[31]), "=f"(d[32]), "=f"(d[33]), "=f"(d[34]), "=f"(d[35]), "=f"(d[36]), "=f"(d[37]), "=f"(d[38]), "=f"(d[39]), "=f"(d[40]), "=f"(d[41]), "=f"(d[42]), "=f"(d[43]), "=f"(d[44]), "=f"(d[45]), "=f"(d[46]), "=f"(d[47])
      : "l"(da), "l"(db));
  }
}
template <int SD> __device__ __forceinline__ void wgmma_rs_n96_t1(float (&d)[48], uint32_t a0, uint32_t a1, uint32_t a2, uint32_t a3, uint64_t db) {
  if constexpr (SD) {
    asm volatile("{\n.reg .pred p;\nsetp.ne.b32 p, 1, 0;\n"
      "wgmma.mma_async.sync.aligned.m64n96k16.f32.bf16.bf16 {%0, %1, %2, %3, %4, %5, %6, %7, %8, %9, %10, %11, %12, %13, %14, %15, %16, %17, %18, %19, %20, %21, %22, %23, %24, %25, %26, %27, %28, %29, %30, %31, %32, %33, %34, %35, %36, %37, %38, %39, %40, %41, %42, %43, %44, %45, %46, %47}, {%48, %49, %50, %51}, %52, p, 1, 1, 1;\n}\n"
      : "+f"(d[0]), "+f"(d[1]), "+f"(d[2]), "+f"(d[3]), "+f"(d[4]), "+f"(d[5]), "+f"(d[6]), "+f"(d[7]), "+f"(d[8]), "+f"(d[9]), "+f"(d[10]), "+f"(d[11]), "+f"(d[12]), "+f"(d[13]), "+f"(d[14]), "+f"(d[15]), "+f"(d[16]), "+f"(d[17]), "+f"(d[18]), "+f"(d[19]), "+f"(d[20]), "+f"(d[21]), "+f"(d[22]), "+f"(d[23]), "+f"(d[24]), "+f"(d[25]), "+f"(d[26]), "+f"(d[27]), "+f"(d[28]), "+f"(d[29]), "+f"(d[30]), "+f"(d[31]), "+f"(d[32]), "+f"(d[33]), "+f"(d[34]), "+f"(d[35]), "+f"(d[36]), "+f"(d[37]), "+f"(d[38]), "+f"(d[39]), "+f"(d[40]), "+f"(d[41]), "+f"(d[42]), "+f"(d[43]), "+f"(d[44]), "+f"(d[45]), "+f"(d[46]), "+f"(d[47])
      : "r"(a0), "r"(a1), "r"(a2), "r"(a3), "l"(db));
  } else {
    asm volatile("{\n.reg .pred p;\nsetp.ne.b32 p, 0, 0;\n"
      "wgmma.mma_async.sync.aligned.m64n96k16.f32.bf16.bf16 {%0, %1, %2, %3, %4, %5, %6, %7, %8, %9, %10, %11, %12, %13, %14, %15, %16, %17, %18, %19, %20, %21, %22, %23, %24, %25, %26, %27, %28, %29, %30, %31, %32, %33, %34, %35, %36, %37, %38, %39, %40, %41, %42, %43, %44, %45, %46, %47}, {%48, %49, %50, %51}, %52, p, 1, 1, 1;\n}\n"
      : "=f"(d[0]), "=f"(d[1]), "=f"(d[2]), "=f"(d[3]), "=f"(d[4]), "=f"(d[5]), "=f"(d[6]), "=f"(d[7]), "=f"(d[8]), "=f"(d[9]), "=f"(d[10]), "=f"(d[11]), "=f"(d[12]), "=f"(d[13]), "=f"(d[14]), "=f"(d[15]), "=f"(d[16]), "=f"(d[17]), "=f"(d[18]), "=f"(d[19]), "=f"(d[20]), "=f"(d[21]), "=f"(d[22]), "=f"(d[23]), "=f"(d[24]), "=f"(d[25]), "=f"(d[26]), "=f"(d[27]), "=f"(d[28]), "=f"(d[29]), "=f"(d[30]), "=f"(d[31]), "=f"(d[32]), "=f"(d[33]), "=f"(d[34]), "=f"(d[35]), "=f"(d[36]), "=f"(d[37]), "=f"(d[38]), "=f"(d[39]), "=f"(d[40]), "=f"(d[41]), "=f"(d[42]), "=f"(d[43]), "=f"(d[44]), "=f"(d[45]), "=f"(d[46]), "=f"(d[47])
      : "r"(a0), "r"(a1), "r"(a2), "r"(a3), "l"(db));
  }
}
template <int SD> __device__ __forceinline__ void wgmma_rs_n64_t0(float (&d)[32], uint32_t a0, uint32_t a1, uint32_t a2, uint32_t a3, uint64_t db) {
  if constexpr (SD) {
    asm volatile("{\n.reg .pred p;\nsetp.ne.b32 p, 1, 0;\n"
      "wgmma.mma_async.sync.aligned.m64n64k16.f32.bf16.bf16 {%0, %1, %2, %3, %4, %5, %6, %7, %8, %9, %10, %11, %12, %13, %14, %15, %16, %17, %18, %19, %20, %21, %22, %23, %24, %25, %26, %27, %28, %29, %30, %31}, {%32, %33, %34, %35}, %36, p, 1, 1, 0;\n}\n"
      : "+f"(d[0]), "+f"(d[1]), "+f"(d[2]), "+f"(d[3]), "+f"(d[4]), "+f"(d[5]), "+f"(d[6]), "+f"(d[7]), "+f"(d[8]), "+f"(d[9]), "+f"(d[10]), "+f"(d[11]), "+f"(d[12]), "+f"(d[13]), "+f"(d[14]), "+f"(d[15]), "+f"(d[16]), "+f"(d[17]), "+f"(d[18]), "+f"(d[19]), "+f"(d[20]), "+f"(d[21]), "+f"(d[22]), "+f"(d[23]), "+f"(d[24]), "+f"(d[25]), "+f"(d[26]), "+f"(d[27]), "+f"(d[28]), "+f"(d[29]), "+f"(d[30]), "+f"(d[31])
      : "r"(a0), "r"(a1), "r"(a2), "r"(a3), "l"(db));
  } else {
    asm volatile("{\n.reg .pred p;\nsetp.ne.b32 p, 0, 0;\n"
      "wgmma.mma_async.sync.aligned.m64n64k16.f32.bf16.bf16 {%0, %1, %2, %3, %4, %5, %6, %7, %8, %9, %10, %11, %12, %13, %14, %15, %16, %17, %18, %19, %20, %21, %22, %23, %24, %25, %26, %27, %28, %29, %30, %31}, {%32, %33, %34, %35}, %36, p, 1, 1, 0;\n}\n"
      : "=f"(d[0]), "=f"(d[1]), "=f"(d[2]), "=f"(d[3]), "=f"(d[4]), "=f"(d[5]), "=f"(d[6]), "=f"(d[7]), "=f"(d[8]), "=f"(d[9]), "=f"(d[10]), "=f"(d[11]), "=f"(d[12]), "=f"(d[13]), "=f"(d[14]), "=f"(d[15]), "=f"(d[16]), "=f"(d[17]), "=f"(d[18]), "=f"(d[19]), "=f"(d[20]), "=f"(d[21]), "=f"(d[22]), "=f"(d[23]), "=f"(d[24]), "=f"(d[25]), "=f"(d[26]), "=f"(d[27]), "=f"(d[28]), "=f"(d[29]), "=f"(d[30]), "=f"(d[31])
      : "r"(a0), "r"(a1), "r"(a2), "r"(a3), "l"(db));
  }
}
template <int SD> __device__ __forceinline__ void wgmma_rs_n32_t1(float (&d)[16], uint32_t a0, uint32_t a1, uint32_t a2, uint32_t a3, uint64_t db) {
  if constexpr (SD) {
    asm volatile("{\n.reg .pred p;\nsetp.ne.b32 p, 1, 0;\n"
      "wgmma.mma_async.sync.aligned.m64n32k16.f32.bf16.bf16 {%0, %1, %2, %3, %4, %5, %6, %7, %8, %9, %10, %11, %12, %13, %14, %15}, {%16, %17, %18, %19}, %20, p, 1, 1, 1;\n}\n"
      : "+f"(d[0]), "+f"(d[1]), "+f"(d[2]), "+f"(d[3]), "+f"(d[4]), "+f"(d[5]), "+f"(d[6]), "+f"(d[7]), "+f"(d[8]), "+f"(d[9]), "+f"(d[10]), "+f"(d[11]), "+f"(d[12]), "+f"(d[13]), "+f"(d[14]), "+f"(d[15])
      : "r"(a0), "r"(a1), "r"(a2), "r"(a3), "l"(db));
  } else {
    asm volatile("{\n.reg .pred p;\nsetp.ne.b32 p, 0, 0;\n"
      "wgmma.mma_async.sync.aligned.m64n32k16.f32.bf16.bf16 {%0, %1, %2, %3, %4, %5, %6, %7, %8, %9, %10, %11, %12, %13, %14, %15}, {%16, %17, %18, %19}, %20, p, 1, 1, 1;\n}\n"
      : "=f"(d[0]), "=f"(d[1]), "=f"(d[2]), "=f"(d[3]), "=f"(d[4]), "=f"(d[5]), "=f"(d[6]), "=f"(d[7]), "=f"(d[8]), "=f"(d[9]), "=f"(d[10]), "=f"(d[11]), "=f"(d[12]), "=f"(d[13]), "=f"(d[14]), "=f"(d[15])
      : "r"(a0), "r"(a1), "r"(a2), "r"(a3), "l"(db));
  }
}
template <int SD> __device__ __forceinline__ void wgmma_rs_n8_t0(float (&d)[4], uint32_t a0, uint32_t a1, uint32_t a2, uint32_t a3, uint64_t db) {
  if constexpr (SD) {
    asm volatile("{\n.reg .pred p;\nsetp.ne.b32 p, 1, 0;\n"
      "wgmma.mma_async.sync.aligned.m64n8k16.f32.bf16.bf16 {%0, %1, %2, %3}, {%4, %5, %6, %7}, %8, p, 1, 1, 0;\n}\n"
      : "+f"(d[0]), "+f"(d[1]), "+f"(d[2]), "+f"(d[3])
      : "r"(a0), "r"(a1), "r"(a2), "r"(a3), "l"(db));
  } else {
    asm volatile("{\n.reg .pred p;\nsetp.ne.b32 p, 0, 0;\n"
      "wgmma.mma_async.sync.aligned.m64n8k16.f32.bf16.bf16 {%0, %1, %2, %3}, {%4, %5, %6, %7}, %8, p, 1, 1, 0;\n}\n"
      : "=f"(d[0]), "=f"(d[1]), "=f"(d[2]), "=f"(d[3])
      : "r"(a0), "r"(a1), "r"(a2), "r"(a3), "l"(db));
  }
}

__device__ __forceinline__ void wg_fence()  { asm volatile("wgmma.fence.sync.aligned;" ::: "memory"); }
__device__ __forceinline__ void wg_commit() { asm volatile("wgmma.commit_group.sync.aligned;" ::: "memory"); }
template <int N> __device__ __forceinline__ void wg_wait() { asm volatile("wgmma.wait_group.sync.aligned %0;" :: "n"(N) : "memory"); }
template <int N> __device__ __forceinline__ void fence_regs(float (&d)[N]) {
#pragma unroll
  for (int i = 0; i < N; i++) asm volatile("" : "+f"(d[i]) :: "memory");
}
__device__ __forceinline__ constexpr uint64_t mk_desc(uint32_t addr, uint32_t lbo, uint32_t sbo, uint32_t swz) {
  return (uint64_t)(addr >> 4) | ((uint64_t)(lbo >> 4) << 16) | ((uint64_t)(sbo >> 4) << 32) | ((uint64_t)swz << 62);
}
__device__ __forceinline__ uint32_t pack_bf16(float lo, float hi) {
  uint32_t r; asm("cvt.rn.bf16x2.f32 %0, %1, %2;" : "=r"(r) : "f"(hi), "f"(lo)); return r;
}
__device__ __forceinline__ uint32_t hmul2(uint32_t a, uint32_t b) {
  uint32_t r; asm("mul.rn.bf16x2 %0, %1, %2;" : "=r"(r) : "r"(a), "r"(b)); return r;
}
template <int HI> __device__ __forceinline__ uint32_t hmul2_b(uint32_t a, uint32_t b) {
  uint32_t r;
  if (HI) asm("{\n.reg .b16 l, h;\n.reg .b32 t;\nmov.b32 {l, h}, %2;\nmov.b32 t, {h, h};\nmul.rn.bf16x2 %0, %1, t;\n}\n" : "=r"(r) : "r"(a), "r"(b));
  else    asm("{\n.reg .b16 l, h;\n.reg .b32 t;\nmov.b32 {l, h}, %2;\nmov.b32 t, {l, l};\nmul.rn.bf16x2 %0, %1, t;\n}\n" : "=r"(r) : "r"(a), "r"(b));
  return r;
}
__device__ __forceinline__ uint32_t hfma2(uint32_t a, uint32_t b, uint32_t c) {
  uint32_t r; asm("fma.rn.bf16x2 %0, %1, %2, %3;" : "=r"(r) : "r"(a), "r"(b), "r"(c)); return r;
}
__device__ __forceinline__ float ex2(float x) { float r; asm("ex2.approx.ftz.f32 %0, %1;" : "=f"(r) : "f"(x)); return r; }
__device__ __forceinline__ float lg2(float x) { float r; asm("lg2.approx.ftz.f32 %0, %1;" : "=f"(r) : "f"(x)); return r; }
__device__ __forceinline__ float rsq(float x) { float r; asm("rsqrt.approx.ftz.f32 %0, %1;" : "=f"(r) : "f"(x)); return r; }
__device__ __forceinline__ float rcp(float x) { float r; asm("rcp.approx.ftz.f32 %0, %1;" : "=f"(r) : "f"(x)); return r; }
__device__ __forceinline__ void stsm4(uint32_t addr, uint32_t r0, uint32_t r1, uint32_t r2, uint32_t r3) {
  asm volatile("stmatrix.sync.aligned.m8n8.x4.shared.b16 [%0], {%1,%2,%3,%4};" :: "r"(addr), "r"(r0), "r"(r1), "r"(r2), "r"(r3) : "memory");
}
__device__ __forceinline__ void fence_async() { asm volatile("fence.proxy.async.shared::cta;" ::: "memory"); }
__device__ __forceinline__ void bar_sync_n(int id, int n) { asm volatile("bar.sync %0, %1;" :: "r"(id), "r"(n) : "memory"); }
__device__ __forceinline__ void bar_arrive_n(int id, int n) { asm volatile("bar.arrive %0, %1;" :: "r"(id), "r"(n) : "memory"); }
__device__ __forceinline__ bool bar_wg_or(int id, bool v) {
  uint32_t r;
  asm volatile("{\n.reg .pred p, q;\nsetp.ne.u32 q, %2, 0;\nbar.red.or.pred p, %1, 128, q;\nselp.u32 %0, 1, 0, p;\n}\n"
               : "=r"(r) : "r"(id), "r"((uint32_t)v) : "memory");
  return r != 0;
}
__device__ __forceinline__ void mbar_init(uint32_t bar, uint32_t cnt) { asm volatile("mbarrier.init.shared::cta.b64 [%0], %1;" :: "r"(bar), "r"(cnt) : "memory"); }
__device__ __forceinline__ void mbar_expect(uint32_t bar, uint32_t bytes) {
  asm volatile("mbarrier.arrive.expect_tx.shared::cta.b64 _, [%0], %1;" :: "r"(bar), "r"(bytes) : "memory");
}
__device__ __forceinline__ void mbar_wait(uint32_t bar, uint32_t parity) {
  asm volatile("{\n.reg .pred p;\n.reg .u32 n;\nmov.u32 n, 0;\n"
               "LW_%=:\nmbarrier.try_wait.parity.shared::cta.b64 p, [%0], %1;\n@p bra.uni LD_%=;\n"
               "add.u32 n, n, 1;\nsetp.lt.u32 p, n, 4194304;\n@p bra.uni LW_%=;\ntrap;\nLD_%=:\n}\n"
               :: "r"(bar), "r"(parity) : "memory");
}
__device__ __forceinline__ void tma5(uint32_t dst, const CUtensorMap* m, uint32_t bar, int c0, int c1, int c2, int c3, int c4) {
  asm volatile("cp.async.bulk.tensor.5d.shared::cluster.global.mbarrier::complete_tx::bytes [%0], [%1, {%3, %4, %5, %6, %7}], [%2];"
               :: "r"(dst), "l"(m), "r"(bar), "r"(c0), "r"(c1), "r"(c2), "r"(c3), "r"(c4) : "memory");
}
__device__ __forceinline__ void tma3(uint32_t dst, const CUtensorMap* m, uint32_t bar, int c0, int c1, int c2) {
  asm volatile("cp.async.bulk.tensor.3d.shared::cluster.global.mbarrier::complete_tx::bytes [%0], [%1, {%3, %4, %5}], [%2];"
               :: "r"(dst), "l"(m), "r"(bar), "r"(c0), "r"(c1), "r"(c2) : "memory");
}
__device__ __forceinline__ uint4 lds128(uint32_t addr) {
  uint4 v; asm volatile("ld.shared.v4.u32 {%0,%1,%2,%3}, [%4];" : "=r"(v.x), "=r"(v.y), "=r"(v.z), "=r"(v.w) : "r"(addr)); return v;
}
__device__ __forceinline__ uint4 ldg128_stream(const void* p) {
  uint4 v; asm volatile("ld.global.nc.L1::no_allocate.v4.u32 {%0,%1,%2,%3}, [%4];" : "=r"(v.x), "=r"(v.y), "=r"(v.z), "=r"(v.w) : "l"(p)); return v;
}
__device__ __forceinline__ void stg128(void* p, uint32_t a, uint32_t b, uint32_t c, uint32_t d) {
  asm volatile("st.global.v4.u32 [%0], {%1,%2,%3,%4};" :: "l"(p), "r"(a), "r"(b), "r"(c), "r"(d) : "memory");
}
__device__ __forceinline__ void prefetch_l2(const void* p, uint32_t bytes) {
  asm volatile("cp.async.bulk.prefetch.L2.global [%0], %1;" :: "l"(p), "r"(bytes) : "memory");
}
__device__ __forceinline__ bool elect_one() {
  uint32_t r; asm volatile("{\n.reg .pred p;\nelect.sync _|p, 0xffffffff;\nselp.u32 %0, 1, 0, p;\n}\n" : "=r"(r)); return r != 0;
}
__device__ __forceinline__ float bf_lo(uint32_t u) { return __uint_as_float(u << 16); }
__device__ __forceinline__ float bf_hi(uint32_t u) { return __uint_as_float(u & 0xFFFF0000u); }
__device__ __forceinline__ float rbf(float x) { return bf_lo(pack_bf16(x, 0.f)); }
__device__ __forceinline__ int orig_tok(int r) { return ((r & 31) >> 2) * 8 + (r >> 5) * 4 + (r & 3); }

__device__ __forceinline__ int slot_window(int s, int G) {
  int wy, wx;
  if (G == 132) {
    constexpr int A0 = 396 + 60, A1 = A0 + 72, B0 = 3 * 396 + 132 + 60, B1 = B0 + 23;
    const int i = s - (s >= B1 ? 95 : s >= A1 ? 72 : 0);
    const int k = s >= B0 ? s - B0 + 72 : s - A0;
    const bool border = (s >= A0 && s < A1) || (s >= B0 && s < B1);
    wy = i / 47; wx = i - wy * 47;
    if (border) { wy = k < 48 ? 47 : k - 48; wx = k < 48 ? k : 47; }
  } else {
    wy = s / NWX; wx = s - wy * NWX;
  }
  return wy << 8 | wx;
}

#define EB_WORD(e, j, a) ((((a) ^ ((j) & 1)) == 0) ? (e).x : (((a) ^ ((j) & 1)) == 1) ? (e).y : (((a) ^ ((j) & 1)) == 2) ? (e).z : (e).w)

__device__ __forceinline__ void softmax_fast(const float (&s)[32], uint32_t (&p)[16], uint32_t eb_addr) {
#pragma unroll
  for (int j = 0; j < 4; j++) {
    const uint4 e = lds128(eb_addr + j * 2048);
#pragma unroll
    for (int a = 0; a < 4; a++)
      p[4 * j + a] = hmul2(pack_bf16(ex2(s[8 * j + 2 * a]), ex2(s[8 * j + 2 * a + 1])), EB_WORD(e, j, a));
  }
}
__device__ __forceinline__ void softmax_true_max(float (&s)[32], uint32_t (&p)[16], uint32_t eb_addr, const uint32_t (&mk)[16]) {
#pragma unroll
  for (int j = 0; j < 4; j++) {
    const uint4 e = lds128(eb_addr + j * 2048);
#pragma unroll
    for (int a = 0; a < 4; a++) {
      const uint32_t w = EB_WORD(e, j, a), m = mk[4 * j + a];
      s[8 * j + 2 * a]     = fmaf(bf_lo(m), LOG2E, s[8 * j + 2 * a] + lg2(bf_lo(w)));
      s[8 * j + 2 * a + 1] = fmaf(bf_hi(m), LOG2E, s[8 * j + 2 * a + 1] + lg2(bf_hi(w)));
    }
  }
  float m0 = s[0], m1 = s[2];
#pragma unroll
  for (int g = 0; g < 8; g++) {
    m0 = fmaxf(m0, fmaxf(s[4 * g + 0], s[4 * g + 1]));
    m1 = fmaxf(m1, fmaxf(s[4 * g + 2], s[4 * g + 3]));
  }
  m0 = fmaxf(m0, __shfl_xor_sync(0xffffffffu, m0, 1)); m0 = fmaxf(m0, __shfl_xor_sync(0xffffffffu, m0, 2));
  m1 = fmaxf(m1, __shfl_xor_sync(0xffffffffu, m1, 1)); m1 = fmaxf(m1, __shfl_xor_sync(0xffffffffu, m1, 2));
#pragma unroll
  for (int g = 0; g < 8; g++) {
    p[2 * g + 0] = pack_bf16(ex2(s[4 * g + 0] - m0), ex2(s[4 * g + 1] - m0));
    p[2 * g + 1] = pack_bf16(ex2(s[4 * g + 2] - m1), ex2(s[4 * g + 3] - m1));
  }
}
template <int H> __device__ __forceinline__ void issue_s(float (&s)[32], const uint32_t (&q)[24], uint64_t dK) {
  constexpr int Q0 = (H == 0 ? 0 : H == 1 ? 4 : H == 2 ? 12 : 16), P0 = (H == 0 ? 0 : H == 1 ? 3 : H == 2 ? 7 : 10);
  wgmma_rs_n64_t0<0>(s, q[Q0], q[Q0 + 1], q[Q0 + 2], q[Q0 + 3], dK + P0 * 64);
  wgmma_rs_n64_t0<1>(s, q[Q0 + 4], q[Q0 + 5], q[Q0 + 6], q[Q0 + 7], dK + P0 * 64 + 128);
}
template <int H> __device__ __forceinline__ void issue_pv(float (&o)[16], const uint32_t (&p)[16], uint64_t dV) {
  constexpr int P0 = (H == 0 ? 0 : H == 1 ? 3 : H == 2 ? 7 : 10);
  wgmma_rs_n32_t1<0>(o, p[0], p[1], p[2], p[3], dV + P0 * 64);
  wgmma_rs_n32_t1<1>(o, p[4], p[5], p[6], p[7], dV + P0 * 64 + 16);
  wgmma_rs_n32_t1<1>(o, p[8], p[9], p[10], p[11], dV + P0 * 64 + 32);
  wgmma_rs_n32_t1<1>(o, p[12], p[13], p[14], p[15], dV + P0 * 64 + 48);
}
__device__ __forceinline__ void issue_proj(float (&d)[48], uint64_t dX, uint64_t dW) {
#pragma unroll
  for (int s = 0; s < 6; s++) {
    const uint64_t a = dX + (s >> 1) * 256 + (s & 1) * 2, b = dW + s * 64;
    if (s == 0) wgmma_ss_n96_t1<0>(d, a, b); else wgmma_ss_n96_t1<1>(d, a, b);
  }
}
__device__ __forceinline__ void pack_sumsq(const float (&a)[48], uint32_t (&f)[24], uint32_t (&sq)[8], uint32_t init) {
#pragma unroll
  for (int i = 0; i < 24; i++) f[i] = pack_bf16(a[2 * i], a[2 * i + 1]);
#pragma unroll
  for (int h = 0; h < 4; h++)
#pragma unroll
    for (int r = 0; r < 2; r++) {
      uint32_t u = f[6 * h + r], v = f[6 * h + 2 + r], w = f[6 * h + 4 + r];
      sq[2 * h + r] = hfma2(w, w, hfma2(v, v, hfma2(u, u, init)));
    }
}
__device__ __forceinline__ void scale_heads(uint32_t (&f)[24], const float (&r)[8]) {
#pragma unroll
  for (int h = 0; h < 4; h++) {
    const uint32_t p = pack_bf16(r[2 * h], r[2 * h + 1]);
#pragma unroll
    for (int c = 0; c < 3; c++) {
      f[6 * h + 2 * c] = hmul2_b<0>(f[6 * h + 2 * c], p);
      f[6 * h + 2 * c + 1] = hmul2_b<1>(f[6 * h + 2 * c + 1], p);
    }
  }
}
template <int ODD> __device__ __forceinline__ void norm_o(const float (&o)[16], uint32_t* of) {
  constexpr int SO = ODD ? 0 : 12, VO = ODD ? 4 : 0;
  const uint32_t p = pack_bf16(rcp(o[SO]), rcp(o[SO + 2]));
#pragma unroll
  for (int g = 0; g < 3; g++) {
    of[2 * g + 0] = hmul2_b<0>(pack_bf16(o[VO + 4 * g + 0], o[VO + 4 * g + 1]), p);
    of[2 * g + 1] = hmul2_b<1>(pack_bf16(o[VO + 4 * g + 2], o[VO + 4 * g + 3]), p);
  }
}

#define TL(i)
#define TG(i)

constexpr int BAR_KV = 1;
constexpr int BAR_OR = 4;
constexpr int BAR_TOK = 7;
constexpr int BAR_SETUP0 = 10, BAR_TAB = 11, BAR_WO = 12;

__global__ void __launch_bounds__(384, 1)
swin_kernel(const __grid_constant__ CUtensorMap tm_x, const __grid_constant__ CUtensorMap tm_xq, const __grid_constant__ CUtensorMap tm_w,
            const __nv_bfloat16* __restrict__ wo,
            const __nv_bfloat16* __restrict__ logit_scale, const __nv_bfloat16* __restrict__ w1, const __nv_bfloat16* __restrict__ w2,
            const __nv_bfloat16* __restrict__ coords, const int* __restrict__ rel_idx, const __nv_bfloat16* __restrict__ mask,
            __nv_bfloat16* __restrict__ out) {
  extern __shared__ __align__(1024) uint8_t smem[];
  constexpr uint32_t sb = 1024;
  const int tid = threadIdx.x, lane = tid & 31;
  const int warp = __shfl_sync(0xffffffffu, (tid >> 5) & 3, 0), wg = __shfl_sync(0xffffffffu, tid >> 7, 0);
  const uint32_t t16 = (tid & 127) * 16;
  const int G = gridDim.x, stride = 3 * G;
  int slot = wg * G + blockIdx.x;
  const uint32_t wgb = sb + SM_WG + wg * WG_SZ;
  const uint32_t bar_x = sb + SM_BAR + 8 + 8 * wg;
  const char* mb = reinterpret_cast<const char*>(mask);
  TL(0); TG(14);

  auto load_x = [&](int w) {
    const int wy = w >> 8, wx = w & 255;
    mbar_expect(bar_x, 12288);
    if (wy != NWX - 1 && wx != NWX - 1) {
      tma5(wgb + WG_X, &tm_x, bar_x, 0, 0, wy * 8 + 4, wx * 2 + 1, 0);
    } else {
#pragma unroll 1
      for (int i = 0; i < 12; i++) {
        const int q = i & 3, c = i >> 2;
        int y = wy * 8 + 4 + (q & 1) * 4; if (y >= IMG) y -= IMG;
        int xq = wx * 2 + 1 + (q >> 1);   if (xq >= IMG / 4) xq -= IMG / 4;
        tma5(wgb + WG_X + i * 1024, &tm_xq, bar_x, 0, 0, y, xq, c);
      }
    }
  };
  auto mask_ptr = [&](int w) { return mb + (uint32_t)((w >> 8) * NWX + (w & 255)) * 8192u; };
  uint4 mw[4];
  auto load_mask = [&](int w) {
    const char* src = mask_ptr(w) + t16;
#pragma unroll
    for (int i = 0; i < 4; i++) mw[i] = ldg128_stream(src + i * 2048);
  };

  int win = slot_window(slot, G);
  if (warp == 0 && elect_one()) {
    mbar_init(bar_x, 1);
    if (wg == 0) mbar_init(sb + SM_BAR, 1);
    fence_async();
    if (wg == 0) { mbar_expect(sb + SM_BAR, 9 * 6144); tma3(sb + SM_W, &tm_w, sb + SM_BAR, 0, 0, 0); }
    load_x(win);
  }
  __syncwarp();
  if ((uint32_t)__cvta_generic_to_shared(smem) != sb) __trap();
  const uint2 lsw = __ldg(reinterpret_cast<const uint2*>(logit_scale));
  uint32_t cw = 0, wa[16], wb[32];
  int4 rid[4];
  if (wg != 0) {
    const int i = tid - 128;
    if (i < 225) cw = __ldg(reinterpret_cast<const uint32_t*>(coords) + i);
#pragma unroll
    for (int j = 0; j < 4; j++) *reinterpret_cast<uint4*>(wa + 4 * j) = __ldg(reinterpret_cast<const uint4*>(w1) + j);
#pragma unroll
    for (int j = 0; j < 8; j++) *reinterpret_cast<uint4*>(wb + 4 * j) = __ldg(reinterpret_cast<const uint4*>(w2) + j);
#pragma unroll
    for (int c = 0; c < 4; c++) rid[c] = __ldg(reinterpret_cast<const int4*>(rel_idx) + c * 256 + i);
  }
  {
    const int i = tid & 127;
    uint8_t* vt = smem + SM_WG + wg * WG_SZ + WG_V + (i < 64 ? 3 : 10) * 1024 + (i & 63) * 16;
    *reinterpret_cast<uint4*>(vt) = make_uint4(0x3F803F80u, 0x3F803F80u, 0x3F803F80u, 0x3F803F80u);
    *reinterpret_cast<uint4*>(vt - (WG_V - WG_K)) = make_uint4(0u, 0u, 0u, 0u);
    if (tid < 16) {
      const uint32_t v = (((tid >> 3) ^ tid) & 1) ? 0u : 0x3F803F80u;
      *reinterpret_cast<uint4*>(smem + SM_SEL + tid * 16) = make_uint4(v, v, v, v);
    }
  }
  float tau[4]; uint32_t slow_heads = 0;
  {
    const float ls[4] = {bf_lo(lsw.x), bf_hi(lsw.x), bf_lo(lsw.y), bf_hi(lsw.y)};
#pragma unroll
    for (int h = 0; h < 4; h++) {
      const float c = ls[h] < -100.f ? -100.f : (ls[h] > 4.59375f ? 4.59375f : ls[h]);
      tau[h] = rbf(ex2(c * LOG2E)) * LOG2E;
      if (!(tau[h] * 2.04f <= 80.f)) slow_heads |= 1u << h;
    }
    slow_heads = __shfl_sync(0xffffffffu, slow_heads, 0);
  }
  TL(3);
  if (wg == 0) {
    if (tid == 0) *reinterpret_cast<float4*>(smem + SM_MISC) = make_float4(tau[0], tau[1], tau[2], tau[3]);
    fence_async();
    bar_arrive_n(BAR_SETUP0, 384);
    bar_sync_n(BAR_KV, 128);
  } else {
    const int i = tid - 128;
    if (i < 225) {
      const float c0 = bf_lo(cw), c1 = bf_hi(cw);
      float z[4] = {0.f, 0.f, 0.f, 0.f};
#pragma unroll
      for (int j = 0; j < 16; j++) {
        const float u = (j & 1) ? bf_hi(wa[j >> 1]) : bf_lo(wa[j >> 1]), w = (j & 1) ? bf_hi(wa[8 + (j >> 1)]) : bf_lo(wa[8 + (j >> 1)]);
        float h = rbf(fmaf(c1, w, c0 * u));
        h = h > 0.f ? h : h * 0.f;
        z[0] = fmaf(h, bf_lo(wb[2 * j]), z[0]); z[1] = fmaf(h, bf_hi(wb[2 * j]), z[1]);
        z[2] = fmaf(h, bf_lo(wb[2 * j + 1]), z[2]); z[3] = fmaf(h, bf_hi(wb[2 * j + 1]), z[3]);
      }
      float e[4];
#pragma unroll
      for (int q = 0; q < 4; q++) {
        const float sh = ((slow_heads >> q) & 1) ? 0.f : -1.02f * tau[q];
        e[q] = ex2(fmaf(16.f * LOG2E, rbf(rcp(1.f + ex2(-LOG2E * rbf(z[q])))), sh));
      }
      *reinterpret_cast<uint2*>(smem + SM_TAB + 8 * i) = make_uint2(pack_bf16(e[0], e[1]), pack_bf16(e[2], e[3]));
    }
    TL(4);
    bar_sync_n(BAR_TAB, 256);
    {
      const int y = (i & 15) >> 1, xh = i & 1, j = 2 * xh + (y >> 2);
      const int X = (i >> 4) & 7, Yl = (i >> 7) & 1;
      uint8_t* dst = smem + SM_EB + j * 2048 + ((X >> 2) * 64 + (Yl * 4 + (X & 3)) * 4 + 2 * (y & 1)) * 16 + ((y >> 1) & 1) * 8;
#pragma unroll
      for (int c = 0; c < 4; c++) {
        const uint2 e0 = *reinterpret_cast<const uint2*>(smem + SM_TAB + 8 * rid[c].x), e1 = *reinterpret_cast<const uint2*>(smem + SM_TAB + 8 * rid[c].y);
        const uint2 e2 = *reinterpret_cast<const uint2*>(smem + SM_TAB + 8 * rid[c].z), e3 = *reinterpret_cast<const uint2*>(smem + SM_TAB + 8 * rid[c].w);
        const uint2 a0 = xh ? e2 : e0, a1 = xh ? e3 : e1, b0 = xh ? e0 : e2, b1 = xh ? e1 : e3;
        uint8_t* d0 = dst + (c >> 1) * 512 + (((c & 1) ^ (j & 1)) * 4) + xh * 16;
        uint8_t* d1 = dst + (c >> 1) * 512 + (((c & 1) ^ (j & 1)) * 4) + (xh ^ 1) * 16;
        *reinterpret_cast<uint32_t*>(d0)         = __byte_perm(a0.x, a1.x, 0x5410); *reinterpret_cast<uint32_t*>(d1)         = __byte_perm(b0.x, b1.x, 0x5410);
        *reinterpret_cast<uint32_t*>(d0 + 8192)  = __byte_perm(a0.x, a1.x, 0x7632); *reinterpret_cast<uint32_t*>(d1 + 8192)  = __byte_perm(b0.x, b1.x, 0x7632);
        *reinterpret_cast<uint32_t*>(d0 + 16384) = __byte_perm(a0.y, a1.y, 0x5410); *reinterpret_cast<uint32_t*>(d1 + 16384) = __byte_perm(b0.y, b1.y, 0x5410);
        *reinterpret_cast<uint32_t*>(d0 + 24576) = __byte_perm(a0.y, a1.y, 0x7632); *reinterpret_cast<uint32_t*>(d1 + 24576) = __byte_perm(b0.y, b1.y, 0x7632);
      }
    }
    TL(5);
    fence_async();
    bar_sync_n(BAR_SETUP0, 384);
    if (wg == 2) {
      bar_arrive_n(BAR_TOK, 256);
      const int k = tid - 256;
      if (k < 96) {
        uint4 v[12];
#pragma unroll
        for (int c = 0; c < 12; c++) v[c] = __ldg(reinterpret_cast<const uint4*>(wo + k * 96) + c);
        float sum = 0.f;
#pragma unroll
        for (int c = 0; c < 12; c++)
          sum += (bf_lo(v[c].x) + bf_hi(v[c].x)) + (bf_lo(v[c].y) + bf_hi(v[c].y)) + (bf_lo(v[c].z) + bf_hi(v[c].z)) + (bf_lo(v[c].w) + bf_hi(v[c].w));
        const float mu = sum * (1.f / 96.f);
        auto cen = [&](uint32_t u) { return pack_bf16(bf_lo(u) - mu, bf_hi(u) - mu); };
        uint8_t* dst = smem + SM_WO + (k >> 3) * 128 + (k & 7) * 16;
#pragma unroll
        for (int j = 0; j < 3; j++) {
          *reinterpret_cast<uint4*>(dst + (4 * j + 0) * 1536) = make_uint4(cen(v[4 * j].x), cen(v[4 * j + 1].x), cen(v[4 * j + 2].x), cen(v[4 * j + 3].x));
          *reinterpret_cast<uint4*>(dst + (4 * j + 1) * 1536) = make_uint4(cen(v[4 * j].y), cen(v[4 * j + 1].y), cen(v[4 * j + 2].y), cen(v[4 * j + 3].y));
          *reinterpret_cast<uint4*>(dst + (4 * j + 2) * 1536) = make_uint4(cen(v[4 * j].z), cen(v[4 * j + 1].z), cen(v[4 * j + 2].z), cen(v[4 * j + 3].z));
          *reinterpret_cast<uint4*>(dst + (4 * j + 3) * 1536) = make_uint4(cen(v[4 * j].w), cen(v[4 * j + 1].w), cen(v[4 * j + 2].w), cen(v[4 * j + 3].w));
        }
      }
      fence_async();
      bar_arrive_n(BAR_WO, 256);
      bar_arrive_n(BAR_WO + 1, 256);
    }
  }
  load_mask(win);
  TL(1);
  mbar_wait(sb + SM_BAR, 0);
  TL(2);

  const uint32_t k_dst = wgb + WG_K + (lane >> 4) * 7168 + warp * 256 + (lane & 15) * 16;
  const uint32_t eb_base = sb + SM_EB + t16;
  const uint32_t out_off = ((lane >> 4) * IMG + ((lane >> 2) & 3)) * PIXB + (lane & 3) * 16;
  const int tok_next = BAR_TOK + (wg == 2 ? 0 : wg + 1);
  constexpr uint32_t EPS8 = 0x2A0D2A0Du;
  uint32_t xphase = 0;
  float kk[48], qq[48];
  mbar_wait(bar_x, 0);
  wg_fence();
  issue_proj(kk, mk_desc(WG_X, 16, 512, 2) + (wgb >> 4), mk_desc(sb + SM_W + 3 * 6144, 6144, 512, 2)); wg_commit();
  issue_proj(qq, mk_desc(WG_X, 16, 512, 2) + (wgb >> 4), mk_desc(sb + SM_W, 6144, 512, 2)); wg_commit();

  while (true) {
    const bool more = slot + stride < NWIN;
    const int nxt = more ? slot_window(slot + stride, G) : win;
    const uint32_t z0 = slot >> 20, zw = z0 + (wgb >> 4);
    const uint64_t dX = mk_desc(WG_X, 16, 512, 2) + zw, dK = mk_desc(WG_K, 1024, 128, 0) + zw, dV = mk_desc(WG_V, 128, 1024, 0) + zw;
    const uint64_t dW = mk_desc(sb + SM_W, 6144, 512, 2) + z0, dWo = mk_desc(sb + SM_WO, 128, 1536, 0) + z0;
    const uint64_t dSel = mk_desc(sb + SM_SEL, 128, 256, 0) + z0;
    TL(0);
    const uint32_t mword = (mw[0].x | mw[0].y | mw[0].z | mw[0].w | mw[1].x | mw[1].y | mw[1].z | mw[1].w) |
                           (mw[2].x | mw[2].y | mw[2].z | mw[2].w | mw[3].x | mw[3].y | mw[3].z | mw[3].w);
    const bool masked = bar_wg_or(BAR_OR + wg, (mword & 0x7FFF7FFFu) != 0u);

    uint32_t qa[24];
    {
      uint32_t ka[24], sq[8];
      float k01[4], k23[4], q01[4], q23[4], vv[48];
      wg_wait<1>(); fence_regs(kk);
      TL(1);
      pack_sumsq(kk, ka, sq, EPS8);
      wg_fence();
      wgmma_rs_n8_t0<0>(k01, sq[0], sq[1], sq[2], sq[3], dSel);
      wgmma_rs_n8_t0<0>(k23, sq[4], sq[5], sq[6], sq[7], dSel);
      wg_commit();
      issue_proj(vv, dX, dW + 6 * 384); wg_commit();
      TL(2);
      wg_wait<2>(); fence_regs(qq);
      uint32_t sr[8];
      pack_sumsq(qq, qa, sr, EPS8);
      wg_fence();
      wgmma_rs_n8_t0<0>(q01, sr[0], sr[1], sr[2], sr[3], dSel);
      wgmma_rs_n8_t0<0>(q23, sr[4], sr[5], sr[6], sr[7], dSel);
      wg_commit();
      TL(3);
      wg_wait<2>(); fence_regs(k01); fence_regs(k23);
      const float rk[8] = {rsq(k01[0]), rsq(k01[2]), rsq(k01[1]), rsq(k01[3]), rsq(k23[0]), rsq(k23[2]), rsq(k23[1]), rsq(k23[3])};
      scale_heads(ka, rk);
#pragma unroll
      for (int i = 0; i < 6; i++) stsm4(k_dst + (i + (i >= 3)) * 1024, ka[2 * i], ka[2 * i + 1], ka[12 + 2 * i], ka[12 + 2 * i + 1]);
      const uint4 qs = lds128(sb + SM_MISC);
      TL(4);
      wg_wait<0>(); fence_regs(vv); fence_regs(q01); fence_regs(q23);
      TL(5);
#pragma unroll
      for (int i = 0; i < 6; i++)
        stsm4(k_dst + (WG_V - WG_K) + (i + (i >= 3)) * 1024, pack_bf16(vv[4 * i], vv[4 * i + 1]), pack_bf16(vv[4 * i + 2], vv[4 * i + 3]),
              pack_bf16(vv[24 + 4 * i], vv[24 + 4 * i + 1]), pack_bf16(vv[24 + 4 * i + 2], vv[24 + 4 * i + 3]));
      fence_async();
      const float s0 = __uint_as_float(qs.x), s1 = __uint_as_float(qs.y), s2 = __uint_as_float(qs.z), s3 = __uint_as_float(qs.w);
      const float rq[8] = {rsq(q01[0]) * s0, rsq(q01[2]) * s0, rsq(q01[1]) * s1, rsq(q01[3]) * s1,
                           rsq(q23[0]) * s2, rsq(q23[2]) * s2, rsq(q23[1]) * s3, rsq(q23[3]) * s3};
      scale_heads(qa, rq);
    }
    bar_sync_n(BAR_KV + wg, 128);
    TL(6);
    if (warp == 0 && more) {
      if (elect_one()) { load_x(nxt); prefetch_l2(mask_ptr(nxt), 8192); }
      __syncwarp();
    }

    const bool pass_token = (wg == 2 ? slot + stride - 2 * G : slot + G) < NWIN;
    uint32_t of[24];
    if (!masked && slow_heads == 0) {
      float sA[32], sB[32], oA[16], oB[16];
      uint32_t pA[16], pB[16];
      wg_fence();
      issue_s<0>(sA, qa, dK);
      issue_s<1>(sB, qa, dK); wg_commit();
      bar_sync_n(BAR_TOK + wg, 256);
      wg_wait<0>(); fence_regs(sA); fence_regs(sB);
      TL(7);
      softmax_fast(sA, pA, eb_base);
      wg_fence();
      issue_s<2>(sA, qa, dK); wg_commit();
      issue_pv<0>(oA, pA, dV); wg_commit();
      TL(8);
      softmax_fast(sB, pB, eb_base + 8192);
      wg_wait<1>(); fence_regs(sA);
      wg_fence();
      issue_s<3>(sB, qa, dK); wg_commit();
      issue_pv<1>(oB, pB, dV); wg_commit();
      TL(9);
      uint32_t pC[16], pD[16]; float oC[16], oD[16];
      softmax_fast(sA, pC, eb_base + 2 * 8192);
      if (pass_token) bar_arrive_n(tok_next, 256);
      wg_wait<1>(); fence_regs(sB); fence_regs(oA);
      wg_fence();
      issue_pv<2>(oC, pC, dV); wg_commit();
      TL(10);
      norm_o<0>(oA, of);
      softmax_fast(sB, pD, eb_base + 3 * 8192);
      wg_fence();
      issue_pv<3>(oD, pD, dV); wg_commit();
      wg_wait<1>(); fence_regs(oB); fence_regs(oC);
      norm_o<1>(oB, of + 6);
      norm_o<0>(oC, of + 12);
      wg_wait<0>(); fence_regs(oD);
      norm_o<1>(oD, of + 18);
    } else {
      uint32_t mk[16];
      const int g = lane >> 2, t = lane & 3;
      const char* mrow = mask_ptr(win) + (orig_tok(16 * warp + g) * 64 + (t >> 1) * 8 + (t & 1) * 2) * 2;
#pragma unroll
      for (int Gk = 0; Gk < 8; Gk++) {
        mk[2 * Gk] = masked ? *reinterpret_cast<const uint32_t*>(mrow + ((Gk & 3) * 16 + (Gk >> 2) * 4) * 2) : 0u;
        mk[2 * Gk + 1] = masked ? *reinterpret_cast<const uint32_t*>(mrow + (16 * 64 + (Gk & 3) * 16 + (Gk >> 2) * 4) * 2) : 0u;
      }
      bar_sync_n(BAR_TOK + wg, 256);
      if (pass_token) bar_arrive_n(tok_next, 256);
      const uint32_t tm = masked ? 0xFu : slow_heads;
#pragma unroll
      for (int i = 0; i < 24; i++) of[i] = 0;
#pragma unroll 1
      for (int h = 0; h < 4; h++) {
        float sc[32], o[16]; uint32_t p[16];
        TL(7 + h);
        const uint32_t po = (h * 3 + (h >> 1)) * 64;
        wg_fence(); issue_s<0>(sc, qa, dK + po); wg_commit();
        wg_wait<0>(); fence_regs(sc);
        if ((tm >> h) & 1) softmax_true_max(sc, p, eb_base + h * 8192, mk); else softmax_fast(sc, p, eb_base + h * 8192);
        wg_fence(); issue_pv<0>(o, p, dV + po); wg_commit();
#pragma unroll
        for (int i = 0; i < 20; i++) qa[i] = (h & 1) ? (i < 16 ? qa[i + 8] : 0u) : qa[i + 4];
#pragma unroll
        for (int i = 0; i < 18; i++) of[i] = of[i + 6];
        wg_wait<0>(); fence_regs(o);
        if (h & 1) norm_o<1>(o, of + 18); else norm_o<0>(o, of + 18);
      }
    }
    TL(11);

    if (slot < 2 * G) bar_sync_n(BAR_WO + wg, 256);
    float y[48];
    wg_fence();
#pragma unroll
    for (int s = 0; s < 6; s++) {
      if (s == 0) wgmma_rs_n96_t1<0>(y, of[0], of[1], of[2], of[3], dWo);
      else wgmma_rs_n96_t1<1>(y, of[4 * s], of[4 * s + 1], of[4 * s + 2], of[4 * s + 3], dWo + s * 16);
    }
    wg_commit();
    load_mask(nxt);
    char* optr;
    {
      const int wy = win >> 8, wx = win & 255;
      int py = wy * 8 + 4 + (warp & 1) * 4;  if (py >= IMG) py -= IMG;
      int px = wx * 8 + 4 + (warp >> 1) * 4; if (px >= IMG) px -= IMG;
      optr = reinterpret_cast<char*>(out) + ((uint32_t)(py * IMG + px) * PIXB + out_off);
    }
    if (more) { xphase ^= 1; mbar_wait(bar_x, xphase); }
    wg_wait<0>(); fence_regs(y);
    TL(12);
    uint32_t yb[24], sy[8];
    pack_sumsq(y, yb, sy, 0u);
    float var[4];
    wg_fence();
    wgmma_rs_n8_t0<0>(var, sy[0], sy[1], sy[2], sy[3], dV + 3 * 64);
    wgmma_rs_n8_t0<1>(var, sy[4], sy[5], sy[6], sy[7], dV + 3 * 64);
    wg_commit();
    issue_proj(kk, dX, dW + 3 * 384); wg_commit();
    issue_proj(qq, dX, dW); wg_commit();
    wg_wait<2>(); fence_regs(var);
    TL(13);
    const uint32_t nn = pack_bf16(rsq(fmaf(var[0], 1.f / 96.f, 1e-5f)), rsq(fmaf(var[2], 1.f / 96.f, 1e-5f)));
#pragma unroll
    for (int j = 0; j < 3; j++) {
      stg128(optr + j * 64, hmul2_b<0>(yb[8 * j], nn), hmul2_b<0>(yb[8 * j + 2], nn), hmul2_b<0>(yb[8 * j + 4], nn), hmul2_b<0>(yb[8 * j + 6], nn));
      stg128(optr + 2 * ROWB + j * 64, hmul2_b<1>(yb[8 * j + 1], nn), hmul2_b<1>(yb[8 * j + 3], nn), hmul2_b<1>(yb[8 * j + 5], nn), hmul2_b<1>(yb[8 * j + 7], nn));
    }
    TL(14);
    if (!more) break;
    win = nxt;
    slot += stride;
  }
  wg_wait<0>();
  TG(15);
}

typedef CUresult (*EncodeFn)(CUtensorMap*, CUtensorMapDataType, cuuint32_t, void*, const cuuint64_t*, const cuuint64_t*,
                             const cuuint32_t*, const cuuint32_t*, CUtensorMapInterleave, CUtensorMapSwizzle,
                             CUtensorMapL2promotion, CUtensorMapFloatOOBfill);

}

extern "C" void kernel_launch(void* const* d_in, const int* in_sizes, int n_in, void* d_out, int out_size) {
  static int sms = 0;
  static EncodeFn encode = nullptr;
  if (sms == 0) {
    int dev = 0;
    cudaGetDevice(&dev);
    cudaDeviceGetAttribute(&sms, cudaDevAttrMultiProcessorCount, dev);
    cudaFuncSetAttribute(swin_kernel, cudaFuncAttributeMaxDynamicSharedMemorySize, SM_TOTAL);
    cudaDriverEntryPointQueryResult qr;
    void* fn = nullptr;
    cudaGetDriverEntryPoint("cuTensorMapEncodeTiled", &fn, cudaEnableDefault, &qr);
    encode = (EncodeFn)fn;
  }
  CUtensorMap tm_x, tm_xq, tm_w;
  {
    cuuint64_t dims[5] = {32, 4, IMG, IMG / 4, 3};
    cuuint64_t strides[4] = {PIXB, ROWB, 4 * PIXB, 64};
    cuuint32_t es[5] = {1, 1, 1, 1, 1};
    cuuint32_t box[5] = {32, 4, 8, 2, 3}, boxq[5] = {32, 4, 4, 1, 1};
    encode(&tm_x, CU_TENSOR_MAP_DATA_TYPE_BFLOAT16, 5, d_in[0], dims, strides, box, es, CU_TENSOR_MAP_INTERLEAVE_NONE,
           CU_TENSOR_MAP_SWIZZLE_64B, CU_TENSOR_MAP_L2_PROMOTION_L2_128B, CU_TENSOR_MAP_FLOAT_OOB_FILL_NONE);
    encode(&tm_xq, CU_TENSOR_MAP_DATA_TYPE_BFLOAT16, 5, d_in[0], dims, strides, boxq, es, CU_TENSOR_MAP_INTERLEAVE_NONE,
           CU_TENSOR_MAP_SWIZZLE_64B, CU_TENSOR_MAP_L2_PROMOTION_L2_128B, CU_TENSOR_MAP_FLOAT_OOB_FILL_NONE);
    cuuint64_t wd[3] = {32, 96, 9};
    cuuint64_t ws[2] = {576, 64};
    cuuint32_t wb[3] = {32, 96, 9};
    encode(&tm_w, CU_TENSOR_MAP_DATA_TYPE_BFLOAT16, 3, d_in[1], wd, ws, wb, es, CU_TENSOR_MAP_INTERLEAVE_NONE,
           CU_TENSOR_MAP_SWIZZLE_64B, CU_TENSOR_MAP_L2_PROMOTION_L2_128B, CU_TENSOR_MAP_FLOAT_OOB_FILL_NONE);
  }
  swin_kernel<<<sms, 384, SM_TOTAL>>>(
      tm_x, tm_xq, tm_w, (const __nv_bfloat16*)d_in[2], (const __nv_bfloat16*)d_in[3],
      (const __nv_bfloat16*)d_in[4], (const __nv_bfloat16*)d_in[5], (const __nv_bfloat16*)d_in[6], (const int*)d_in[7],
      (const __nv_bfloat16*)d_in[8], (__nv_bfloat16*)d_out);
}
```

```cpp
#include <cuda_runtime.h>
#include <cuda.h>
#include <cuda_bf16.h>
#include <stdint.h>

#define TOKEN 3
namespace {

constexpr int IMG   = 384;
constexpr int NWX   = 48;
constexpr int NWIN  = NWX * NWX;
constexpr int PIXB  = 192;
constexpr int ROWB  = IMG * PIXB;
constexpr float LOG2E = 1.4426950408889634f;

constexpr int SM_W    = 0;
constexpr int SM_WO   = SM_W + 9 * 6144;
constexpr int SM_EB   = SM_WO + 12 * 1536;
constexpr int SM_WG   = SM_EB + 32768;
constexpr int WG_X    = 0;
constexpr int WG_K    = 12288;
constexpr int WG_V    = WG_K + 14336;
constexpr int WG_SZ   = WG_V + 14336;
constexpr int SM_TAB  = SM_WG + 2 * WG_SZ + WG_V + 4096;
constexpr int SM_SEL  = SM_WG + 3 * WG_SZ;
constexpr int SM_MISC = SM_SEL + 256;
constexpr int SM_BAR  = SM_MISC + 16;
constexpr int SM_TOTAL = SM_BAR + 64;

template <int SD> __device__ __forceinline__ void wgmma_ss_n96_t1(float (&d)[48], uint64_t da, uint64_t db) {
  if constexpr (SD) {
    asm volatile("{\n.reg .pred p;\nsetp.ne.b32 p, 1, 0;\n"
      "wgmma.mma_async.sync.aligned.m64n96k16.f32.bf16.bf16 {%0, %1, %2, %3, %4, %5, %6, %7, %8, %9, %10, %11, %12, %13, %14, %15, %16, %17, %18, %19, %20, %21, %22, %23, %24, %25, %26, %27, %28, %29, %30, %31, %32, %33, %34, %35, %36, %37, %38, %39, %40, %41, %42, %43, %44, %45, %46, %47}, %48, %49, p, 1, 1, 0, 1;\n}\n"
      : "+f"(d[0]), "+f"(d[1]), "+f"(d[2]), "+f"(d[3]), "+f"(d[4]), "+f"(d[5]), "+f"(d[6]), "+f"(d[7]), "+f"(d[8]), "+f"(d[9]), "+f"(d[10]), "+f"(d[11]), "+f"(d[12]), "+f"(d[13]), "+f"(d[14]), "+f"(d[15]), "+f"(d[16]), "+f"(d[17]), "+f"(d[18]), "+f"(d[19]), "+f"(d[20]), "+f"(d[21]), "+f"(d[22]), "+f"(d[23]), "+f"(d[24]), "+f"(d[25]), "+f"(d[26]), "+f"(d[27]), "+f"(d[28]), "+f"(d[29]), "+f"(d[30]), "+f"(d[31]), "+f"(d[32]), "+f"(d[33]), "+f"(d[34]), "+f"(d[35]), "+f"(d[36]), "+f"(d[37]), "+f"(d[38]), "+f"(d[39]), "+f"(d[40]), "+f"(d[41]), "+f"(d[42]), "+f"(d[43]), "+f"(d[44]), "+f"(d[45]), "+f"(d[46]), "+f"(d[47])
      : "l"(da), "l"(db));
  } else {
    asm volatile("{\n.reg .pred p;\nsetp.ne.b32 p, 0, 0;\n"
      "wgmma.mma_async.sync.aligned.m64n96k16.f32.bf16.bf16 {%0, %1, %2, %3, %4, %5, %6, %7, %8, %9, %10, %11, %12, %13, %14, %15, %16, %17, %18, %19, %20, %21, %22, %23, %24, %25, %26, %27, %28, %29, %30, %31, %32, %33, %34, %35, %36, %37, %38, %39, %40, %41, %42, %43, %44, %45, %46, %47}, %48, %49, p, 1, 1, 0, 1;\n}\n"
      : "=f"(d[0]), "=f"(d[1]), "=f"(d[2]), "=f"(d[3]), "=f"(d[4]), "=f"(d[5]), "=f"(d[6]), "=f"(d[7]), "=f"(d[8]), "=f"(d[9]), "=f"(d[10]), "=f"(d[11]), "=f"(d[12]), "=f"(d[13]), "=f"(d[14]), "=f"(d[15]), "=f"(d[16]), "=f"(d[17]), "=f"(d[18]), "=f"(d[19]), "=f"(d[20]), "=f"(d[21]), "=f"(d[22]), "=f"(d[23]), "=f"(d[24]), "=f"(d[25]), "=f"(d[26]), "=f"(d[27]), "=f"(d[28]), "=f"(d[29]), "=f"(d[30]), "=f"(d[31]), "=f"(d[32]), "=f"(d[33]), "=f"(d[34]), "=f"(d[35]), "=f"(d[36]), "=f"(d[37]), "=f"(d[38]), "=f"(d[39]), "=f"(d[40]), "=f"(d[41]), "=f"(d[42]), "=f"(d[43]), "=f"(d[44]), "=f"(d[45]), "=f"(d[46]), "=f"(d[47])
      : "l"(da), "l"(db));
  }
}
template <int SD> __device__ __forceinline__ void wgmma_rs_n96_t1(float (&d)[48], uint32_t a0, uint32_t a1, uint32_t a2, uint32_t a3, uint64_t db) {
  if constexpr (SD) {
    asm volatile("{\n.reg .pred p;\nsetp.ne.b32 p, 1, 0;\n"
      "wgmma.mma_async.sync.aligned.m64n96k16.f32.bf16.bf16 {%0, %1, %2, %3, %4, %5, %6, %7, %8, %9, %10, %11, %12, %13, %14, %15, %16, %17, %18, %19, %20, %21, %22, %23, %24, %25, %26, %27, %28, %29, %30, %31, %32, %33, %34, %35, %36, %37, %38, %39, %40, %41, %42, %43, %44, %45, %46, %47}, {%48, %49, %50, %51}, %52, p, 1, 1, 1;\n}\n"
      : "+f"(d[0]), "+f"(d[1]), "+f"(d[2]), "+f"(d[3]), "+f"(d[4]), "+f"(d[5]), "+f"(d[6]), "+f"(d[7]), "+f"(d[8]), "+f"(d[9]), "+f"(d[10]), "+f"(d[11]), "+f"(d[12]), "+f"(d[13]), "+f"(d[14]), "+f"(d[15]), "+f"(d[16]), "+f"(d[17]), "+f"(d[18]), "+f"(d[19]), "+f"(d[20]), "+f"(d[21]), "+f"(d[22]), "+f"(d[23]), "+f"(d[24]), "+f"(d[25]), "+f"(d[26]), "+f"(d[27]), "+f"(d[28]), "+f"(d[29]), "+f"(d[30]), "+f"(d[31]), "+f"(d[32]), "+f"(d[33]), "+f"(d[34]), "+f"(d[35]), "+f"(d[36]), "+f"(d[37]), "+f"(d[38]), "+f"(d[39]), "+f"(d[40]), "+f"(d[41]), "+f"(d[42]), "+f"(d[43]), "+f"(d[44]), "+f"(d[45]), "+f"(d[46]), "+f"(d[47])
      : "r"(a0), "r"(a1), "r"(a2), "r"(a3), "l"(db));
  } else {
    asm volatile("{\n.reg .pred p;\nsetp.ne.b32 p, 0, 0;\n"
      "wgmma.mma_async.sync.aligned.m64n96k16.f32.bf16.bf16 {%0, %1, %2, %3, %4, %5, %6, %7, %8, %9, %10, %11, %12, %13, %14, %15, %16, %17, %18, %19, %20, %21, %22, %23, %24, %25, %26, %27, %28, %29, %30, %31, %32, %33, %34, %35, %36, %37, %38, %39, %40, %41, %42, %43, %44, %45, %46, %47}, {%48, %49, %50, %51}, %52, p, 1, 1, 1;\n}\n"
      : "=f"(d[0]), "=f"(d[1]), "=f"(d[2]), "=f"(d[3]), "=f"(d[4]), "=f"(d[5]), "=f"(d[6]), "=f"(d[7]), "=f"(d[8]), "=f"(d[9]), "=f"(d[10]), "=f"(d[11]), "=f"(d[12]), "=f"(d[13]), "=f"(d[14]), "=f"(d[15]), "=f"(d[16]), "=f"(d[17]), "=f"(d[18]), "=f"(d[19]), "=f"(d[20]), "=f"(d[21]), "=f"(d[22]), "=f"(d[23]), "=f"(d[24]), "=f"(d[25]), "=f"(d[26]), "=f"(d[27]), "=f"(d[28]), "=f"(d[29]), "=f"(d[30]), "=f"(d[31]), "=f"(d[32]), "=f"(d[33]), "=f"(d[34]), "=f"(d[35]), "=f"(d[36]), "=f"(d[37]), "=f"(d[38]), "=f"(d[39]), "=f"(d[40]), "=f"(d[41]), "=f"(d[42]), "=f"(d[43]), "=f"(d[44]), "=f"(d[45]), "=f"(d[46]), "=f"(d[47])
      : "r"(a0), "r"(a1), "r"(a2), "r"(a3), "l"(db));
  }
}
template <int SD> __device__ __forceinline__ void wgmma_rs_n64_t0(float (&d)[32], uint32_t a0, uint32_t a1, uint32_t a2, uint32_t a3, uint64_t db) {
  if constexpr (SD) {
    asm volatile("{\n.reg .pred p;\nsetp.ne.b32 p, 1, 0;\n"
      "wgmma.mma_async.sync.aligned.m64n64k16.f32.bf16.bf16 {%0, %1, %2, %3, %4, %5, %6, %7, %8, %9, %10, %11, %12, %13, %14, %15, %16, %17, %18, %19, %20, %21, %22, %23, %24, %25, %26, %27, %28, %29, %30, %31}, {%32, %33, %34, %35}, %36, p, 1, 1, 0;\n}\n"
      : "+f"(d[0]), "+f"(d[1]), "+f"(d[2]), "+f"(d[3]), "+f"(d[4]), "+f"(d[5]), "+f"(d[6]), "+f"(d[7]), "+f"(d[8]), "+f"(d[9]), "+f"(d[10]), "+f"(d[11]), "+f"(d[12]), "+f"(d[13]), "+f"(d[14]), "+f"(d[15]), "+f"(d[16]), "+f"(d[17]), "+f"(d[18]), "+f"(d[19]), "+f"(d[20]), "+f"(d[21]), "+f"(d[22]), "+f"(d[23]), "+f"(d[24]), "+f"(d[25]), "+f"(d[26]), "+f"(d[27]), "+f"(d[28]), "+f"(d[29]), "+f"(d[30]), "+f"(d[31])
      : "r"(a0), "r"(a1), "r"(a2), "r"(a3), "l"(db));
  } else {
    asm volatile("{\n.reg .pred p;\nsetp.ne.b32 p, 0, 0;\n"
      "wgmma.mma_async.sync.aligned.m64n64k16.f32.bf16.bf16 {%0, %1, %2, %3, %4, %5, %6, %7, %8, %9, %10, %11, %12, %13, %14, %15, %16, %17, %18, %19, %20, %21, %22, %23, %24, %25, %26, %27, %28, %29, %30, %31}, {%32, %33, %34, %35}, %36, p, 1, 1, 0;\n}\n"
      : "=f"(d[0]), "=f"(d[1]), "=f"(d[2]), "=f"(d[3]), "=f"(d[4]), "=f"(d[5]), "=f"(d[6]), "=f"(d[7]), "=f"(d[8]), "=f"(d[9]), "=f"(d[10]), "=f"(d[11]), "=f"(d[12]), "=f"(d[13]), "=f"(d[14]), "=f"(d[15]), "=f"(d[16]), "=f"(d[17]), "=f"(d[18]), "=f"(d[19]), "=f"(d[20]), "=f"(d[21]), "=f"(d[22]), "=f"(d[23]), "=f"(d[24]), "=f"(d[25]), "=f"(d[26]), "=f"(d[27]), "=f"(d[28]), "=f"(d[29]), "=f"(d[30]), "=f"(d[31])
      : "r"(a0), "r"(a1), "r"(a2), "r"(a3), "l"(db));
  }
}
template <int SD> __device__ __forceinline__ void wgmma_rs_n32_t1(float (&d)[16], uint32_t a0, uint32_t a1, uint32_t a2, uint32_t a3, uint64_t db) {
  if constexpr (SD) {
    asm volatile("{\n.reg .pred p;\nsetp.ne.b32 p, 1, 0;\n"
      "wgmma.mma_async.sync.aligned.m64n32k16.f32.bf16.bf16 {%0, %1, %2, %3, %4, %5, %6, %7, %8, %9, %10, %11, %12, %13, %14, %15}, {%16, %17, %18, %19}, %20, p, 1, 1, 1;\n}\n"
      : "+f"(d[0]), "+f"(d[1]), "+f"(d[2]), "+f"(d[3]), "+f"(d[4]), "+f"(d[5]), "+f"(d[6]), "+f"(d[7]), "+f"(d[8]), "+f"(d[9]), "+f"(d[10]), "+f"(d[11]), "+f"(d[12]), "+f"(d[13]), "+f"(d[14]), "+f"(d[15])
      : "r"(a0), "r"(a1), "r"(a2), "r"(a3), "l"(db));
  } else {
    asm volatile("{\n.reg .pred p;\nsetp.ne.b32 p, 0, 0;\n"
      "wgmma.mma_async.sync.aligned.m64n32k16.f32.bf16.bf16 {%0, %1, %2, %3, %4, %5, %6, %7, %8, %9, %10, %11, %12, %13, %14, %15}, {%16, %17, %18, %19}, %20, p, 1, 1, 1;\n}\n"
      : "=f"(d[0]), "=f"(d[1]), "=f"(d[2]), "=f"(d[3]), "=f"(d[4]), "=f"(d[5]), "=f"(d[6]), "=f"(d[7]), "=f"(d[8]), "=f"(d[9]), "=f"(d[10]), "=f"(d[11]), "=f"(d[12]), "=f"(d[13]), "=f"(d[14]), "=f"(d[15])
      : "r"(a0), "r"(a1), "r"(a2), "r"(a3), "l"(db));
  }
}
template <int SD> __device__ __forceinline__ void wgmma_rs_n8_t0(float (&d)[4], uint32_t a0, uint32_t a1, uint32_t a2, uint32_t a3, uint64_t db) {
  if constexpr (SD) {
    asm volatile("{\n.reg .pred p;\nsetp.ne.b32 p, 1, 0;\n"
      "wgmma.mma_async.sync.aligned.m64n8k16.f32.bf16.bf16 {%0, %1, %2, %3}, {%4, %5, %6, %7}, %8, p, 1, 1, 0;\n}\n"
      : "+f"(d[0]), "+f"(d[1]), "+f"(d[2]), "+f"(d[3])
      : "r"(a0), "r"(a1), "r"(a2), "r"(a3), "l"(db));
  } else {
    asm volatile("{\n.reg .pred p;\nsetp.ne.b32 p, 0, 0;\n"
      "wgmma.mma_async.sync.aligned.m64n8k16.f32.bf16.bf16 {%0, %1, %2, %3}, {%4, %5, %6, %7}, %8, p, 1, 1, 0;\n}\n"
      : "=f"(d[0]), "=f"(d[1]), "=f"(d[2]), "=f"(d[3])
      : "r"(a0), "r"(a1), "r"(a2), "r"(a3), "l"(db));
  }
}

__device__ __forceinline__ void wg_fence()  { asm volatile("wgmma.fence.sync.aligned;" ::: "memory"); }
__device__ __forceinline__ void wg_commit() { asm volatile("wgmma.commit_group.sync.aligned;" ::: "memory"); }
template <int N> __device__ __forceinline__ void wg_wait() { asm volatile("wgmma.wait_group.sync.aligned %0;" :: "n"(N) : "memory"); }
template <int N> __device__ __forceinline__ void fence_regs(float (&d)[N]) {
#pragma unroll
  for (int i = 0; i < N; i++) asm volatile("" : "+f"(d[i]) :: "memory");
}
__device__ __forceinline__ constexpr uint64_t mk_desc(uint32_t addr, uint32_t lbo, uint32_t sbo, uint32_t swz) {
  return (uint64_t)(addr >> 4) | ((uint64_t)(lbo >> 4) << 16) | ((uint64_t)(sbo >> 4) << 32) | ((uint64_t)swz << 62);
}
__device__ __forceinline__ uint32_t pack_bf16(float lo, float hi) {
  uint32_t r; asm("cvt.rn.bf16x2.f32 %0, %1, %2;" : "=r"(r) : "f"(hi), "f"(lo)); return r;
}
__device__ __forceinline__ uint32_t hmul2(uint32_t a, uint32_t b) {
  uint32_t r; asm("mul.rn.bf16x2 %0, %1, %2;" : "=r"(r) : "r"(a), "r"(b)); return r;
}
template <int HI> __device__ __forceinline__ uint32_t hmul2_b(uint32_t a, uint32_t b) {
  uint32_t r;
  if (HI) asm("{\n.reg .b16 l, h;\n.reg .b32 t;\nmov.b32 {l, h}, %2;\nmov.b32 t, {h, h};\nmul.rn.bf16x2 %0, %1, t;\n}\n" : "=r"(r) : "r"(a), "r"(b));
  else    asm("{\n.reg .b16 l, h;\n.reg .b32 t;\nmov.b32 {l, h}, %2;\nmov.b32 t, {l, l};\nmul.rn.bf16x2 %0, %1, t;\n}\n" : "=r"(r) : "r"(a), "r"(b));
  return r;
}
__device__ __forceinline__ uint32_t hfma2(uint32_t a, uint32_t b, uint32_t c) {
  uint32_t r; asm("fma.rn.bf16x2 %0, %1, %2, %3;" : "=r"(r) : "r"(a), "r"(b), "r"(c)); return r;
}
__device__ __forceinline__ float ex2(float x) { float r; asm("ex2.approx.ftz.f32 %0, %1;" : "=f"(r) : "f"(x)); return r; }
__device__ __forceinline__ float rsq(float x) { float r; asm("rsqrt.approx.ftz.f32 %0, %1;" : "=f"(r) : "f"(x)); return r; }
__device__ __forceinline__ float rcp(float x) { float r; asm("rcp.approx.ftz.f32 %0, %1;" : "=f"(r) : "f"(x)); return r; }
__device__ __forceinline__ void stsm4(uint32_t addr, uint32_t r0, uint32_t r1, uint32_t r2, uint32_t r3) {
  asm volatile("stmatrix.sync.aligned.m8n8.x4.shared.b16 [%0], {%1,%2,%3,%4};" :: "r"(addr), "r"(r0), "r"(r1), "r"(r2), "r"(r3) : "memory");
}
__device__ __forceinline__ void fence_async() { asm volatile("fence.proxy.async.shared::cta;" ::: "memory"); }
__device__ __forceinline__ void bar_sync_n(int id, int n) { asm volatile("bar.sync %0, %1;" :: "r"(id), "r"(n) : "memory"); }
__device__ __forceinline__ void bar_arrive_n(int id, int n) { asm volatile("bar.arrive %0, %1;" :: "r"(id), "r"(n) : "memory"); }
__device__ __forceinline__ bool bar_wg_or(int id, bool v) {
  uint32_t r;
  asm volatile("{\n.reg .pred p, q;\nsetp.ne.u32 q, %2, 0;\nbar.red.or.pred p, %1, 128, q;\nselp.u32 %0, 1, 0, p;\n}\n"
               : "=r"(r) : "r"(id), "r"((uint32_t)v) : "memory");
  return r != 0;
}
__device__ __forceinline__ void mbar_init(uint32_t bar, uint32_t cnt) { asm volatile("mbarrier.init.shared::cta.b64 [%0], %1;" :: "r"(bar), "r"(cnt) : "memory"); }
__device__ __forceinline__ void mbar_expect(uint32_t bar, uint32_t bytes) {
  asm volatile("mbarrier.arrive.expect_tx.shared::cta.b64 _, [%0], %1;" :: "r"(bar), "r"(bytes) : "memory");
}
__device__ __forceinline__ void mbar_arrive(uint32_t bar) { asm volatile("mbarrier.arrive.shared::cta.b64 _, [%0];" :: "r"(bar) : "memory"); }
__device__ __forceinline__ void mbar_wait(uint32_t bar, uint32_t parity) {
  asm volatile("{\n.reg .pred p;\n.reg .u32 n;\nmov.u32 n, 0;\n"
               "LW_%=:\nmbarrier.try_wait.parity.shared::cta.b64 p, [%0], %1;\n@p bra.uni LD_%=;\n"
               "add.u32 n, n, 1;\nsetp.lt.u32 p, n, 4194304;\n@p bra.uni LW_%=;\ntrap;\nLD_%=:\n}\n"
               :: "r"(bar), "r"(parity) : "memory");
}
__device__ __forceinline__ void tma5(uint32_t dst, const CUtensorMap* m, uint32_t bar, int c0, int c1, int c2, int c3, int c4) {
  asm volatile("cp.async.bulk.tensor.5d.shared::cluster.global.mbarrier::complete_tx::bytes [%0], [%1, {%3, %4, %5, %6, %7}], [%2];"
               :: "r"(dst), "l"(m), "r"(bar), "r"(c0), "r"(c1), "r"(c2), "r"(c3), "r"(c4) : "memory");
}
__device__ __forceinline__ void tma3(uint32_t dst, const CUtensorMap* m, uint32_t bar, int c0, int c1, int c2) {
  asm volatile("cp.async.bulk.tensor.3d.shared::cluster.global.mbarrier::complete_tx::bytes [%0], [%1, {%3, %4, %5}], [%2];"
               :: "r"(dst), "l"(m), "r"(bar), "r"(c0), "r"(c1), "r"(c2) : "memory");
}
__device__ __forceinline__ uint4 lds128(uint32_t addr) {
  uint4 v; asm volatile("ld.shared.v4.u32 {%0,%1,%2,%3}, [%4];" : "=r"(v.x), "=r"(v.y), "=r"(v.z), "=r"(v.w) : "r"(addr)); return v;
}
__device__ __forceinline__ uint4 ldg128_stream(const void* p) {
  uint4 v; asm volatile("ld.global.nc.L1::no_allocate.v4.u32 {%0,%1,%2,%3}, [%4];" : "=r"(v.x), "=r"(v.y), "=r"(v.z), "=r"(v.w) : "l"(p)); return v;
}
__device__ __forceinline__ void stg128(void* p, uint32_t a, uint32_t b, uint32_t c, uint32_t d) {
  asm volatile("st.global.v4.u32 [%0], {%1,%2,%3,%4};" :: "l"(p), "r"(a), "r"(b), "r"(c), "r"(d) : "memory");
}
__device__ __forceinline__ void prefetch_l2(const void* p, uint32_t bytes) {
  asm volatile("cp.async.bulk.prefetch.L2.global [%0], %1;" :: "l"(p), "r"(bytes) : "memory");
}
__device__ __forceinline__ bool elect_one() {
  uint32_t r; asm volatile("{\n.reg .pred p;\nelect.sync _|p, 0xffffffff;\nselp.u32 %0, 1, 0, p;\n}\n" : "=r"(r)); return r != 0;
}
__device__ __forceinline__ float bf_lo(uint32_t u) { return __uint_as_float(u << 16); }
__device__ __forceinline__ float bf_hi(uint32_t u) { return __uint_as_float(u & 0xFFFF0000u); }
__device__ __forceinline__ float rbf(float x) { return bf_lo(pack_bf16(x, 0.f)); }
__device__ __forceinline__ int orig_tok(int r) { return ((r & 31) >> 2) * 8 + (r >> 5) * 4 + (r & 3); }

__device__ __forceinline__ int slot_window(int s, bool g132) {
  constexpr int A0 = 396 + 60, A1 = A0 + 72, B0 = 3 * 396 + 132 + 60, B1 = B0 + 23;
  const int i = s - (s >= B1 ? 95 : s >= A1 ? 72 : 0);
  const int k = s >= B0 ? s - B0 + 72 : s - A0;
  const bool border = (s >= A0 && s < A1) || (s >= B0 && s < B1);
  const int iy = (i * 2789) >> 17, sy = (s * 2731) >> 17;
  const int wa = border ? (k < 48 ? (47 << 8 | k) : ((k - 48) << 8 | 47)) : (iy << 8 | (i - iy * 47));
  return g132 ? wa : (sy << 8 | (s - sy * 48));
}

#define EB_WORD(e, j, a) ((((a) ^ ((j) & 1)) == 0) ? (e).x : (((a) ^ ((j) & 1)) == 1) ? (e).y : (((a) ^ ((j) & 1)) == 2) ? (e).z : (e).w)

__device__ __forceinline__ void load_eb(uint32_t (&e)[16], uint32_t eb_addr) {
#pragma unroll
  for (int j = 0; j < 4; j++) {
    const uint4 v = lds128(eb_addr + j * 2048);
#pragma unroll
    for (int a = 0; a < 4; a++) e[4 * j + a] = EB_WORD(v, j, a);
  }
}
__device__ __forceinline__ void softmax_fast(const float (&s)[32], uint32_t (&p)[16]) {
#pragma unroll
  for (int i = 0; i < 16; i++) p[i] = hmul2(pack_bf16(ex2(s[2 * i]), ex2(s[2 * i + 1])), p[i]);
}
__device__ __forceinline__ uint32_t hmax2(uint32_t a, uint32_t b) {
  uint32_t r; asm("max.bf16x2 %0, %1, %2;" : "=r"(r) : "r"(a), "r"(b)); return r;
}
__device__ __forceinline__ uint32_t hmax2_nan(uint32_t a, uint32_t b) {
  uint32_t r; asm("max.NaN.bf16x2 %0, %1, %2;" : "=r"(r) : "r"(a), "r"(b)); return r;
}
__device__ __forceinline__ float quad_max(float m) {
  m = fmaxf(m, __shfl_xor_sync(0xffffffffu, m, 1));
  return fmaxf(m, __shfl_xor_sync(0xffffffffu, m, 2));
}
__device__ __forceinline__ void softmax_true_max(float (&s)[32], uint32_t (&p)[16], const uint32_t (&mk)[16]) {
#pragma unroll
  for (int i = 0; i < 16; i++) {
    s[2 * i] = fmaf(bf_lo(mk[i]), LOG2E, s[2 * i]); s[2 * i + 1] = fmaf(bf_hi(mk[i]), LOG2E, s[2 * i + 1]);
  }
  float m0 = s[0], m1 = s[2];
#pragma unroll
  for (int g = 0; g < 8; g++) {
    m0 = fmaxf(m0, fmaxf(s[4 * g + 0], s[4 * g + 1]));
    m1 = fmaxf(m1, fmaxf(s[4 * g + 2], s[4 * g + 3]));
  }
  m0 = quad_max(m0); m1 = quad_max(m1);
  uint32_t n0 = 0, n1 = 0;
#pragma unroll
  for (int g = 0; g < 8; g++) {
    p[2 * g + 0] = hmul2(pack_bf16(ex2(s[4 * g + 0] - m0), ex2(s[4 * g + 1] - m0)), p[2 * g + 0]);
    p[2 * g + 1] = hmul2(pack_bf16(ex2(s[4 * g + 2] - m1), ex2(s[4 * g + 3] - m1)), p[2 * g + 1]);
    n0 = hmax2(n0, p[2 * g]); n1 = hmax2(n1, p[2 * g + 1]);
  }
  const uint32_t r = pack_bf16(rcp(quad_max(fmaxf(bf_lo(n0), bf_hi(n0)))), rcp(quad_max(fmaxf(bf_lo(n1), bf_hi(n1)))));
#pragma unroll
  for (int g = 0; g < 8; g++) { p[2 * g] = hmul2_b<0>(p[2 * g], r); p[2 * g + 1] = hmul2_b<1>(p[2 * g + 1], r); }
}
template <int H> __device__ __forceinline__ void issue_s(float (&s)[32], const uint32_t (&q)[24], uint64_t dK) {
  constexpr int Q0 = (H == 0 ? 0 : H == 1 ? 4 : H == 2 ? 12 : 16), P0 = (H == 0 ? 0 : H == 1 ? 3 : H == 2 ? 7 : 10);
  wgmma_rs_n64_t0<0>(s, q[Q0], q[Q0 + 1], q[Q0 + 2], q[Q0 + 3], dK + P0 * 64);
  wgmma_rs_n64_t0<1>(s, q[Q0 + 4], q[Q0 + 5], q[Q0 + 6], q[Q0 + 7], dK + P0 * 64 + 128);
}
template <int H> __device__ __forceinline__ void issue_pv(float (&o)[16], const uint32_t (&p)[16], uint64_t dV) {
  constexpr int P0 = (H == 0 ? 0 : H == 1 ? 3 : H == 2 ? 7 : 10);
  wgmma_rs_n32_t1<0>(o, p[0], p[1], p[2], p[3], dV + P0 * 64);
  wgmma_rs_n32_t1<1>(o, p[4], p[5], p[6], p[7], dV + P0 * 64 + 16);
  wgmma_rs_n32_t1<1>(o, p[8], p[9], p[10], p[11], dV + P0 * 64 + 32);
  wgmma_rs_n32_t1<1>(o, p[12], p[13], p[14], p[15], dV + P0 * 64 + 48);
}
__device__ __forceinline__ void issue_proj(float (&d)[48], uint64_t dX, uint64_t dW) {
#pragma unroll
  for (int s = 0; s < 6; s++) {
    const uint64_t a = dX + (s >> 1) * 256 + (s & 1) * 2, b = dW + s * 64;
    if (s == 0) wgmma_ss_n96_t1<0>(d, a, b); else wgmma_ss_n96_t1<1>(d, a, b);
  }
}
__device__ __forceinline__ void pack_sumsq(const float (&a)[48], uint32_t (&f)[24], uint32_t (&sq)[8], uint32_t init) {
#pragma unroll
  for (int i = 0; i < 24; i++) f[i] = pack_bf16(a[2 * i], a[2 * i + 1]);
#pragma unroll
  for (int h = 0; h < 4; h++)
#pragma unroll
    for (int r = 0; r < 2; r++) {
      uint32_t u = f[6 * h + r], v = f[6 * h + 2 + r], w = f[6 * h + 4 + r];
      sq[2 * h + r] = hfma2(w, w, hfma2(v, v, hfma2(u, u, init)));
    }
}
__device__ __forceinline__ void scale_heads(uint32_t (&f)[24], const float (&r)[8]) {
#pragma unroll
  for (int h = 0; h < 4; h++) {
    const uint32_t p = pack_bf16(r[2 * h], r[2 * h + 1]);
#pragma unroll
    for (int c = 0; c < 3; c++) {
      f[6 * h + 2 * c] = hmul2_b<0>(f[6 * h + 2 * c], p);
      f[6 * h + 2 * c + 1] = hmul2_b<1>(f[6 * h + 2 * c + 1], p);
    }
  }
}
template <int ODD> __device__ __forceinline__ void norm_o(const float (&o)[16], uint32_t* of) {
  constexpr int SO = ODD ? 0 : 12, VO = ODD ? 4 : 0;
  const uint32_t p = pack_bf16(rcp(o[SO]), rcp(o[SO + 2]));
#pragma unroll
  for (int g = 0; g < 3; g++) {
    of[2 * g + 0] = hmul2_b<0>(pack_bf16(o[VO + 4 * g + 0], o[VO + 4 * g + 1]), p);
    of[2 * g + 1] = hmul2_b<1>(pack_bf16(o[VO + 4 * g + 2], o[VO + 4 * g + 3]), p);
  }
}

#define TL(i)
#define TG(i)

constexpr int BAR_KV = 1;
constexpr int BAR_AUX = 4;
constexpr int BAR_TOK = 7;
constexpr int BAR_SETUP0 = 10, BAR_TAB = 11, BAR_WO = 12;

__global__ void __launch_bounds__(384, 1)
swin_kernel(const __grid_constant__ CUtensorMap tm_x, const __grid_constant__ CUtensorMap tm_xq, const __grid_constant__ CUtensorMap tm_w,
            const __nv_bfloat16* __restrict__ wo,
            const __nv_bfloat16* __restrict__ logit_scale, const __nv_bfloat16* __restrict__ w1, const __nv_bfloat16* __restrict__ w2,
            const __nv_bfloat16* __restrict__ coords, const int* __restrict__ rel_idx, const __nv_bfloat16* __restrict__ mask,
            __nv_bfloat16* __restrict__ out) {
  extern __shared__ __align__(1024) uint8_t smem[];
  constexpr uint32_t sb = 1024;
  const int tid = threadIdx.x, lane = tid & 31;
  const int warp = __shfl_sync(0xffffffffu, (tid >> 5) & 3, 0), wg = __shfl_sync(0xffffffffu, tid >> 7, 0);
  const uint32_t t16 = (tid & 127) * 16;
  const int G = gridDim.x, stride = 3 * G;
  int slot = wg * G + blockIdx.x;
  const uint32_t wgb = sb + SM_WG + wg * WG_SZ;
  const uint32_t bar_x = sb + SM_BAR + 8 + 8 * wg;
  const char* mb = reinterpret_cast<const char*>(mask);
  TL(0); TG(14);

  auto load_x = [&](int w) {
    const int wy = w >> 8, wx = w & 255;
    mbar_expect(bar_x, 12288);
    if (wy != NWX - 1 && wx != NWX - 1) {
      tma5(wgb + WG_X, &tm_x, bar_x, 0, 0, wy * 8 + 4, wx * 2 + 1, 0);
    } else {
#pragma unroll 1
      for (int i = 0; i < 12; i++) {
        const int q = i & 3, c = i >> 2;
        int y = wy * 8 + 4 + (q & 1) * 4; if (y >= IMG) y -= IMG;
        int xq = wx * 2 + 1 + (q >> 1);   if (xq >= IMG / 4) xq -= IMG / 4;
        tma5(wgb + WG_X + i * 1024, &tm_xq, bar_x, 0, 0, y, xq, c);
      }
    }
  };
  auto mask_ptr = [&](int w) { return mb + (uint32_t)((w >> 8) * NWX + (w & 255)) * 8192u; };
  uint4 mw[4];
  auto load_mask = [&](int w) {
    const char* src = mask_ptr(w) + t16;
#pragma unroll
    for (int i = 0; i < 4; i++) mw[i] = ldg128_stream(src + i * 2048);
  };

  const bool g132 = G == 132;
  int win = slot_window(slot, g132);
  if (warp == 0 && elect_one()) {
    mbar_init(bar_x, 1);
    mbar_init(bar_x + 24, 4);
    if (wg == 0) mbar_init(sb + SM_BAR, 1);
    fence_async();
    if (wg == 0) { load_x(win); mbar_expect(sb + SM_BAR, 9 * 6144); tma3(sb + SM_W, &tm_w, sb + SM_BAR, 0, 0, 0); }
  }
  __syncwarp();
  if ((uint32_t)__cvta_generic_to_shared(smem) != sb) __trap();
  const uint2 lsw = __ldg(reinterpret_cast<const uint2*>(logit_scale));
  uint32_t cw = 0, wa[16], wb[32];
  int4 rid[4];
  if (wg != 0) {
    const int i = tid - 128;
    if (i < 225) cw = __ldg(reinterpret_cast<const uint32_t*>(coords) + i);
#pragma unroll
    for (int j = 0; j < 4; j++) *reinterpret_cast<uint4*>(wa + 4 * j) = __ldg(reinterpret_cast<const uint4*>(w1) + j);
#pragma unroll
    for (int j = 0; j < 8; j++) *reinterpret_cast<uint4*>(wb + 4 * j) = __ldg(reinterpret_cast<const uint4*>(w2) + j);
#pragma unroll
    for (int c = 0; c < 4; c++) rid[c] = __ldg(reinterpret_cast<const int4*>(rel_idx) + c * 256 + i);
  }
  {
    const int i = tid & 127;
    uint8_t* vt = smem + SM_WG + wg * WG_SZ + WG_V + (i < 64 ? 3 : 10) * 1024 + (i & 63) * 16;
    *reinterpret_cast<uint4*>(vt) = make_uint4(0x3F803F80u, 0x3F803F80u, 0x3F803F80u, 0x3F803F80u);
    *reinterpret_cast<uint4*>(vt - (WG_V - WG_K)) = make_uint4(0u, 0u, 0u, 0u);
    if (tid < 16) {
      const uint32_t v = (((tid >> 3) ^ tid) & 1) ? 0u : 0x3F803F80u;
      *reinterpret_cast<uint4*>(smem + SM_SEL + tid * 16) = make_uint4(v, v, v, v);
    }
  }
  float tau[4]; uint32_t slow_heads = 0;
  {
    const float ls[4] = {bf_lo(lsw.x), bf_hi(lsw.x), bf_lo(lsw.y), bf_hi(lsw.y)};
#pragma unroll
    for (int h = 0; h < 4; h++) {
      const float c = ls[h] < -100.f ? -100.f : (ls[h] > 4.59375f ? 4.59375f : ls[h]);
      tau[h] = rbf(ex2(c * LOG2E)) * LOG2E;
      if (!(tau[h] * 2.04f <= 80.f)) slow_heads |= 1u << h;
    }
    slow_heads = __shfl_sync(0xffffffffu, slow_heads, 0);
  }
  TL(3);
  if (wg == 0) {
    if (tid == 0) *reinterpret_cast<float4*>(smem + SM_MISC) = make_float4(tau[0], tau[1], tau[2], tau[3]);
    fence_async();
    bar_arrive_n(BAR_SETUP0, 384);
    bar_sync_n(BAR_AUX, 128);
  } else {
    const int i = tid - 128;
    if (wg == 1 && warp == 0 && slow_heads < 16 && elect_one()) load_x(win);
    __syncwarp();
    uint4 v[9];
    if (wg == 2) {
#pragma unroll
      for (int c = 0; c < 9; c++)
        v[c] = __ldg(reinterpret_cast<const uint4*>(wo + ((c / 3) * 32 + ((tid & 127) >> 2)) * 96) + (c % 3) * 4 + (lane & 3));
    }
    if (i < 225) {
      const float c0 = bf_lo(cw), c1 = bf_hi(cw);
      float z[4] = {0.f, 0.f, 0.f, 0.f};
#pragma unroll
      for (int j = 0; j < 16; j++) {
        const float u = (j & 1) ? bf_hi(wa[j >> 1]) : bf_lo(wa[j >> 1]), w = (j & 1) ? bf_hi(wa[8 + (j >> 1)]) : bf_lo(wa[8 + (j >> 1)]);
        float h = rbf(fmaf(c1, w, c0 * u));
        h = h > 0.f ? h : h * 0.f;
        z[0] = fmaf(h, bf_lo(wb[2 * j]), z[0]); z[1] = fmaf(h, bf_hi(wb[2 * j]), z[1]);
        z[2] = fmaf(h, bf_lo(wb[2 * j + 1]), z[2]); z[3] = fmaf(h, bf_hi(wb[2 * j + 1]), z[3]);
      }
      float e[4];
#pragma unroll
      for (int q = 0; q < 4; q++) {
        const float sh = ((slow_heads >> q) & 1) ? 0.f : -1.02f * tau[q];
        e[q] = ex2(fmaf(16.f * LOG2E, rbf(rcp(1.f + ex2(-LOG2E * rbf(z[q])))), sh));
      }
      *reinterpret_cast<uint2*>(smem + SM_TAB + 8 * i) = make_uint2(pack_bf16(e[0], e[1]), pack_bf16(e[2], e[3]));
    }
    TL(4);
    bar_sync_n(BAR_TAB, 256);
    if (wg == 2 && warp == 0 && elect_one()) load_x(win);
    __syncwarp();
    {
      const int y = (i & 15) >> 1, xh = i & 1, j = 2 * xh + (y >> 2);
      const int X = (i >> 4) & 7, Yl = (i >> 7) & 1;
      uint8_t* dst = smem + SM_EB + j * 2048 + ((X >> 2) * 64 + (Yl * 4 + (X & 3)) * 4 + 2 * (y & 1)) * 16 + ((y >> 1) & 1) * 8;
#pragma unroll
      for (int c = 0; c < 4; c++) {
        const uint2 e0 = *reinterpret_cast<const uint2*>(smem + SM_TAB + 8 * rid[c].x), e1 = *reinterpret_cast<const uint2*>(smem + SM_TAB + 8 * rid[c].y);
        const uint2 e2 = *reinterpret_cast<const uint2*>(smem + SM_TAB + 8 * rid[c].z), e3 = *reinterpret_cast<const uint2*>(smem + SM_TAB + 8 * rid[c].w);
        const uint2 a0 = xh ? e2 : e0, a1 = xh ? e3 : e1, b0 = xh ? e0 : e2, b1 = xh ? e1 : e3;
        uint8_t* d0 = dst + (c >> 1) * 512 + (((c & 1) ^ (j & 1)) * 4) + xh * 16;
        uint8_t* d1 = dst + (c >> 1) * 512 + (((c & 1) ^ (j & 1)) * 4) + (xh ^ 1) * 16;
        *reinterpret_cast<uint32_t*>(d0)         = __byte_perm(a0.x, a1.x, 0x5410); *reinterpret_cast<uint32_t*>(d1)         = __byte_perm(b0.x, b1.x, 0x5410);
        *reinterpret_cast<uint32_t*>(d0 + 8192)  = __byte_perm(a0.x, a1.x, 0x7632); *reinterpret_cast<uint32_t*>(d1 + 8192)  = __byte_perm(b0.x, b1.x, 0x7632);
        *reinterpret_cast<uint32_t*>(d0 + 16384) = __byte_perm(a0.y, a1.y, 0x5410); *reinterpret_cast<uint32_t*>(d1 + 16384) = __byte_perm(b0.y, b1.y, 0x5410);
        *reinterpret_cast<uint32_t*>(d0 + 24576) = __byte_perm(a0.y, a1.y, 0x7632); *reinterpret_cast<uint32_t*>(d1 + 24576) = __byte_perm(b0.y, b1.y, 0x7632);
      }
    }
    TL(5);
    fence_async();
    bar_sync_n(BAR_SETUP0, 384);
    if (wg == 2) {
      bar_arrive_n(BAR_TOK, 256);
#pragma unroll
      for (int r = 0; r < 3; r++) {
        float sum = 0.f;
#pragma unroll
        for (int c = 3 * r; c < 3 * r + 3; c++)
          sum += (bf_lo(v[c].x) + bf_hi(v[c].x)) + (bf_lo(v[c].y) + bf_hi(v[c].y)) + (bf_lo(v[c].z) + bf_hi(v[c].z)) + (bf_lo(v[c].w) + bf_hi(v[c].w));
        sum += __shfl_xor_sync(0xffffffffu, sum, 1);
        sum += __shfl_xor_sync(0xffffffffu, sum, 2);
        const float mu = sum * (1.f / 96.f);
        auto cen = [&](uint32_t u) { return pack_bf16(bf_lo(u) - mu, bf_hi(u) - mu); };
        uint8_t* dst = smem + SM_WO + (r * 4 + warp) * 128 + lane * 4;
#pragma unroll
        for (int j = 0; j < 3; j++) {
          *reinterpret_cast<uint32_t*>(dst + (4 * j + 0) * 1536) = cen(v[3 * r + j].x);
          *reinterpret_cast<uint32_t*>(dst + (4 * j + 1) * 1536) = cen(v[3 * r + j].y);
          *reinterpret_cast<uint32_t*>(dst + (4 * j + 2) * 1536) = cen(v[3 * r + j].z);
          *reinterpret_cast<uint32_t*>(dst + (4 * j + 3) * 1536) = cen(v[3 * r + j].w);
        }
      }
      fence_async();
      bar_arrive_n(BAR_WO, 256);
      bar_arrive_n(BAR_WO + 1, 256);
    }
  }
  TL(1);
  mbar_wait(bar_x, 0);
  if (warp == 0 && elect_one()) prefetch_l2(mask_ptr(win), 8192);
  __syncwarp();
  mbar_wait(sb + SM_BAR, 0);
  TL(2);

  const uint32_t k_dst = wgb + WG_K + (lane >> 4) * 7168 + warp * 256 + (lane & 15) * 16;
  const uint32_t eb_base = sb + SM_EB + t16;
  const uint32_t out_off = ((lane >> 4) * IMG + ((lane >> 2) & 3)) * PIXB + (lane & 3) * 16;
  const int tok_next = BAR_TOK + (wg == 2 ? 0 : wg + 1);
  constexpr uint32_t EPS8 = 0x2A0D2A0Du;
  uint32_t xphase = 0;
  float kk[48], qq[48];
  wg_fence();
  issue_proj(kk, mk_desc(WG_X, 16, 512, 2) + (wgb >> 4), mk_desc(sb + SM_W + 3 * 6144, 6144, 512, 2)); wg_commit();
  issue_proj(qq, mk_desc(WG_X, 16, 512, 2) + (wgb >> 4), mk_desc(sb + SM_W, 6144, 512, 2)); wg_commit();

  while (true) {
    const bool more = slot + stride < NWIN;
    const int nxt = slot_window(more ? slot + stride : slot, g132);
    const uint32_t z0 = slot >> 20, zw = z0 + (wgb >> 4);
    const uint64_t dX = mk_desc(WG_X, 16, 512, 2) + zw, dK = mk_desc(WG_K, 1024, 128, 0) + zw, dV = mk_desc(WG_V, 128, 1024, 0) + zw;
    const uint64_t dW = mk_desc(sb + SM_W, 6144, 512, 2) + z0, dWo = mk_desc(sb + SM_WO, 128, 1536, 0) + z0;
    const uint64_t dSel = mk_desc(sb + SM_SEL, 128, 256, 0) + z0;
    TL(0);
    uint32_t qa[24];
    {
      uint32_t ka[24], sq[8];
      float k01[4], k23[4], q01[4], q23[4], vv[48];
      const uint4 qs = lds128(sb + SM_MISC);
      wg_wait<1>(); fence_regs(kk);
      TL(1);
      pack_sumsq(kk, ka, sq, EPS8);
      wg_fence();
      wgmma_rs_n8_t0<0>(k01, sq[0], sq[1], sq[2], sq[3], dSel);
      wgmma_rs_n8_t0<0>(k23, sq[4], sq[5], sq[6], sq[7], dSel);
      wg_commit();
      issue_proj(vv, dX, dW + 6 * 384); wg_commit();
      TL(2);
      wg_wait<2>(); fence_regs(qq);
      uint32_t sr[8];
      pack_sumsq(qq, qa, sr, EPS8);
      wg_fence();
      wgmma_rs_n8_t0<0>(q01, sr[0], sr[1], sr[2], sr[3], dSel);
      wgmma_rs_n8_t0<0>(q23, sr[4], sr[5], sr[6], sr[7], dSel);
      wg_commit();
      load_mask(win);
      TL(3);
      wg_wait<2>(); fence_regs(k01); fence_regs(k23);
      const float rk[8] = {rsq(k01[0]), rsq(k01[2]), rsq(k01[1]), rsq(k01[3]), rsq(k23[0]), rsq(k23[2]), rsq(k23[1]), rsq(k23[3])};
      scale_heads(ka, rk);
      mbar_wait(bar_x + 24, xphase ^ 1);
#pragma unroll
      for (int i = 0; i < 6; i++) stsm4(k_dst + (i + (i >= 3)) * 1024, ka[2 * i], ka[2 * i + 1], ka[12 + 2 * i], ka[12 + 2 * i + 1]);
      TL(4);
      wg_wait<0>(); fence_regs(vv); fence_regs(q01); fence_regs(q23);
      TL(5);
#pragma unroll
      for (int i = 0; i < 6; i++)
        stsm4(k_dst + (WG_V - WG_K) + (i + (i >= 3)) * 1024, pack_bf16(vv[4 * i], vv[4 * i + 1]), pack_bf16(vv[4 * i + 2], vv[4 * i + 3]),
              pack_bf16(vv[24 + 4 * i], vv[24 + 4 * i + 1]), pack_bf16(vv[24 + 4 * i + 2], vv[24 + 4 * i + 3]));
      const float s0 = __uint_as_float(qs.x), s1 = __uint_as_float(qs.y), s2 = __uint_as_float(qs.z), s3 = __uint_as_float(qs.w);
      const float rq[8] = {rsq(q01[0]) * s0, rsq(q01[2]) * s0, rsq(q01[1]) * s1, rsq(q01[3]) * s1,
                           rsq(q23[0]) * s2, rsq(q23[2]) * s2, rsq(q23[1]) * s3, rsq(q23[3]) * s3};
      scale_heads(qa, rq);
    }
    const uint32_t mword = (mw[0].x | mw[0].y | mw[0].z | mw[0].w | mw[1].x | mw[1].y | mw[1].z | mw[1].w) |
                           (mw[2].x | mw[2].y | mw[2].z | mw[2].w | mw[3].x | mw[3].y | mw[3].z | mw[3].w);
    fence_async();
    const bool masked = bar_wg_or(BAR_KV + wg, (mword & 0x7FFF7FFFu) != 0u);
    TL(6);
    auto prefetch_next = [&]() {
      if (warp == 0 && more) {
        if (elect_one()) { load_x(nxt); prefetch_l2(mask_ptr(nxt), 8192); }
        __syncwarp();
      }
    };

    const bool pass_token = (wg == 2 ? slot + stride - 2 * G : slot + G) < NWIN;
    uint32_t of[24];
    if (!masked && slow_heads == 0) {
      float sA[32], sB[32], oA[16], oB[16], oC[16], oD[16];
      uint32_t pA[16], pB[16], pC[16], pD[16];
      wg_fence();
      issue_s<0>(sA, qa, dK);
      issue_s<1>(sB, qa, dK); wg_commit();
      prefetch_next();
      if (slot < G) bar_sync_n(BAR_TOK + wg, 256);
      load_eb(pA, eb_base);
      if (slot >= G) bar_sync_n(BAR_TOK + wg, 256);
      wg_wait<0>(); fence_regs(sA); fence_regs(sB);
      TL(7);
      load_eb(pB, eb_base + 8192);
      softmax_fast(sA, pA);
      wg_fence();
      issue_s<2>(sA, qa, dK); wg_commit();
      issue_pv<0>(oA, pA, dV); wg_commit();
      TL(8);
      softmax_fast(sB, pB);
      load_eb(pC, eb_base + 2 * 8192);
      wg_wait<1>(); fence_regs(sA);
      wg_fence();
      issue_s<3>(sB, qa, dK); wg_commit();
      issue_pv<1>(oB, pB, dV); wg_commit();
      TL(9);
      softmax_fast(sA, pC);
      if (pass_token) bar_arrive_n(tok_next, 256);
      load_eb(pD, eb_base + 3 * 8192);
      wg_wait<1>(); fence_regs(sB); fence_regs(oA);
      wg_fence();
      issue_pv<2>(oC, pC, dV); wg_commit();
      TL(10);
      norm_o<0>(oA, of);
      softmax_fast(sB, pD);
      wg_fence();
      issue_pv<3>(oD, pD, dV); wg_commit();
      wg_wait<1>(); fence_regs(oB); fence_regs(oC);
      norm_o<1>(oB, of + 6);
      norm_o<0>(oC, of + 12);
      wg_wait<0>(); fence_regs(oD);
      norm_o<1>(oD, of + 18);
    } else {
      uint32_t mk[16], em[16];
      const int g = lane >> 2, t = lane & 3;
      const char* mrow = mask_ptr(win) + (orig_tok(16 * warp + g) * 64 + (t >> 1) * 8 + (t & 1) * 2) * 2;
#pragma unroll
      for (int Gk = 0; Gk < 8; Gk++) {
        mk[2 * Gk] = masked ? *reinterpret_cast<const uint32_t*>(mrow + ((Gk & 3) * 16 + (Gk >> 2) * 4) * 2) : 0u;
        mk[2 * Gk + 1] = masked ? *reinterpret_cast<const uint32_t*>(mrow + (16 * 64 + (Gk & 3) * 16 + (Gk >> 2) * 4) * 2) : 0u;
      }
      prefetch_next();
      bar_sync_n(BAR_TOK + wg, 256);
      if (pass_token) bar_arrive_n(tok_next, 256);
      uint32_t x0 = mk[0], x1 = mk[1];
#pragma unroll
      for (int i = 0; i < 16; i++) {
        em[i] = pack_bf16(ex2(bf_lo(mk[i]) * LOG2E), ex2(bf_hi(mk[i]) * LOG2E));
        if (i & 1) x1 = hmax2_nan(x1, mk[i]); else x0 = hmax2_nan(x0, mk[i]);
      }
      const bool nan_in = !(bf_lo(x0) == bf_lo(x0) && bf_hi(x0) == bf_hi(x0) && bf_lo(x1) == bf_lo(x1) && bf_hi(x1) == bf_hi(x1));
      const float r0 = quad_max(fmaxf(bf_lo(x0), bf_hi(x0))), r1 = quad_max(fmaxf(bf_lo(x1), bf_hi(x1)));
      const bool unsafe = bar_wg_or(BAR_AUX + wg, nan_in || !(fabsf(r0) <= 8.f && fabsf(r1) <= 8.f));
      const uint32_t tm = unsafe ? 0xFu : slow_heads;
#pragma unroll
      for (int i = 0; i < 24; i++) of[i] = 0;
#pragma unroll 1
      for (int h = 0; h < 4; h++) {
        float sc[32], o[16]; uint32_t p[16];
        TL(7 + h);
        const uint32_t po = (h * 3 + (h >> 1)) * 64;
        wg_fence(); issue_s<0>(sc, qa, dK + po); wg_commit();
        load_eb(p, eb_base + h * 8192);
        const bool tmax = (tm >> h) & 1;
        if (!tmax) {
#pragma unroll
          for (int i = 0; i < 16; i++) p[i] = hmul2(p[i], em[i]);
        }
        wg_wait<0>(); fence_regs(sc);
        if (tmax) softmax_true_max(sc, p, mk); else softmax_fast(sc, p);
        wg_fence(); issue_pv<0>(o, p, dV + po); wg_commit();
#pragma unroll
        for (int i = 0; i < 20; i++) qa[i] = (h & 1) ? (i < 16 ? qa[i + 8] : 0u) : qa[i + 4];
#pragma unroll
        for (int i = 0; i < 18; i++) of[i] = of[i + 6];
        wg_wait<0>(); fence_regs(o);
        if (h & 1) norm_o<1>(o, of + 18); else norm_o<0>(o, of + 18);
      }
    }
    if (elect_one()) mbar_arrive(bar_x + 24);
    __syncwarp();
    TL(11);

    if (slot < 2 * G) bar_sync_n(BAR_WO + wg, 256);
    float y[48];
    wg_fence();
#pragma unroll
    for (int s = 0; s < 6; s++) {
      if (s == 0) wgmma_rs_n96_t1<0>(y, of[0], of[1], of[2], of[3], dWo);
      else wgmma_rs_n96_t1<1>(y, of[4 * s], of[4 * s + 1], of[4 * s + 2], of[4 * s + 3], dWo + s * 16);
    }
    wg_commit();
    char* optr;
    {
      const int wy = win >> 8, wx = win & 255;
      int py = wy * 8 + 4 + (warp & 1) * 4;  if (py >= IMG) py -= IMG;
      int px = wx * 8 + 4 + (warp >> 1) * 4; if (px >= IMG) px -= IMG;
      optr = reinterpret_cast<char*>(out) + ((uint32_t)(py * IMG + px) * PIXB + out_off);
    }
    xphase ^= 1;
    mbar_wait(bar_x, more ? xphase : xphase ^ 1);
    wg_wait<0>(); fence_regs(y);
    TL(12);
    uint32_t yb[24], sy[8];
    pack_sumsq(y, yb, sy, 0u);
    float var[4];
    wg_fence();
    wgmma_rs_n8_t0<0>(var, sy[0], sy[1], sy[2], sy[3], dV + 3 * 64);
    wgmma_rs_n8_t0<1>(var, sy[4], sy[5], sy[6], sy[7], dV + 3 * 64);
    wg_commit();
    issue_proj(kk, dX, dW + 3 * 384); wg_commit();
    issue_proj(qq, dX, dW); wg_commit();
    wg_wait<2>(); fence_regs(var);
    TL(13);
    const uint32_t nn = pack_bf16(rsq(fmaf(var[0], 1.f / 96.f, 1e-5f)), rsq(fmaf(var[2], 1.f / 96.f, 1e-5f)));
#pragma unroll
    for (int j = 0; j < 3; j++) {
      stg128(optr + j * 64, hmul2_b<0>(yb[8 * j], nn), hmul2_b<0>(yb[8 * j + 2], nn), hmul2_b<0>(yb[8 * j + 4], nn), hmul2_b<0>(yb[8 * j + 6], nn));
      stg128(optr + 2 * ROWB + j * 64, hmul2_b<1>(yb[8 * j + 1], nn), hmul2_b<1>(yb[8 * j + 3], nn), hmul2_b<1>(yb[8 * j + 5], nn), hmul2_b<1>(yb[8 * j + 7], nn));
    }
    TL(14);
    if (!more) break;
    win = nxt;
    slot += stride;
  }
  wg_wait<0>();
  TG(15);
}

typedef CUresult (*EncodeFn)(CUtensorMap*, CUtensorMapDataType, cuuint32_t, void*, const cuuint64_t*, const cuuint64_t*,
                             const cuuint32_t*, const cuuint32_t*, CUtensorMapInterleave, CUtensorMapSwizzle,
                             CUtensorMapL2promotion, CUtensorMapFloatOOBfill);

}

extern "C" void kernel_launch(void* const* d_in, const int* in_sizes, int n_in, void* d_out, int out_size) {
  static int sms = 0;
  static EncodeFn encode = nullptr;
  if (sms == 0) {
    int dev = 0;
    cudaGetDevice(&dev);
    cudaDeviceGetAttribute(&sms, cudaDevAttrMultiProcessorCount, dev);
    cudaFuncSetAttribute(swin_kernel, cudaFuncAttributeMaxDynamicSharedMemorySize, SM_TOTAL);
    cudaDriverEntryPointQueryResult qr;
    void* fn = nullptr;
    cudaGetDriverEntryPoint("cuTensorMapEncodeTiled", &fn, cudaEnableDefault, &qr);
    encode = (EncodeFn)fn;
  }
  CUtensorMap tm_x, tm_xq, tm_w;
  {
    cuuint64_t dims[5] = {32, 4, IMG, IMG / 4, 3};
    cuuint64_t strides[4] = {PIXB, ROWB, 4 * PIXB, 64};
    cuuint32_t es[5] = {1, 1, 1, 1, 1};
    cuuint32_t box[5] = {32, 4, 8, 2, 3}, boxq[5] = {32, 4, 4, 1, 1};
    encode(&tm_x, CU_TENSOR_MAP_DATA_TYPE_BFLOAT16, 5, d_in[0], dims, strides, box, es, CU_TENSOR_MAP_INTERLEAVE_NONE,
           CU_TENSOR_MAP_SWIZZLE_64B, CU_TENSOR_MAP_L2_PROMOTION_L2_128B, CU_TENSOR_MAP_FLOAT_OOB_FILL_NONE);
    encode(&tm_xq, CU_TENSOR_MAP_DATA_TYPE_BFLOAT16, 5, d_in[0], dims, strides, boxq, es, CU_TENSOR_MAP_INTERLEAVE_NONE,
           CU_TENSOR_MAP_SWIZZLE_64B, CU_TENSOR_MAP_L2_PROMOTION_L2_128B, CU_TENSOR_MAP_FLOAT_OOB_FILL_NONE);
    cuuint64_t wd[3] = {32, 96, 9};
    cuuint64_t ws[2] = {576, 64};
    cuuint32_t wb[3] = {32, 96, 9};
    encode(&tm_w, CU_TENSOR_MAP_DATA_TYPE_BFLOAT16, 3, d_in[1], wd, ws, wb, es, CU_TENSOR_MAP_INTERLEAVE_NONE,
           CU_TENSOR_MAP_SWIZZLE_64B, CU_TENSOR_MAP_L2_PROMOTION_L2_128B, CU_TENSOR_MAP_FLOAT_OOB_FILL_NONE);
  }
  swin_kernel<<<sms, 384, SM_TOTAL>>>(
      tm_x, tm_xq, tm_w, (const __nv_bfloat16*)d_in[2], (const __nv_bfloat16*)d_in[3],
      (const __nv_bfloat16*)d_in[4], (const __nv_bfloat16*)d_in[5], (const __nv_bfloat16*)d_in[6], (const int*)d_in[7],
      (const __nv_bfloat16*)d_in[8], (__nv_bfloat16*)d_out);
}
```

```cpp
#include <cuda_runtime.h>
#include <cuda.h>
#include <cuda_bf16.h>
#include <stdint.h>

#define TOKEN 3
namespace {

constexpr int IMG   = 384;
constexpr int NWX   = 48;
constexpr int NWIN  = NWX * NWX;
constexpr int PIXB  = 192;
constexpr int ROWB  = IMG * PIXB;
constexpr float LOG2E = 1.4426950408889634f;

constexpr int SM_W    = 0;
constexpr int SM_WV   = 3 * 12288;
constexpr int SM_WO   = SM_W + 9 * 6144;
constexpr int SM_EB   = SM_WO + 12 * 1536;
constexpr int SM_WG   = SM_EB + 32768;
constexpr int WG_X    = 0;
constexpr int WG_K    = 12288;
constexpr int WG_V    = WG_K + 14336;
constexpr int WG_SZ   = WG_V + 14336;
constexpr int SM_TAB  = SM_WG + WG_SZ + WG_V + 4096;
constexpr int SM_WOR  = SM_WG + WG_K;
constexpr int SM_SEL  = SM_WG + 3 * WG_SZ;
constexpr int SM_MISC = SM_SEL + 256;
constexpr int SM_BAR  = SM_MISC + 16;
constexpr int SM_TKT  = SM_BAR + 104;
constexpr int SM_PAR  = SM_BAR + 128;
constexpr int SM_LANE = SM_PAR + 192;
constexpr int NENT    = 16;
constexpr int SM_WIN  = SM_LANE + 128;
constexpr int SM_TOTAL = SM_WIN + 3 * NENT * 32;

template <int SD> __device__ __forceinline__ void wgmma_ss_n192_t1(float (&d)[96], uint64_t da, uint64_t db) {
  if constexpr (SD) {
    asm volatile("{\n.reg .pred p;\nsetp.ne.b32 p, 1, 0;\n"
      "wgmma.mma_async.sync.aligned.m64n192k16.f32.bf16.bf16 {%0, %1, %2, %3, %4, %5, %6, %7, %8, %9, %10, %11, %12, %13, %14, %15, %16, %17, %18, %19, %20, %21, %22, %23, %24, %25, %26, %27, %28, %29, %30, %31, %32, %33, %34, %35, %36, %37, %38, %39, %40, %41, %42, %43, %44, %45, %46, %47, %48, %49, %50, %51, %52, %53, %54, %55, %56, %57, %58, %59, %60, %61, %62, %63, %64, %65, %66, %67, %68, %69, %70, %71, %72, %73, %74, %75, %76, %77, %78, %79, %80, %81, %82, %83, %84, %85, %86, %87, %88, %89, %90, %91, %92, %93, %94, %95}, %96, %97, p, 1, 1, 0, 1;\n}\n"
      : "+f"(d[0]), "+f"(d[1]), "+f"(d[2]), "+f"(d[3]), "+f"(d[4]), "+f"(d[5]), "+f"(d[6]), "+f"(d[7]), "+f"(d[8]), "+f"(d[9]), "+f"(d[10]), "+f"(d[11]), "+f"(d[12]), "+f"(d[13]), "+f"(d[14]), "+f"(d[15]), "+f"(d[16]), "+f"(d[17]), "+f"(d[18]), "+f"(d[19]), "+f"(d[20]), "+f"(d[21]), "+f"(d[22]), "+f"(d[23]), "+f"(d[24]), "+f"(d[25]), "+f"(d[26]), "+f"(d[27]), "+f"(d[28]), "+f"(d[29]), "+f"(d[30]), "+f"(d[31]), "+f"(d[32]), "+f"(d[33]), "+f"(d[34]), "+f"(d[35]), "+f"(d[36]), "+f"(d[37]), "+f"(d[38]), "+f"(d[39]), "+f"(d[40]), "+f"(d[41]), "+f"(d[42]), "+f"(d[43]), "+f"(d[44]), "+f"(d[45]), "+f"(d[46]), "+f"(d[47]), "+f"(d[48]), "+f"(d[49]), "+f"(d[50]), "+f"(d[51]), "+f"(d[52]), "+f"(d[53]), "+f"(d[54]), "+f"(d[55]), "+f"(d[56]), "+f"(d[57]), "+f"(d[58]), "+f"(d[59]), "+f"(d[60]), "+f"(d[61]), "+f"(d[62]), "+f"(d[63]), "+f"(d[64]), "+f"(d[65]), "+f"(d[66]), "+f"(d[67]), "+f"(d[68]), "+f"(d[69]), "+f"(d[70]), "+f"(d[71]), "+f"(d[72]), "+f"(d[73]), "+f"(d[74]), "+f"(d[75]), "+f"(d[76]), "+f"(d[77]), "+f"(d[78]), "+f"(d[79]), "+f"(d[80]), "+f"(d[81]), "+f"(d[82]), "+f"(d[83]), "+f"(d[84]), "+f"(d[85]), "+f"(d[86]), "+f"(d[87]), "+f"(d[88]), "+f"(d[89]), "+f"(d[90]), "+f"(d[91]), "+f"(d[92]), "+f"(d[93]), "+f"(d[94]), "+f"(d[95])
      : "l"(da), "l"(db));
  } else {
    asm volatile("{\n.reg .pred p;\nsetp.ne.b32 p, 0, 0;\n"
      "wgmma.mma_async.sync.aligned.m64n192k16.f32.bf16.bf16 {%0, %1, %2, %3, %4, %5, %6, %7, %8, %9, %10, %11, %12, %13, %14, %15, %16, %17, %18, %19, %20, %21, %22, %23, %24, %25, %26, %27, %28, %29, %30, %31, %32, %33, %34, %35, %36, %37, %38, %39, %40, %41, %42, %43, %44, %45, %46, %47, %48, %49, %50, %51, %52, %53, %54, %55, %56, %57, %58, %59, %60, %61, %62, %63, %64, %65, %66, %67, %68, %69, %70, %71, %72, %73, %74, %75, %76, %77, %78, %79, %80, %81, %82, %83, %84, %85, %86, %87, %88, %89, %90, %91, %92, %93, %94, %95}, %96, %97, p, 1, 1, 0, 1;\n}\n"
      : "=f"(d[0]), "=f"(d[1]), "=f"(d[2]), "=f"(d[3]), "=f"(d[4]), "=f"(d[5]), "=f"(d[6]), "=f"(d[7]), "=f"(d[8]), "=f"(d[9]), "=f"(d[10]), "=f"(d[11]), "=f"(d[12]), "=f"(d[13]), "=f"(d[14]), "=f"(d[15]), "=f"(d[16]), "=f"(d[17]), "=f"(d[18]), "=f"(d[19]), "=f"(d[20]), "=f"(d[21]), "=f"(d[22]), "=f"(d[23]), "=f"(d[24]), "=f"(d[25]), "=f"(d[26]), "=f"(d[27]), "=f"(d[28]), "=f"(d[29]), "=f"(d[30]), "=f"(d[31]), "=f"(d[32]), "=f"(d[33]), "=f"(d[34]), "=f"(d[35]), "=f"(d[36]), "=f"(d[37]), "=f"(d[38]), "=f"(d[39]), "=f"(d[40]), "=f"(d[41]), "=f"(d[42]), "=f"(d[43]), "=f"(d[44]), "=f"(d[45]), "=f"(d[46]), "=f"(d[47]), "=f"(d[48]), "=f"(d[49]), "=f"(d[50]), "=f"(d[51]), "=f"(d[52]), "=f"(d[53]), "=f"(d[54]), "=f"(d[55]), "=f"(d[56]), "=f"(d[57]), "=f"(d[58]), "=f"(d[59]), "=f"(d[60]), "=f"(d[61]), "=f"(d[62]), "=f"(d[63]), "=f"(d[64]), "=f"(d[65]), "=f"(d[66]), "=f"(d[67]), "=f"(d[68]), "=f"(d[69]), "=f"(d[70]), "=f"(d[71]), "=f"(d[72]), "=f"(d[73]), "=f"(d[74]), "=f"(d[75]), "=f"(d[76]), "=f"(d[77]), "=f"(d[78]), "=f"(d[79]), "=f"(d[80]), "=f"(d[81]), "=f"(d[82]), "=f"(d[83]), "=f"(d[84]), "=f"(d[85]), "=f"(d[86]), "=f"(d[87]), "=f"(d[88]), "=f"(d[89]), "=f"(d[90]), "=f"(d[91]), "=f"(d[92]), "=f"(d[93]), "=f"(d[94]), "=f"(d[95])
      : "l"(da), "l"(db));
  }
}
template <int SD> __device__ __forceinline__ void wgmma_ss_n96_t1(float (&d)[48], uint64_t da, uint64_t db) {
  if constexpr (SD) {
    asm volatile("{\n.reg .pred p;\nsetp.ne.b32 p, 1, 0;\n"
      "wgmma.mma_async.sync.aligned.m64n96k16.f32.bf16.bf16 {%0, %1, %2, %3, %4, %5, %6, %7, %8, %9, %10, %11, %12, %13, %14, %15, %16, %17, %18, %19, %20, %21, %22, %23, %24, %25, %26, %27, %28, %29, %30, %31, %32, %33, %34, %35, %36, %37, %38, %39, %40, %41, %42, %43, %44, %45, %46, %47}, %48, %49, p, 1, 1, 0, 1;\n}\n"
      : "+f"(d[0]), "+f"(d[1]), "+f"(d[2]), "+f"(d[3]), "+f"(d[4]), "+f"(d[5]), "+f"(d[6]), "+f"(d[7]), "+f"(d[8]), "+f"(d[9]), "+f"(d[10]), "+f"(d[11]), "+f"(d[12]), "+f"(d[13]), "+f"(d[14]), "+f"(d[15]), "+f"(d[16]), "+f"(d[17]), "+f"(d[18]), "+f"(d[19]), "+f"(d[20]), "+f"(d[21]), "+f"(d[22]), "+f"(d[23]), "+f"(d[24]), "+f"(d[25]), "+f"(d[26]), "+f"(d[27]), "+f"(d[28]), "+f"(d[29]), "+f"(d[30]), "+f"(d[31]), "+f"(d[32]), "+f"(d[33]), "+f"(d[34]), "+f"(d[35]), "+f"(d[36]), "+f"(d[37]), "+f"(d[38]), "+f"(d[39]), "+f"(d[40]), "+f"(d[41]), "+f"(d[42]), "+f"(d[43]), "+f"(d[44]), "+f"(d[45]), "+f"(d[46]), "+f"(d[47])
      : "l"(da), "l"(db));
  } else {
    asm volatile("{\n.reg .pred p;\nsetp.ne.b32 p, 0, 0;\n"
      "wgmma.mma_async.sync.aligned.m64n96k16.f32.bf16.bf16 {%0, %1, %2, %3, %4, %5, %6, %7, %8, %9, %10, %11, %12, %13, %14, %15, %16, %17, %18, %19, %20, %21, %22, %23, %24, %25, %26, %27, %28, %29, %30, %31, %32, %33, %34, %35, %36, %37, %38, %39, %40, %41, %42, %43, %44, %45, %46, %47}, %48, %49, p, 1, 1, 0, 1;\n}\n"
      : "=f"(d[0]), "=f"(d[1]), "=f"(d[2]), "=f"(d[3]), "=f"(d[4]), "=f"(d[5]), "=f"(d[6]), "=f"(d[7]), "=f"(d[8]), "=f"(d[9]), "=f"(d[10]), "=f"(d[11]), "=f"(d[12]), "=f"(d[13]), "=f"(d[14]), "=f"(d[15]), "=f"(d[16]), "=f"(d[17]), "=f"(d[18]), "=f"(d[19]), "=f"(d[20]), "=f"(d[21]), "=f"(d[22]), "=f"(d[23]), "=f"(d[24]), "=f"(d[25]), "=f"(d[26]), "=f"(d[27]), "=f"(d[28]), "=f"(d[29]), "=f"(d[30]), "=f"(d[31]), "=f"(d[32]), "=f"(d[33]), "=f"(d[34]), "=f"(d[35]), "=f"(d[36]), "=f"(d[37]), "=f"(d[38]), "=f"(d[39]), "=f"(d[40]), "=f"(d[41]), "=f"(d[42]), "=f"(d[43]), "=f"(d[44]), "=f"(d[45]), "=f"(d[46]), "=f"(d[47])
      : "l"(da), "l"(db));
  }
}
template <int SD> __device__ __forceinline__ void wgmma_rs_n96_t1(float (&d)[48], uint32_t a0, uint32_t a1, uint32_t a2, uint32_t a3, uint64_t db) {
  if constexpr (SD) {
    asm volatile("{\n.reg .pred p;\nsetp.ne.b32 p, 1, 0;\n"
      "wgmma.mma_async.sync.aligned.m64n96k16.f32.bf16.bf16 {%0, %1, %2, %3, %4, %5, %6, %7, %8, %9, %10, %11, %12, %13, %14, %15, %16, %17, %18, %19, %20, %21, %22, %23, %24, %25, %26, %27, %28, %29, %30, %31, %32, %33, %34, %35, %36, %37, %38, %39, %40, %41, %42, %43, %44, %45, %46, %47}, {%48, %49, %50, %51}, %52, p, 1, 1, 1;\n}\n"
      : "+f"(d[0]), "+f"(d[1]), "+f"(d[2]), "+f"(d[3]), "+f"(d[4]), "+f"(d[5]), "+f"(d[6]), "+f"(d[7]), "+f"(d[8]), "+f"(d[9]), "+f"(d[10]), "+f"(d[11]), "+f"(d[12]), "+f"(d[13]), "+f"(d[14]), "+f"(d[15]), "+f"(d[16]), "+f"(d[17]), "+f"(d[18]), "+f"(d[19]), "+f"(d[20]), "+f"(d[21]), "+f"(d[22]), "+f"(d[23]), "+f"(d[24]), "+f"(d[25]), "+f"(d[26]), "+f"(d[27]), "+f"(d[28]), "+f"(d[29]), "+f"(d[30]), "+f"(d[31]), "+f"(d[32]), "+f"(d[33]), "+f"(d[34]), "+f"(d[35]), "+f"(d[36]), "+f"(d[37]), "+f"(d[38]), "+f"(d[39]), "+f"(d[40]), "+f"(d[41]), "+f"(d[42]), "+f"(d[43]), "+f"(d[44]), "+f"(d[45]), "+f"(d[46]), "+f"(d[47])
      : "r"(a0), "r"(a1), "r"(a2), "r"(a3), "l"(db));
  } else {
    asm volatile("{\n.reg .pred p;\nsetp.ne.b32 p, 0, 0;\n"
      "wgmma.mma_async.sync.aligned.m64n96k16.f32.bf16.bf16 {%0, %1, %2, %3, %4, %5, %6, %7, %8, %9, %10, %11, %12, %13, %14, %15, %16, %17, %18, %19, %20, %21, %22, %23, %24, %25, %26, %27, %28, %29, %30, %31, %32, %33, %34, %35, %36, %37, %38, %39, %40, %41, %42, %43, %44, %45, %46, %47}, {%48, %49, %50, %51}, %52, p, 1, 1, 1;\n}\n"
      : "=f"(d[0]), "=f"(d[1]), "=f"(d[2]), "=f"(d[3]), "=f"(d[4]), "=f"(d[5]), "=f"(d[6]), "=f"(d[7]), "=f"(d[8]), "=f"(d[9]), "=f"(d[10]), "=f"(d[11]), "=f"(d[12]), "=f"(d[13]), "=f"(d[14]), "=f"(d[15]), "=f"(d[16]), "=f"(d[17]), "=f"(d[18]), "=f"(d[19]), "=f"(d[20]), "=f"(d[21]), "=f"(d[22]), "=f"(d[23]), "=f"(d[24]), "=f"(d[25]), "=f"(d[26]), "=f"(d[27]), "=f"(d[28]), "=f"(d[29]), "=f"(d[30]), "=f"(d[31]), "=f"(d[32]), "=f"(d[33]), "=f"(d[34]), "=f"(d[35]), "=f"(d[36]), "=f"(d[37]), "=f"(d[38]), "=f"(d[39]), "=f"(d[40]), "=f"(d[41]), "=f"(d[42]), "=f"(d[43]), "=f"(d[44]), "=f"(d[45]), "=f"(d[46]), "=f"(d[47])
      : "r"(a0), "r"(a1), "r"(a2), "r"(a3), "l"(db));
  }
}
template <int SD> __device__ __forceinline__ void wgmma_rs_n64_t0(float (&d)[32], uint32_t a0, uint32_t a1, uint32_t a2, uint32_t a3, uint64_t db) {
  if constexpr (SD) {
    asm volatile("{\n.reg .pred p;\nsetp.ne.b32 p, 1, 0;\n"
      "wgmma.mma_async.sync.aligned.m64n64k16.f32.bf16.bf16 {%0, %1, %2, %3, %4, %5, %6, %7, %8, %9, %10, %11, %12, %13, %14, %15, %16, %17, %18, %19, %20, %21, %22, %23, %24, %25, %26, %27, %28, %29, %30, %31}, {%32, %33, %34, %35}, %36, p, 1, 1, 0;\n}\n"
      : "+f"(d[0]), "+f"(d[1]), "+f"(d[2]), "+f"(d[3]), "+f"(d[4]), "+f"(d[5]), "+f"(d[6]), "+f"(d[7]), "+f"(d[8]), "+f"(d[9]), "+f"(d[10]), "+f"(d[11]), "+f"(d[12]), "+f"(d[13]), "+f"(d[14]), "+f"(d[15]), "+f"(d[16]), "+f"(d[17]), "+f"(d[18]), "+f"(d[19]), "+f"(d[20]), "+f"(d[21]), "+f"(d[22]), "+f"(d[23]), "+f"(d[24]), "+f"(d[25]), "+f"(d[26]), "+f"(d[27]), "+f"(d[28]), "+f"(d[29]), "+f"(d[30]), "+f"(d[31])
      : "r"(a0), "r"(a1), "r"(a2), "r"(a3), "l"(db));
  } else {
    asm volatile("{\n.reg .pred p;\nsetp.ne.b32 p, 0, 0;\n"
      "wgmma.mma_async.sync.aligned.m64n64k16.f32.bf16.bf16 {%0, %1, %2, %3, %4, %5, %6, %7, %8, %9, %10, %11, %12, %13, %14, %15, %16, %17, %18, %19, %20, %21, %22, %23, %24, %25, %26, %27, %28, %29, %30, %31}, {%32, %33, %34, %35}, %36, p, 1, 1, 0;\n}\n"
      : "=f"(d[0]), "=f"(d[1]), "=f"(d[2]), "=f"(d[3]), "=f"(d[4]), "=f"(d[5]), "=f"(d[6]), "=f"(d[7]), "=f"(d[8]), "=f"(d[9]), "=f"(d[10]), "=f"(d[11]), "=f"(d[12]), "=f"(d[13]), "=f"(d[14]), "=f"(d[15]), "=f"(d[16]), "=f"(d[17]), "=f"(d[18]), "=f"(d[19]), "=f"(d[20]), "=f"(d[21]), "=f"(d[22]), "=f"(d[23]), "=f"(d[24]), "=f"(d[25]), "=f"(d[26]), "=f"(d[27]), "=f"(d[28]), "=f"(d[29]), "=f"(d[30]), "=f"(d[31])
      : "r"(a0), "r"(a1), "r"(a2), "r"(a3), "l"(db));
  }
}
template <int SD> __device__ __forceinline__ void wgmma_rs_n32_t1(float (&d)[16], uint32_t a0, uint32_t a1, uint32_t a2, uint32_t a3, uint64_t db) {
  if constexpr (SD) {
    asm volatile("{\n.reg .pred p;\nsetp.ne.b32 p, 1, 0;\n"
      "wgmma.mma_async.sync.aligned.m64n32k16.f32.bf16.bf16 {%0, %1, %2, %3, %4, %5, %6, %7, %8, %9, %10, %11, %12, %13, %14, %15}, {%16, %17, %18, %19}, %20, p, 1, 1, 1;\n}\n"
      : "+f"(d[0]), "+f"(d[1]), "+f"(d[2]), "+f"(d[3]), "+f"(d[4]), "+f"(d[5]), "+f"(d[6]), "+f"(d[7]), "+f"(d[8]), "+f"(d[9]), "+f"(d[10]), "+f"(d[11]), "+f"(d[12]), "+f"(d[13]), "+f"(d[14]), "+f"(d[15])
      : "r"(a0), "r"(a1), "r"(a2), "r"(a3), "l"(db));
  } else {
    asm volatile("{\n.reg .pred p;\nsetp.ne.b32 p, 0, 0;\n"
      "wgmma.mma_async.sync.aligned.m64n32k16.f32.bf16.bf16 {%0, %1, %2, %3, %4, %5, %6, %7, %8, %9, %10, %11, %12, %13, %14, %15}, {%16, %17, %18, %19}, %20, p, 1, 1, 1;\n}\n"
      : "=f"(d[0]), "=f"(d[1]), "=f"(d[2]), "=f"(d[3]), "=f"(d[4]), "=f"(d[5]), "=f"(d[6]), "=f"(d[7]), "=f"(d[8]), "=f"(d[9]), "=f"(d[10]), "=f"(d[11]), "=f"(d[12]), "=f"(d[13]), "=f"(d[14]), "=f"(d[15])
      : "r"(a0), "r"(a1), "r"(a2), "r"(a3), "l"(db));
  }
}
template <int SD> __device__ __forceinline__ void wgmma_rs_n8_t0(float (&d)[4], uint32_t a0, uint32_t a1, uint32_t a2, uint32_t a3, uint64_t db) {
  if constexpr (SD) {
    asm volatile("{\n.reg .pred p;\nsetp.ne.b32 p, 1, 0;\n"
      "wgmma.mma_async.sync.aligned.m64n8k16.f32.bf16.bf16 {%0, %1, %2, %3}, {%4, %5, %6, %7}, %8, p, 1, 1, 0;\n}\n"
      : "+f"(d[0]), "+f"(d[1]), "+f"(d[2]), "+f"(d[3])
      : "r"(a0), "r"(a1), "r"(a2), "r"(a3), "l"(db));
  } else {
    asm volatile("{\n.reg .pred p;\nsetp.ne.b32 p, 0, 0;\n"
      "wgmma.mma_async.sync.aligned.m64n8k16.f32.bf16.bf16 {%0, %1, %2, %3}, {%4, %5, %6, %7}, %8, p, 1, 1, 0;\n}\n"
      : "=f"(d[0]), "=f"(d[1]), "=f"(d[2]), "=f"(d[3])
      : "r"(a0), "r"(a1), "r"(a2), "r"(a3), "l"(db));
  }
}

__device__ __forceinline__ void wg_fence()  { asm volatile("wgmma.fence.sync.aligned;" ::: "memory"); }
__device__ __forceinline__ void wg_commit() { asm volatile("wgmma.commit_group.sync.aligned;" ::: "memory"); }
template <int N> __device__ __forceinline__ void wg_wait() { asm volatile("wgmma.wait_group.sync.aligned %0;" :: "n"(N) : "memory"); }
template <int N> __device__ __forceinline__ void fence_regs(float (&d)[N]) {
#pragma unroll
  for (int i = 0; i < N; i++) asm volatile("" : "+f"(d[i]) :: "memory");
}
__device__ __forceinline__ constexpr uint64_t mk_desc(uint32_t addr, uint32_t lbo, uint32_t sbo, uint32_t swz) {
  return (uint64_t)(addr >> 4) | ((uint64_t)(lbo >> 4) << 16) | ((uint64_t)(sbo >> 4) << 32) | ((uint64_t)swz << 62);
}
__device__ __forceinline__ uint32_t pack_bf16(float lo, float hi) {
  uint32_t r; asm("cvt.rn.bf16x2.f32 %0, %1, %2;" : "=r"(r) : "f"(hi), "f"(lo)); return r;
}
__device__ __forceinline__ uint32_t hmul2(uint32_t a, uint32_t b) {
  uint32_t r; asm("mul.rn.bf16x2 %0, %1, %2;" : "=r"(r) : "r"(a), "r"(b)); return r;
}
template <int HI> __device__ __forceinline__ uint32_t hmul2_b(uint32_t a, uint32_t b) {
  uint32_t r;
  if (HI) asm("{\n.reg .b16 l, h;\n.reg .b32 t;\nmov.b32 {l, h}, %2;\nmov.b32 t, {h, h};\nmul.rn.bf16x2 %0, %1, t;\n}\n" : "=r"(r) : "r"(a), "r"(b));
  else    asm("{\n.reg .b16 l, h;\n.reg .b32 t;\nmov.b32 {l, h}, %2;\nmov.b32 t, {l, l};\nmul.rn.bf16x2 %0, %1, t;\n}\n" : "=r"(r) : "r"(a), "r"(b));
  return r;
}
__device__ __forceinline__ uint32_t hfma2(uint32_t a, uint32_t b, uint32_t c) {
  uint32_t r; asm("fma.rn.bf16x2 %0, %1, %2, %3;" : "=r"(r) : "r"(a), "r"(b), "r"(c)); return r;
}
__device__ __forceinline__ float ex2(float x) { float r; asm("ex2.approx.ftz.f32 %0, %1;" : "=f"(r) : "f"(x)); return r; }
__device__ __forceinline__ float rsq(float x) { float r; asm("rsqrt.approx.ftz.f32 %0, %1;" : "=f"(r) : "f"(x)); return r; }
__device__ __forceinline__ float rcp(float x) { float r; asm("rcp.approx.ftz.f32 %0, %1;" : "=f"(r) : "f"(x)); return r; }
__device__ __forceinline__ void stsm4(uint32_t addr, uint32_t r0, uint32_t r1, uint32_t r2, uint32_t r3) {
  asm volatile("stmatrix.sync.aligned.m8n8.x4.shared.b16 [%0], {%1,%2,%3,%4};" :: "r"(addr), "r"(r0), "r"(r1), "r"(r2), "r"(r3) : "memory");
}
__device__ __forceinline__ void fence_async() { asm volatile("fence.proxy.async.shared::cta;" ::: "memory"); }
__device__ __forceinline__ void bar_sync_n(int id, int n) { asm volatile("bar.sync %0, %1;" :: "r"(id), "r"(n) : "memory"); }
__device__ __forceinline__ void bar_arrive_n(int id, int n) { asm volatile("bar.arrive %0, %1;" :: "r"(id), "r"(n) : "memory"); }
__device__ __forceinline__ bool bar_wg_or(int id, bool v) {
  uint32_t r;
  asm volatile("{\n.reg .pred p, q;\nsetp.ne.u32 q, %2, 0;\nbar.red.or.pred p, %1, 128, q;\nselp.u32 %0, 1, 0, p;\n}\n"
               : "=r"(r) : "r"(id), "r"((uint32_t)v) : "memory");
  return r != 0;
}
__device__ __forceinline__ void mbar_init(uint32_t bar, uint32_t cnt) { asm volatile("mbarrier.init.shared::cta.b64 [%0], %1;" :: "r"(bar), "r"(cnt) : "memory"); }
__device__ __forceinline__ void mbar_expect(uint32_t bar, uint32_t bytes) {
  asm volatile("mbarrier.arrive.expect_tx.shared::cta.b64 _, [%0], %1;" :: "r"(bar), "r"(bytes) : "memory");
}
__device__ __forceinline__ void mbar_arrive(uint32_t bar) { asm volatile("mbarrier.arrive.shared::cta.b64 _, [%0];" :: "r"(bar) : "memory"); }
__device__ __forceinline__ void mbar_wait(uint32_t bar, uint32_t parity) {
  asm volatile("{\n.reg .pred p;\n.reg .u32 n;\nmov.u32 n, 0;\n"
               "LW_%=:\nmbarrier.try_wait.parity.shared::cta.b64 p, [%0], %1;\n@p bra.uni LD_%=;\n"
               "add.u32 n, n, 1;\nsetp.lt.u32 p, n, 4194304;\n@p bra.uni LW_%=;\ntrap;\nLD_%=:\n}\n"
               :: "r"(bar), "r"(parity) : "memory");
}
__device__ __forceinline__ void tma5(uint32_t dst, const CUtensorMap* m, uint32_t bar, int c0, int c1, int c2, int c3, int c4) {
  asm volatile("cp.async.bulk.tensor.5d.shared::cluster.global.mbarrier::complete_tx::bytes [%0], [%1, {%3, %4, %5, %6, %7}], [%2];"
               :: "r"(dst), "l"(m), "r"(bar), "r"(c0), "r"(c1), "r"(c2), "r"(c3), "r"(c4) : "memory");
}
__device__ __forceinline__ void tma3(uint32_t dst, const CUtensorMap* m, uint32_t bar, int c0, int c1, int c2) {
  asm volatile("cp.async.bulk.tensor.3d.shared::cluster.global.mbarrier::complete_tx::bytes [%0], [%1, {%3, %4, %5}], [%2];"
               :: "r"(dst), "l"(m), "r"(bar), "r"(c0), "r"(c1), "r"(c2) : "memory");
}
__device__ __forceinline__ void bulk_g2s(uint32_t dst, const void* src, uint32_t bytes, uint32_t bar) {
  asm volatile("cp.async.bulk.shared::cluster.global.mbarrier::complete_tx::bytes [%0], [%1], %2, [%3];"
               :: "r"(dst), "l"(src), "r"(bytes), "r"(bar) : "memory");
}
__device__ __forceinline__ uint32_t lds32(uint32_t addr) {
  uint32_t v; asm volatile("ld.shared.u32 %0, [%1];" : "=r"(v) : "r"(addr)); return v;
}
__device__ __forceinline__ uint64_t opaque(uint64_t v) { asm volatile("" : "+l"(v)); return v; }
__device__ __forceinline__ uint4 lds128(uint32_t addr) {
  uint4 v; asm volatile("ld.shared.v4.u32 {%0,%1,%2,%3}, [%4];" : "=r"(v.x), "=r"(v.y), "=r"(v.z), "=r"(v.w) : "r"(addr)); return v;
}
__device__ __forceinline__ uint4 ldg128_stream(const void* p) {
  uint4 v; asm volatile("ld.global.nc.L1::no_allocate.v4.u32 {%0,%1,%2,%3}, [%4];" : "=r"(v.x), "=r"(v.y), "=r"(v.z), "=r"(v.w) : "l"(p)); return v;
}
__device__ __forceinline__ void stg128(void* p, uint32_t a, uint32_t b, uint32_t c, uint32_t d) {
  asm volatile("st.global.v4.u32 [%0], {%1,%2,%3,%4};" :: "l"(p), "r"(a), "r"(b), "r"(c), "r"(d) : "memory");
}
__device__ __forceinline__ void prefetch_l2(const void* p, uint32_t bytes) {
  asm volatile("cp.async.bulk.prefetch.L2.global [%0], %1;" :: "l"(p), "r"(bytes) : "memory");
}
__device__ __forceinline__ bool elect_one() {
  uint32_t r; asm volatile("{\n.reg .pred p;\nelect.sync _|p, 0xffffffff;\nselp.u32 %0, 1, 0, p;\n}\n" : "=r"(r)); return r != 0;
}
__device__ __forceinline__ float bf_lo(uint32_t u) { return __uint_as_float(u << 16); }
__device__ __forceinline__ float bf_hi(uint32_t u) { return __uint_as_float(u & 0xFFFF0000u); }
__device__ __forceinline__ float rbf(float x) { return bf_lo(pack_bf16(x, 0.f)); }
__device__ __forceinline__ int orig_tok(int r) { return ((r & 31) >> 2) * 8 + (r >> 5) * 4 + (r & 3); }

__device__ __forceinline__ int slot_window(int s, bool g132) {
  constexpr int A0 = 396 + 60, A1 = A0 + 72, B0 = 3 * 396 + 132 + 60, B1 = B0 + 23;
  const int i = s - (s >= B1 ? 95 : s >= A1 ? 72 : 0);
  const int k = s >= B0 ? s - B0 + 72 : s - A0;
  const bool border = (s >= A0 && s < A1) || (s >= B0 && s < B1);
  const int iy = (i * 2789) >> 17, sy = (s * 2731) >> 17;
  const int wa = border ? (k < 48 ? (47 << 8 | k) : ((k - 48) << 8 | 47)) : (iy << 8 | (i - iy * 47));
  return g132 ? wa : (sy << 8 | (s - sy * 48));
}

#define EB_WORD(e, j, a) ((((a) ^ ((j) & 1)) == 0) ? (e).x : (((a) ^ ((j) & 1)) == 1) ? (e).y : (((a) ^ ((j) & 1)) == 2) ? (e).z : (e).w)

__device__ __forceinline__ void load_eb(uint32_t (&e)[16], uint32_t eb_addr) {
#pragma unroll
  for (int j = 0; j < 4; j++) {
    const uint4 v = lds128(eb_addr + j * 2048);
#pragma unroll
    for (int a = 0; a < 4; a++) e[4 * j + a] = EB_WORD(v, j, a);
  }
}
__device__ __forceinline__ void softmax_fast(const float (&s)[32], uint32_t (&p)[16]) {
#pragma unroll
  for (int i = 0; i < 16; i++) p[i] = hmul2(pack_bf16(ex2(s[2 * i]), ex2(s[2 * i + 1])), p[i]);
}
__device__ __forceinline__ uint32_t hmax2(uint32_t a, uint32_t b) {
  uint32_t r; asm("max.bf16x2 %0, %1, %2;" : "=r"(r) : "r"(a), "r"(b)); return r;
}
__device__ __forceinline__ uint32_t hmax2_nan(uint32_t a, uint32_t b) {
  uint32_t r; asm("max.NaN.bf16x2 %0, %1, %2;" : "=r"(r) : "r"(a), "r"(b)); return r;
}
__device__ __forceinline__ float quad_max(float m) {
  m = fmaxf(m, __shfl_xor_sync(0xffffffffu, m, 1));
  return fmaxf(m, __shfl_xor_sync(0xffffffffu, m, 2));
}
__device__ __forceinline__ void softmax_true_max(float (&s)[32], uint32_t (&p)[16], const uint32_t (&mk)[16]) {
#pragma unroll
  for (int i = 0; i < 16; i++) {
    s[2 * i] = fmaf(bf_lo(mk[i]), LOG2E, s[2 * i]); s[2 * i + 1] = fmaf(bf_hi(mk[i]), LOG2E, s[2 * i + 1]);
  }
  float m0 = s[0], m1 = s[2];
#pragma unroll
  for (int g = 0; g < 8; g++) {
    m0 = fmaxf(m0, fmaxf(s[4 * g + 0], s[4 * g + 1]));
    m1 = fmaxf(m1, fmaxf(s[4 * g + 2], s[4 * g + 3]));
  }
  m0 = quad_max(m0); m1 = quad_max(m1);
  uint32_t n0 = 0, n1 = 0;
#pragma unroll
  for (int g = 0; g < 8; g++) {
    p[2 * g + 0] = hmul2(pack_bf16(ex2(s[4 * g + 0] - m0), ex2(s[4 * g + 1] - m0)), p[2 * g + 0]);
    p[2 * g + 1] = hmul2(pack_bf16(ex2(s[4 * g + 2] - m1), ex2(s[4 * g + 3] - m1)), p[2 * g + 1]);
    n0 = hmax2(n0, p[2 * g]); n1 = hmax2(n1, p[2 * g + 1]);
  }
  const uint32_t r = pack_bf16(rcp(quad_max(fmaxf(bf_lo(n0), bf_hi(n0)))), rcp(quad_max(fmaxf(bf_lo(n1), bf_hi(n1)))));
#pragma unroll
  for (int g = 0; g < 8; g++) { p[2 * g] = hmul2_b<0>(p[2 * g], r); p[2 * g + 1] = hmul2_b<1>(p[2 * g + 1], r); }
}
template <int H> __device__ __forceinline__ void issue_s(float (&s)[32], const uint32_t (&q)[24], uint64_t dK) {
  constexpr int Q0 = (H == 0 ? 0 : H == 1 ? 4 : H == 2 ? 12 : 16), P0 = (H == 0 ? 0 : H == 1 ? 3 : H == 2 ? 7 : 10);
  wgmma_rs_n64_t0<0>(s, q[Q0], q[Q0 + 1], q[Q0 + 2], q[Q0 + 3], dK + P0 * 64);
  wgmma_rs_n64_t0<1>(s, q[Q0 + 4], q[Q0 + 5], q[Q0 + 6], q[Q0 + 7], dK + P0 * 64 + 128);
}
template <int H> __device__ __forceinline__ void issue_pv(float (&o)[16], const uint32_t (&p)[16], uint64_t dV) {
  constexpr int P0 = (H == 0 ? 0 : H == 1 ? 3 : H == 2 ? 7 : 10);
  wgmma_rs_n32_t1<0>(o, p[0], p[1], p[2], p[3], dV + P0 * 64);
  wgmma_rs_n32_t1<1>(o, p[4], p[5], p[6], p[7], dV + P0 * 64 + 16);
  wgmma_rs_n32_t1<1>(o, p[8], p[9], p[10], p[11], dV + P0 * 64 + 32);
  wgmma_rs_n32_t1<1>(o, p[12], p[13], p[14], p[15], dV + P0 * 64 + 48);
}
__device__ __forceinline__ void issue_proj(float (&d)[48], uint64_t dX, uint64_t dW) {
#pragma unroll
  for (int s = 0; s < 6; s++) {
    const uint64_t a = dX + (s >> 1) * 256 + (s & 1) * 2, b = dW + s * 64;
    if (s == 0) wgmma_ss_n96_t1<0>(d, a, b); else wgmma_ss_n96_t1<1>(d, a, b);
  }
}
__device__ __forceinline__ void issue_qk(float (&d)[96], uint64_t dX, uint64_t dW) {
#pragma unroll
  for (int s = 0; s < 6; s++) {
    const uint64_t a = dX + (s >> 1) * 256 + (s & 1) * 2, b = dW + s * 128;
    if (s == 0) wgmma_ss_n192_t1<0>(d, a, b); else wgmma_ss_n192_t1<1>(d, a, b);
  }
}
__device__ __forceinline__ void pack_sumsq(const float* a, uint32_t (&f)[24], uint32_t (&sq)[8], uint32_t init) {
#pragma unroll
  for (int i = 0; i < 24; i++) f[i] = pack_bf16(a[2 * i], a[2 * i + 1]);
#pragma unroll
  for (int h = 0; h < 4; h++)
#pragma unroll
    for (int r = 0; r < 2; r++) {
      uint32_t u = f[6 * h + r], v = f[6 * h + 2 + r], w = f[6 * h + 4 + r];
      sq[2 * h + r] = hfma2(w, w, hfma2(v, v, hfma2(u, u, init)));
    }
}
__device__ __forceinline__ void scale_heads(uint32_t (&f)[24], const float (&r)[8]) {
#pragma unroll
  for (int h = 0; h < 4; h++) {
    const uint32_t p = pack_bf16(r[2 * h], r[2 * h + 1]);
#pragma unroll
    for (int c = 0; c < 3; c++) {
      f[6 * h + 2 * c] = hmul2_b<0>(f[6 * h + 2 * c], p);
      f[6 * h + 2 * c + 1] = hmul2_b<1>(f[6 * h + 2 * c + 1], p);
    }
  }
}
template <int ODD> __device__ __forceinline__ void norm_o(const float (&o)[16], uint32_t* of) {
  constexpr int SO = ODD ? 0 : 12, VO = ODD ? 4 : 0;
  const uint32_t p = pack_bf16(rcp(o[SO]), rcp(o[SO + 2]));
#pragma unroll
  for (int g = 0; g < 3; g++) {
    of[2 * g + 0] = hmul2_b<0>(pack_bf16(o[VO + 4 * g + 0], o[VO + 4 * g + 1]), p);
    of[2 * g + 1] = hmul2_b<1>(pack_bf16(o[VO + 4 * g + 2], o[VO + 4 * g + 3]), p);
  }
}

#define TL(i)
#define TG(i)

constexpr int BAR_KV = 1;
constexpr int BAR_AUX = 4;
constexpr int BAR_TAB = 7, BAR_SETUP = 8, BAR_RDY = 9;
constexpr int MB_WQK = 0, MB_X = 8, MB_KV = 32, MB_WV = 56, MB_WO = 64, MB_TURN = 72;

#define X1EARLY 1

__global__ void __launch_bounds__(384, 1)
swin_kernel(const __grid_constant__ CUtensorMap tm_x, const __grid_constant__ CUtensorMap tm_xq, const __grid_constant__ CUtensorMap tm_wqk,
            const __grid_constant__ CUtensorMap tm_wv,
            const __nv_bfloat16* __restrict__ wo,
            const __nv_bfloat16* __restrict__ logit_scale, const __nv_bfloat16* __restrict__ w1, const __nv_bfloat16* __restrict__ w2,
            const __nv_bfloat16* __restrict__ coords, const int* __restrict__ rel_idx, const __nv_bfloat16* __restrict__ mask,
            __nv_bfloat16* __restrict__ out) {
  extern __shared__ __align__(1024) uint8_t smem[];
  constexpr uint32_t sb = 1024, mbar = sb + SM_BAR;
  const int tid = threadIdx.x, lane = tid & 31;
  const int warp = __shfl_sync(0xffffffffu, (tid >> 5) & 3, 0), wg = __shfl_sync(0xffffffffu, tid >> 7, 0);
  const uint32_t t16 = (tid & 127) * 16;
  const int G = gridDim.x;
  const uint32_t wgb = sb + SM_WG + wg * WG_SZ;
  const uint32_t bar_x = mbar + MB_X + 8 * wg;
  const char* mb = reinterpret_cast<const char*>(mask);
  TL(0); TG(14);

  auto load_x = [&](int w, int g) {
    const uint32_t dst = sb + SM_WG + g * WG_SZ + WG_X, bar = mbar + MB_X + 8 * g;
    const int wy = w >> 8, wx = w & 255;
    mbar_expect(bar, 12288);
    if (wy != NWX - 1 && wx != NWX - 1) {
      tma5(dst, &tm_x, bar, 0, 0, wy * 8 + 4, wx * 2 + 1, 0);
    } else {
#pragma unroll 1
      for (int i = 0; i < 12; i++) {
        const int q = i & 3, c = i >> 2;
        int y = wy * 8 + 4 + (q & 1) * 4; if (y >= IMG) y -= IMG;
        int xq = wx * 2 + 1 + (q >> 1);   if (xq >= IMG / 4) xq -= IMG / 4;
        tma5(dst + i * 1024, &tm_xq, bar, 0, 0, y, xq, c);
      }
    }
  };
  auto mask_off = [&](int w) { return (uint32_t)((w >> 8) * NWX + (w & 255)) * 8192u; };
  uint4 mw[4];
  auto load_mask = [&](uint32_t off) {
    const char* src = mb + (off + t16);
#pragma unroll
    for (int i = 0; i < 4; i++) mw[i] = ldg128_stream(src + i * 2048);
  };
  auto mask_or = [&](uint32_t seed) {
    uint32_t r = seed & 0x80008000u;
#pragma unroll
    for (int i = 0; i < 4; i++) {
      asm("lop3.b32 %0, %0, %1, %2, 0xFE;" : "+r"(r) : "r"(mw[i].x), "r"(mw[i].y));
      asm("lop3.b32 %0, %0, %1, %2, 0xFE;" : "+r"(r) : "r"(mw[i].z), "r"(mw[i].w));
    }
    return r;
  };
  auto lds_uniform = [&](uint32_t addr) { return __shfl_sync(0xffffffffu, lds32(addr), 0); };

  const bool g132 = G == 132;
  uint32_t cw = 0;
  int4 rid[4];
  if (wg == 0) {
    if (warp == 0) {
      if (elect_one()) {
#pragma unroll
        for (int i = 0; i < 13; i++) mbar_init(mbar + 8 * i, ((i >= 4 && i < 7) || i >= 9) ? 4 : 1);
        *reinterpret_cast<volatile uint32_t*>(smem + SM_TKT) = 0;
        fence_async();
        mbar_expect(mbar + MB_WQK, 3 * 12288);
        tma3(sb + SM_W, &tm_wqk, mbar + MB_WQK, 0, 0, 0);
        load_x(slot_window(blockIdx.x, g132), 0);
        mbar_expect(mbar + MB_WO, 18432);
        bulk_g2s(sb + SM_WOR, wo, 18432, mbar + MB_WO);
        mbar_expect(mbar + MB_WV, 3 * 6144);
        tma3(sb + SM_WV, &tm_wv, mbar + MB_WV, 0, 0, 0);
        load_x(slot_window(blockIdx.x + G, g132), 1);
#pragma unroll
        for (int i = 0; i < 4; i++) mbar_arrive(mbar + MB_TURN);
      }
      __syncwarp();
    }
  } else {
    const int i = tid - 128;
    if (i < 12) *reinterpret_cast<uint4*>(smem + SM_PAR + 16 * i) = __ldg(i < 4 ? reinterpret_cast<const uint4*>(w1) + i : reinterpret_cast<const uint4*>(w2) + (i - 4));
    if (i < 225) cw = __ldg(reinterpret_cast<const uint32_t*>(coords) + i);
#pragma unroll
    for (int c = 0; c < 4; c++) rid[c] = __ldg(reinterpret_cast<const int4*>(rel_idx) + c * 256 + i);
  }
  const uint2 lsw = __ldg(reinterpret_cast<const uint2*>(logit_scale));
  if ((uint32_t)__cvta_generic_to_shared(smem) != sb) __trap();
  auto const_tiles = [&]() {
    const int i = tid & 127;
    uint8_t* vt = smem + SM_WG + wg * WG_SZ + WG_V + (i < 64 ? 3 : 10) * 1024 + (i & 63) * 16;
    *reinterpret_cast<uint4*>(vt) = make_uint4(0x3F803F80u, 0x3F803F80u, 0x3F803F80u, 0x3F803F80u);
    *reinterpret_cast<uint4*>(vt - (WG_V - WG_K)) = make_uint4(0u, 0u, 0u, 0u);
  };
  if (wg != 0) const_tiles();
  else if (tid >= 32 && tid < 32 + 3 * NENT) {
    const int e = tid - 32, sl = blockIdx.x + (e / NENT) * G + (e % NENT) * 3 * G;
    const int w = sl < NWIN ? slot_window(sl, g132) : -1;
    const int wy = w >> 8, wx = w & 255;
    const uint32_t y0 = wy * 8 + 4, y1 = wy == NWX - 1 ? 0 : y0 + 4, x0 = wx * 8 + 4, x1 = wx == NWX - 1 ? 0 : x0 + 4;
    *reinterpret_cast<uint4*>(smem + SM_WIN + e * 32) = make_uint4((y0 * IMG + x0) * PIXB, (y1 * IMG + x0) * PIXB, (y0 * IMG + x1) * PIXB, (y1 * IMG + x1) * PIXB);
    *reinterpret_cast<uint2*>(smem + SM_WIN + e * 32 + 16) = make_uint2(w, mask_off(w));
  } else if (tid >= 96) {
    *reinterpret_cast<uint32_t*>(smem + SM_LANE + lane * 4) = ((lane >> 4) * IMG + ((lane >> 2) & 3)) * PIXB + (lane & 3) * 16;
    if (lane < 16) {
      const uint32_t v = (((lane >> 3) ^ lane) & 1) ? 0u : 0x3F803F80u;
      *reinterpret_cast<uint4*>(smem + SM_SEL + lane * 16) = make_uint4(v, v, v, v);
    }
  }
  float tau[4]; uint32_t slow_heads = 0;
  {
    const float ls[4] = {bf_lo(lsw.x), bf_hi(lsw.x), bf_lo(lsw.y), bf_hi(lsw.y)};
#pragma unroll
    for (int h = 0; h < 4; h++) {
      const float c = ls[h] < -100.f ? -100.f : (ls[h] > 4.59375f ? 4.59375f : ls[h]);
      tau[h] = rbf(ex2(c * LOG2E)) * LOG2E;
      if (!(tau[h] * 2.04f <= 80.f)) slow_heads |= 1u << h;
    }
    slow_heads = __shfl_sync(0xffffffffu, slow_heads, 0);
  }
  TL(3);
  if (wg == 0) {
    if (tid == 0) *reinterpret_cast<float4*>(smem + SM_MISC) = make_float4(tau[0], tau[1], tau[2], tau[3]);
    fence_async();
    bar_arrive_n(BAR_SETUP, 384);
    bar_sync_n(BAR_AUX, 128);
  } else {
    const int i = tid - 128;
    bar_sync_n(BAR_TAB, 256);
    TL(4);
    if (i < 225) {
      const float c0 = bf_lo(cw), c1 = bf_hi(cw);
      float z[4] = {0.f, 0.f, 0.f, 0.f};
#pragma unroll
      for (int jj = 0; jj < 2; jj++) {
        const uint4 ua4 = lds128(sb + SM_PAR + 16 * jj), ub4 = lds128(sb + SM_PAR + 32 + 16 * jj);
        const uint32_t ua[4] = {ua4.x, ua4.y, ua4.z, ua4.w}, ub[4] = {ub4.x, ub4.y, ub4.z, ub4.w};
#pragma unroll
        for (int j = 0; j < 4; j++) {
          const uint4 wb = lds128(sb + SM_PAR + 64 + 64 * jj + 16 * j);
          const uint32_t hp = pack_bf16(fmaf(c1, bf_lo(ub[j]), c0 * bf_lo(ua[j])), fmaf(c1, bf_hi(ub[j]), c0 * bf_hi(ua[j])));
          float h0 = bf_lo(hp), h1 = bf_hi(hp);
          h0 = h0 > 0.f ? h0 : h0 * 0.f; h1 = h1 > 0.f ? h1 : h1 * 0.f;
          z[0] = fmaf(h0, bf_lo(wb.x), z[0]); z[1] = fmaf(h0, bf_hi(wb.x), z[1]); z[2] = fmaf(h0, bf_lo(wb.y), z[2]); z[3] = fmaf(h0, bf_hi(wb.y), z[3]);
          z[0] = fmaf(h1, bf_lo(wb.z), z[0]); z[1] = fmaf(h1, bf_hi(wb.z), z[1]); z[2] = fmaf(h1, bf_lo(wb.w), z[2]); z[3] = fmaf(h1, bf_hi(wb.w), z[3]);
        }
      }
      float e[4];
#pragma unroll
      for (int q = 0; q < 4; q++) {
        const float sh = ((slow_heads >> q) & 1) ? 0.f : -1.02f * tau[q];
        e[q] = ex2(fmaf(16.f * LOG2E, rbf(rcp(1.f + ex2(-LOG2E * rbf(z[q])))), sh));
      }
      *reinterpret_cast<uint2*>(smem + SM_TAB + 8 * i) = make_uint2(pack_bf16(e[0], e[1]), pack_bf16(e[2], e[3]));
    }
    TL(5);
    bar_sync_n(BAR_TAB, 256);
#pragma unroll
    for (int c = 0; c < 4; c++) asm volatile("" : "+r"(rid[c].x), "+r"(rid[c].y), "+r"(rid[c].z), "+r"(rid[c].w));
    {
      const int y = (i & 15) >> 1, xh = i & 1, j = 2 * xh + (y >> 2);
      const int X = (i >> 4) & 7, Yl = (i >> 7) & 1;
      uint8_t* dst = smem + SM_EB + j * 2048 + ((X >> 2) * 64 + (Yl * 4 + (X & 3)) * 4 + 2 * (y & 1)) * 16 + ((y >> 1) & 1) * 8;
#pragma unroll
      for (int c = 0; c < 4; c++) {
        const int ia0 = xh ? rid[c].z : rid[c].x, ia1 = xh ? rid[c].w : rid[c].y, ib0 = xh ? rid[c].x : rid[c].z, ib1 = xh ? rid[c].y : rid[c].w;
        const uint2 a0 = *reinterpret_cast<const uint2*>(smem + SM_TAB + 8 * ia0), a1 = *reinterpret_cast<const uint2*>(smem + SM_TAB + 8 * ia1);
        const uint2 b0 = *reinterpret_cast<const uint2*>(smem + SM_TAB + 8 * ib0), b1 = *reinterpret_cast<const uint2*>(smem + SM_TAB + 8 * ib1);
        uint8_t* d0 = dst + (c >> 1) * 512 + (((c & 1) ^ (j & 1)) * 4) + xh * 16;
        uint8_t* d1 = dst + (c >> 1) * 512 + (((c & 1) ^ (j & 1)) * 4) + (xh ^ 1) * 16;
        *reinterpret_cast<uint32_t*>(d0)         = __byte_perm(a0.x, a1.x, 0x5410); *reinterpret_cast<uint32_t*>(d1)         = __byte_perm(b0.x, b1.x, 0x5410);
        *reinterpret_cast<uint32_t*>(d0 + 8192)  = __byte_perm(a0.x, a1.x, 0x7632); *reinterpret_cast<uint32_t*>(d1 + 8192)  = __byte_perm(b0.x, b1.x, 0x7632);
        *reinterpret_cast<uint32_t*>(d0 + 16384) = __byte_perm(a0.y, a1.y, 0x5410); *reinterpret_cast<uint32_t*>(d1 + 16384) = __byte_perm(b0.y, b1.y, 0x5410);
        *reinterpret_cast<uint32_t*>(d0 + 24576) = __byte_perm(a0.y, a1.y, 0x7632); *reinterpret_cast<uint32_t*>(d1 + 24576) = __byte_perm(b0.y, b1.y, 0x7632);
      }
    }
    TL(6);
    fence_async();
    bar_arrive_n(BAR_RDY, 384);
    bar_sync_n(BAR_SETUP, 384);
  }
  uint32_t wl = sb + SM_WIN + wg * NENT * 32;
  load_mask(lds32(wl + 20));
  TL(1);
  mbar_wait(bar_x, 0);
  mbar_wait(mbar + MB_WQK, 0);
  TL(2);
  float qk[96];
  wg_fence();
  issue_qk(qk, mk_desc(WG_X, 16, 512, 2) + (wgb >> 4), mk_desc(sb + SM_W, 12288, 1024, 1)); wg_commit();
  if (warp == 0 && elect_one()) {
    if (wg == 0) {
      load_x(lds32(wl + 2 * NENT * 32 + 16), 2);
    }
    if ((int)lds32(wl + 48) >= 0) prefetch_l2(mb + lds32(wl + 52), 8192);
  }
  __syncwarp();
  if (wg == 0) {
    mbar_wait(mbar + MB_WO, 0);
#pragma unroll 1
    for (int r = 0; r < 3; r++) {
      uint4 v[3];
#pragma unroll
      for (int c = 0; c < 3; c++) v[c] = lds128(sb + SM_WOR + (r * 32 + (tid >> 2)) * 192 + c * 64 + (lane & 3) * 16);
      float sum = 0.f;
#pragma unroll
      for (int c = 0; c < 3; c++)
        sum += (bf_lo(v[c].x) + bf_hi(v[c].x)) + (bf_lo(v[c].y) + bf_hi(v[c].y)) + (bf_lo(v[c].z) + bf_hi(v[c].z)) + (bf_lo(v[c].w) + bf_hi(v[c].w));
      sum += __shfl_xor_sync(0xffffffffu, sum, 1);
      sum += __shfl_xor_sync(0xffffffffu, sum, 2);
      const float mu = sum * (1.f / 96.f);
      auto cen = [&](uint32_t u) { return pack_bf16(bf_lo(u) - mu, bf_hi(u) - mu); };
      uint8_t* dst = smem + SM_WO + (r * 4 + warp) * 128 + lane * 4;
#pragma unroll
      for (int j = 0; j < 3; j++) {
        *reinterpret_cast<uint32_t*>(dst + (4 * j + 0) * 1536) = cen(v[j].x);
        *reinterpret_cast<uint32_t*>(dst + (4 * j + 1) * 1536) = cen(v[j].y);
        *reinterpret_cast<uint32_t*>(dst + (4 * j + 2) * 1536) = cen(v[j].z);
        *reinterpret_cast<uint32_t*>(dst + (4 * j + 3) * 1536) = cen(v[j].w);
      }
    }
    bar_sync_n(BAR_AUX, 128);
    const_tiles();
    fence_async();
    bar_arrive_n(BAR_RDY + 1, 256);
    bar_arrive_n(BAR_RDY + 2, 256);
  }
  uint32_t mword = mask_or(0);
  TL(7);
  bar_sync_n(BAR_RDY + wg, wg == 0 ? 384 : 256);
  mbar_wait(mbar + MB_WV, 0);
  TL(8);

  const uint32_t k_dst = wgb + WG_K + (lane >> 4) * 7168 + warp * 256 + (lane & 15) * 16;
  const uint32_t eb_base = sb + SM_EB + t16;
  constexpr uint32_t EPS8 = 0x2A0D2A0Du;
  uint32_t xphase = 0;

  while (true) {
    const int nxt = lds_uniform(wl + 48);
    const bool more = nxt >= 0;
    const uint32_t z0 = wl >> 20, zw = z0 + (wgb >> 4);
    const uint64_t dX = opaque(mk_desc(WG_X, 16, 512, 2) + zw);
    TL(0);
    uint32_t qa[24];
    {
      uint32_t ka[24], sk[8], sq[8];
      float k01[4], k23[4], q01[4], q23[4], vv[48];
      constexpr uint64_t dSel = mk_desc(sb + SM_SEL, 128, 256, 0);
      wg_wait<0>(); fence_regs(qk);
      TL(1);
      pack_sumsq(qk + 48, ka, sk, EPS8);
      pack_sumsq(qk, qa, sq, EPS8);
      wg_fence();
      wgmma_rs_n8_t0<0>(k01, sk[0], sk[1], sk[2], sk[3], dSel);
      wgmma_rs_n8_t0<0>(k23, sk[4], sk[5], sk[6], sk[7], dSel);
      wgmma_rs_n8_t0<0>(q01, sq[0], sq[1], sq[2], sq[3], dSel);
      wgmma_rs_n8_t0<0>(q23, sq[4], sq[5], sq[6], sq[7], dSel);
      wg_commit();
      issue_proj(vv, dX, opaque(mk_desc(sb + SM_WV, 6144, 512, 2) + z0)); wg_commit();
      const uint4 qs = lds128(sb + SM_MISC);
      if (warp == 1 && elect_one()) {
        uint32_t tk;
        asm volatile("atom.shared.add.u32 %0, [%1], 1;" : "=r"(tk) : "r"(sb + SM_TKT) : "memory");
        asm volatile("st.shared.u32 [%0], %1;" :: "r"(sb + SM_TKT + 4 + 4 * wg), "r"(tk) : "memory");
      }
      __syncwarp();
      TL(2);
      wg_wait<1>(); fence_regs(k01); fence_regs(k23); fence_regs(q01); fence_regs(q23);
      TL(3);
      const float rk[8] = {rsq(k01[0]), rsq(k01[2]), rsq(k01[1]), rsq(k01[3]), rsq(k23[0]), rsq(k23[2]), rsq(k23[1]), rsq(k23[3])};
      scale_heads(ka, rk);
#pragma unroll
      for (int i = 0; i < 6; i++) stsm4(k_dst + (i + (i >= 3)) * 1024, ka[2 * i], ka[2 * i + 1], ka[12 + 2 * i], ka[12 + 2 * i + 1]);
      TL(4);
      wg_wait<0>(); fence_regs(vv);
      TL(5);
#pragma unroll
      for (int i = 0; i < 6; i++)
        stsm4(k_dst + (WG_V - WG_K) + (i + (i >= 3)) * 1024, pack_bf16(vv[4 * i], vv[4 * i + 1]), pack_bf16(vv[4 * i + 2], vv[4 * i + 3]),
              pack_bf16(vv[24 + 4 * i], vv[24 + 4 * i + 1]), pack_bf16(vv[24 + 4 * i + 2], vv[24 + 4 * i + 3]));
      const float s0 = __uint_as_float(qs.x), s1 = __uint_as_float(qs.y), s2 = __uint_as_float(qs.z), s3 = __uint_as_float(qs.w);
      const float rq[8] = {rsq(q01[0]) * s0, rsq(q01[2]) * s0, rsq(q01[1]) * s1, rsq(q01[3]) * s1,
                           rsq(q23[0]) * s2, rsq(q23[2]) * s2, rsq(q23[1]) * s3, rsq(q23[3]) * s3};
      scale_heads(qa, rq);
    }
    fence_async();
    const bool general = bar_wg_or(BAR_KV + wg, ((mword & 0x7FFF7FFFu) | slow_heads) != 0u);
    TL(6);
    const uint64_t dK = opaque(mk_desc(WG_K, 1024, 128, 0) + zw), dV = opaque(mk_desc(WG_V, 128, 1024, 0) + zw);
    auto prefetch_next = [&]() {
      if (warp == 0 && more) {
        if (elect_one()) {
          load_x(nxt, wg);
          if ((int)lds32(wl + 80) >= 0) prefetch_l2(mb + lds32(wl + 84), 8192);
        }
        __syncwarp();
      }
    };

    const uint32_t tk = lds32(sb + SM_TKT + 4 + 4 * wg);
    auto wait_turn = [&]() { mbar_wait(mbar + MB_TURN + (tk & 3) * 8, (tk >> 2) & 1); };
    auto pass_turn = [&]() { if (elect_one()) mbar_arrive(mbar + MB_TURN + ((tk + 1) & 3) * 8); __syncwarp(); };
    uint32_t of[24];
    if (__builtin_expect(!general, 1)) {
      float sA[32], sB[32], oA[16], oB[16], oC[16], oD[16];
      uint32_t pA[16], pB[16], pC[16], pD[16];
      wg_fence();
      issue_s<0>(sA, qa, dK);
      issue_s<1>(sB, qa, dK); wg_commit();
      load_eb(pA, eb_base);
      prefetch_next();
      wait_turn();
      wg_wait<0>(); fence_regs(sA); fence_regs(sB);
      TL(7);
      load_eb(pB, eb_base + 8192);
      softmax_fast(sA, pA);
      wg_fence();
      issue_s<2>(sA, qa, dK); wg_commit();
      issue_pv<0>(oA, pA, dV); wg_commit();
      TL(8);
      softmax_fast(sB, pB);
      load_eb(pC, eb_base + 2 * 8192);
      wg_wait<1>(); fence_regs(sA);
      wg_fence();
      issue_s<3>(sB, qa, dK); wg_commit();
      issue_pv<1>(oB, pB, dV); wg_commit();
      TL(9);
      softmax_fast(sA, pC);
      pass_turn();
      load_eb(pD, eb_base + 3 * 8192);
      wg_wait<1>(); fence_regs(sB); fence_regs(oA);
      wg_fence();
      issue_pv<2>(oC, pC, dV); wg_commit();
      TL(10);
      norm_o<0>(oA, of);
      softmax_fast(sB, pD);
      wg_fence();
      issue_pv<3>(oD, pD, dV); wg_commit();
      wg_wait<1>(); fence_regs(oB); fence_regs(oC);
      norm_o<1>(oB, of + 6);
      norm_o<0>(oC, of + 12);
      wg_wait<0>(); fence_regs(oD);
      norm_o<1>(oD, of + 18);
    } else {
      uint32_t mk[16], em[16];
      const int g = lane >> 2, t = lane & 3;
      const char* mrow = mb + (lds32(wl + 20) + (orig_tok(16 * warp + g) * 64 + (t >> 1) * 8 + (t & 1) * 2) * 2);
#pragma unroll
      for (int Gk = 0; Gk < 8; Gk++) {
        mk[2 * Gk] = *reinterpret_cast<const uint32_t*>(mrow + ((Gk & 3) * 16 + (Gk >> 2) * 4) * 2);
        mk[2 * Gk + 1] = *reinterpret_cast<const uint32_t*>(mrow + (16 * 64 + (Gk & 3) * 16 + (Gk >> 2) * 4) * 2);
      }
      prefetch_next();
      wait_turn();
      pass_turn();
      uint32_t x0 = mk[0], x1 = mk[1];
#pragma unroll
      for (int i = 0; i < 16; i++) {
        em[i] = pack_bf16(ex2(bf_lo(mk[i]) * LOG2E), ex2(bf_hi(mk[i]) * LOG2E));
        if (i & 1) x1 = hmax2_nan(x1, mk[i]); else x0 = hmax2_nan(x0, mk[i]);
      }
      const bool nan_in = !(bf_lo(x0) == bf_lo(x0) && bf_hi(x0) == bf_hi(x0) && bf_lo(x1) == bf_lo(x1) && bf_hi(x1) == bf_hi(x1));
      const float r0 = quad_max(fmaxf(bf_lo(x0), bf_hi(x0))), r1 = quad_max(fmaxf(bf_lo(x1), bf_hi(x1)));
      const bool unsafe = bar_wg_or(BAR_AUX + wg, nan_in || !(fabsf(r0) <= 8.f && fabsf(r1) <= 8.f));
      const uint32_t tm = unsafe ? 0xFu : slow_heads;
#pragma unroll
      for (int i = 0; i < 24; i++) of[i] = 0;
#pragma unroll 1
      for (int h = 0; h < 4; h++) {
        float sc[32], o[16]; uint32_t p[16];
        TL(7 + h);
        const uint32_t po = (h * 3 + (h >> 1)) * 64;
        wg_fence(); issue_s<0>(sc, qa, dK + po); wg_commit();
        load_eb(p, eb_base + h * 8192);
        const bool tmax = (tm >> h) & 1;
        if (!tmax) {
#pragma unroll
          for (int i = 0; i < 16; i++) p[i] = hmul2(p[i], em[i]);
        }
        wg_wait<0>(); fence_regs(sc);
        if (tmax) softmax_true_max(sc, p, mk); else softmax_fast(sc, p);
        wg_fence(); issue_pv<0>(o, p, dV + po); wg_commit();
#pragma unroll
        for (int i = 0; i < 20; i++) qa[i] = (h & 1) ? (i < 16 ? qa[i + 8] : 0u) : qa[i + 4];
#pragma unroll
        for (int i = 0; i < 18; i++) of[i] = of[i + 6];
        wg_wait<0>(); fence_regs(o);
        if (h & 1) norm_o<1>(o, of + 18); else norm_o<0>(o, of + 18);
      }
    }
    TL(11);

    float y[48];
    {
      const uint64_t dWo = opaque(mk_desc(sb + SM_WO, 128, 1536, 0) + z0);
      wg_fence();
#pragma unroll
      for (int s = 0; s < 6; s++) {
        if (s == 0) wgmma_rs_n96_t1<0>(y, of[0], of[1], of[2], of[3], dWo);
        else wgmma_rs_n96_t1<1>(y, of[4 * s], of[4 * s + 1], of[4 * s + 2], of[4 * s + 3], dWo + s * 16);
      }
      wg_commit();
    }
    char* const optr = reinterpret_cast<char*>(out) + (lds32(wl + 4 * warp) + lds32(sb + SM_LANE + ((t16 >> 2) & 124)));
    uint32_t yb[24];
    float var[4];
    auto ln_head = [&]() {
      uint32_t sy[8];
      wg_wait<0>(); fence_regs(y);
      TL(12);
      pack_sumsq(y, yb, sy, 0u);
      wg_fence();
      wgmma_rs_n8_t0<0>(var, sy[0], sy[1], sy[2], sy[3], dV + 3 * 64);
      wgmma_rs_n8_t0<1>(var, sy[4], sy[5], sy[6], sy[7], dV + 3 * 64);
      wg_commit();
    };
    auto ln_tail = [&]() {
      fence_regs(var);
      TL(13);
      uint32_t last;
      const uint32_t nn = pack_bf16(rsq(fmaf(var[0], 1.f / 96.f, 1e-5f)), rsq(fmaf(var[2], 1.f / 96.f, 1e-5f)));
#pragma unroll
      for (int j = 0; j < 3; j++) {
        stg128(optr + j * 64, hmul2_b<0>(yb[8 * j], nn), hmul2_b<0>(yb[8 * j + 2], nn), hmul2_b<0>(yb[8 * j + 4], nn), hmul2_b<0>(yb[8 * j + 6], nn));
        last = hmul2_b<1>(yb[8 * j + 7], nn);
        stg128(optr + 2 * ROWB + j * 64, hmul2_b<1>(yb[8 * j + 1], nn), hmul2_b<1>(yb[8 * j + 3], nn), hmul2_b<1>(yb[8 * j + 5], nn), last);
      }
      return last;
    };
    if (!more) { ln_head(); wg_wait<0>(); ln_tail(); TL(14); break; }
    load_mask(lds32(wl + 52));
    if (elect_one()) mbar_arrive(bar_x + (MB_KV - MB_X));
    __syncwarp();
    mbar_wait(bar_x, xphase ^ 1);
    mbar_wait(bar_x + (MB_KV - MB_X), xphase);
    xphase ^= 1;
    ln_head();
    issue_qk(qk, dX, opaque(mk_desc(sb + SM_W, 12288, 1024, 1) + z0)); wg_commit();
    wg_wait<1>();
    mword = mask_or(ln_tail());
    TL(14);
    wl += 32;
  }
  TG(15);
}

typedef CUresult (*EncodeFn)(CUtensorMap*, CUtensorMapDataType, cuuint32_t, void*, const cuuint64_t*, const cuuint64_t*,
                             const cuuint32_t*, const cuuint32_t*, CUtensorMapInterleave, CUtensorMapSwizzle,
                             CUtensorMapL2promotion, CUtensorMapFloatOOBfill);

}

extern "C" void kernel_launch(void* const* d_in, const int* in_sizes, int n_in, void* d_out, int out_size) {
  static int sms = 0;
  static EncodeFn encode = nullptr;
  if (sms == 0) {
    int dev = 0;
    cudaGetDevice(&dev);
    cudaDeviceGetAttribute(&sms, cudaDevAttrMultiProcessorCount, dev);
    cudaFuncSetAttribute(swin_kernel, cudaFuncAttributeMaxDynamicSharedMemorySize, SM_TOTAL);
    cudaDriverEntryPointQueryResult qr;
    void* fn = nullptr;
    cudaGetDriverEntryPoint("cuTensorMapEncodeTiled", &fn, cudaEnableDefault, &qr);
    encode = (EncodeFn)fn;
  }
  CUtensorMap tm_x, tm_xq, tm_wqk, tm_wv;
  {
    cuuint64_t dims[5] = {32, 4, IMG, IMG / 4, 3};
    cuuint64_t strides[4] = {PIXB, ROWB, 4 * PIXB, 64};
    cuuint32_t es[5] = {1, 1, 1, 1, 1};
    cuuint32_t box[5] = {32, 4, 8, 2, 3}, boxq[5] = {32, 4, 4, 1, 1};
    encode(&tm_x, CU_TENSOR_MAP_DATA_TYPE_BFLOAT16, 5, d_in[0], dims, strides, box, es, CU_TENSOR_MAP_INTERLEAVE_NONE,
           CU_TENSOR_MAP_SWIZZLE_64B, CU_TENSOR_MAP_L2_PROMOTION_L2_128B, CU_TENSOR_MAP_FLOAT_OOB_FILL_NONE);
    encode(&tm_xq, CU_TENSOR_MAP_DATA_TYPE_BFLOAT16, 5, d_in[0], dims, strides, boxq, es, CU_TENSOR_MAP_INTERLEAVE_NONE,
           CU_TENSOR_MAP_SWIZZLE_64B, CU_TENSOR_MAP_L2_PROMOTION_L2_128B, CU_TENSOR_MAP_FLOAT_OOB_FILL_NONE);
    cuuint64_t qd[3] = {64, 96, 3}, qs[2] = {576, 128}, vd[3] = {32, 96, 3}, vs[2] = {576, 64};
    cuuint32_t qb[3] = {64, 96, 3}, vb[3] = {32, 96, 3};
    encode(&tm_wqk, CU_TENSOR_MAP_DATA_TYPE_BFLOAT16, 3, d_in[1], qd, qs, qb, es, CU_TENSOR_MAP_INTERLEAVE_NONE,
           CU_TENSOR_MAP_SWIZZLE_128B, CU_TENSOR_MAP_L2_PROMOTION_L2_256B, CU_TENSOR_MAP_FLOAT_OOB_FILL_NONE);
    encode(&tm_wv, CU_TENSOR_MAP_DATA_TYPE_BFLOAT16, 3, (char*)d_in[1] + 384, vd, vs, vb, es, CU_TENSOR_MAP_INTERLEAVE_NONE,
           CU_TENSOR_MAP_SWIZZLE_64B, CU_TENSOR_MAP_L2_PROMOTION_L2_256B, CU_TENSOR_MAP_FLOAT_OOB_FILL_NONE);
  }
  swin_kernel<<<sms, 384, SM_TOTAL>>>(
      tm_x, tm_xq, tm_wqk, tm_wv, (const __nv_bfloat16*)d_in[2], (const __nv_bfloat16*)d_in[3],
      (const __nv_bfloat16*)d_in[4], (const __nv_bfloat16*)d_in[5], (const __nv_bfloat16*)d_in[6], (const int*)d_in[7],
      (const __nv_bfloat16*)d_in[8], (__nv_bfloat16*)d_out);
}
```

```cpp
#include <cuda_runtime.h>
#include <cuda.h>
#include <cuda_bf16.h>
#include <stdint.h>
#include <type_traits>

#define TOKEN 3
namespace {

constexpr int IMG   = 384;
constexpr int NWX   = 48;
constexpr int NWIN  = NWX * NWX;
constexpr int PIXB  = 192;
constexpr int ROWB  = IMG * PIXB;
constexpr float LOG2E = 1.4426950408889634f;
constexpr float TAU_FAST_MAX = 50.f;

constexpr int SM_W    = 0;
constexpr int SM_WV   = 3 * 12288;
constexpr int SM_WO   = SM_W + 9 * 6144;
constexpr int SM_EB   = SM_WO + 12 * 1536;
constexpr int SM_WG   = SM_EB + 32768;
constexpr int WG_X    = 0;
constexpr int WG_K    = 12288;
constexpr int WG_V    = WG_K + 14336;
constexpr int WG_SZ   = WG_V + 14336;
constexpr int SM_TAB  = SM_WG + WG_SZ + WG_V + 4096;
constexpr int SM_WOR  = SM_WG + WG_K;
constexpr int SM_SEL  = SM_WG + 3 * WG_SZ;
constexpr int SM_MISC = SM_SEL + 256;
constexpr int SM_BAR  = SM_MISC + 16;
constexpr int SM_TKT  = SM_BAR + 104;
constexpr int SM_PAR  = SM_BAR + 160;
constexpr int SM_LANE = SM_PAR + 192;
constexpr int NENT    = 16;
constexpr int SM_WIN  = (SM_LANE + 128 + 63) / 64 * 64;
constexpr int SM_TOTAL = SM_WIN + 3 * NENT * 32;

template <int SD> __device__ __forceinline__ void wgmma_ss_n192_t1(float (&d)[96], uint64_t da, uint64_t db) {
  if constexpr (SD) {
    asm volatile("{\n.reg .pred p;\nsetp.ne.b32 p, 1, 0;\n"
      "wgmma.mma_async.sync.aligned.m64n192k16.f32.bf16.bf16 {%0, %1, %2, %3, %4, %5, %6, %7, %8, %9, %10, %11, %12, %13, %14, %15, %16, %17, %18, %19, %20, %21, %22, %23, %24, %25, %26, %27, %28, %29, %30, %31, %32, %33, %34, %35, %36, %37, %38, %39, %40, %41, %42, %43, %44, %45, %46, %47, %48, %49, %50, %51, %52, %53, %54, %55, %56, %57, %58, %59, %60, %61, %62, %63, %64, %65, %66, %67, %68, %69, %70, %71, %72, %73, %74, %75, %76, %77, %78, %79, %80, %81, %82, %83, %84, %85, %86, %87, %88, %89, %90, %91, %92, %93, %94, %95}, %96, %97, p, 1, 1, 0, 1;\n}\n"
      : "+f"(d[0]), "+f"(d[1]), "+f"(d[2]), "+f"(d[3]), "+f"(d[4]), "+f"(d[5]), "+f"(d[6]), "+f"(d[7]), "+f"(d[8]), "+f"(d[9]), "+f"(d[10]), "+f"(d[11]), "+f"(d[12]), "+f"(d[13]), "+f"(d[14]), "+f"(d[15]), "+f"(d[16]), "+f"(d[17]), "+f"(d[18]), "+f"(d[19]), "+f"(d[20]), "+f"(d[21]), "+f"(d[22]), "+f"(d[23]), "+f"(d[24]), "+f"(d[25]), "+f"(d[26]), "+f"(d[27]), "+f"(d[28]), "+f"(d[29]), "+f"(d[30]), "+f"(d[31]), "+f"(d[32]), "+f"(d[33]), "+f"(d[34]), "+f"(d[35]), "+f"(d[36]), "+f"(d[37]), "+f"(d[38]), "+f"(d[39]), "+f"(d[40]), "+f"(d[41]), "+f"(d[42]), "+f"(d[43]), "+f"(d[44]), "+f"(d[45]), "+f"(d[46]), "+f"(d[47]), "+f"(d[48]), "+f"(d[49]), "+f"(d[50]), "+f"(d[51]), "+f"(d[52]), "+f"(d[53]), "+f"(d[54]), "+f"(d[55]), "+f"(d[56]), "+f"(d[57]), "+f"(d[58]), "+f"(d[59]), "+f"(d[60]), "+f"(d[61]), "+f"(d[62]), "+f"(d[63]), "+f"(d[64]), "+f"(d[65]), "+f"(d[66]), "+f"(d[67]), "+f"(d[68]), "+f"(d[69]), "+f"(d[70]), "+f"(d[71]), "+f"(d[72]), "+f"(d[73]), "+f"(d[74]), "+f"(d[75]), "+f"(d[76]), "+f"(d[77]), "+f"(d[78]), "+f"(d[79]), "+f"(d[80]), "+f"(d[81]), "+f"(d[82]), "+f"(d[83]), "+f"(d[84]), "+f"(d[85]), "+f"(d[86]), "+f"(d[87]), "+f"(d[88]), "+f"(d[89]), "+f"(d[90]), "+f"(d[91]), "+f"(d[92]), "+f"(d[93]), "+f"(d[94]), "+f"(d[95])
      : "l"(da), "l"(db));
  } else {
    asm volatile("{\n.reg .pred p;\nsetp.ne.b32 p, 0, 0;\n"
      "wgmma.mma_async.sync.aligned.m64n192k16.f32.bf16.bf16 {%0, %1, %2, %3, %4, %5, %6, %7, %8, %9, %10, %11, %12, %13, %14, %15, %16, %17, %18, %19, %20, %21, %22, %23, %24, %25, %26, %27, %28, %29, %30, %31, %32, %33, %34, %35, %36, %37, %38, %39, %40, %41, %42, %43, %44, %45, %46, %47, %48, %49, %50, %51, %52, %53, %54, %55, %56, %57, %58, %59, %60, %61, %62, %63, %64, %65, %66, %67, %68, %69, %70, %71, %72, %73, %74, %75, %76, %77, %78, %79, %80, %81, %82, %83, %84, %85, %86, %87, %88, %89, %90, %91, %92, %93, %94, %95}, %96, %97, p, 1, 1, 0, 1;\n}\n"
      : "=f"(d[0]), "=f"(d[1]), "=f"(d[2]), "=f"(d[3]), "=f"(d[4]), "=f"(d[5]), "=f"(d[6]), "=f"(d[7]), "=f"(d[8]), "=f"(d[9]), "=f"(d[10]), "=f"(d[11]), "=f"(d[12]), "=f"(d[13]), "=f"(d[14]), "=f"(d[15]), "=f"(d[16]), "=f"(d[17]), "=f"(d[18]), "=f"(d[19]), "=f"(d[20]), "=f"(d[21]), "=f"(d[22]), "=f"(d[23]), "=f"(d[24]), "=f"(d[25]), "=f"(d[26]), "=f"(d[27]), "=f"(d[28]), "=f"(d[29]), "=f"(d[30]), "=f"(d[31]), "=f"(d[32]), "=f"(d[33]), "=f"(d[34]), "=f"(d[35]), "=f"(d[36]), "=f"(d[37]), "=f"(d[38]), "=f"(d[39]), "=f"(d[40]), "=f"(d[41]), "=f"(d[42]), "=f"(d[43]), "=f"(d[44]), "=f"(d[45]), "=f"(d[46]), "=f"(d[47]), "=f"(d[48]), "=f"(d[49]), "=f"(d[50]), "=f"(d[51]), "=f"(d[52]), "=f"(d[53]), "=f"(d[54]), "=f"(d[55]), "=f"(d[56]), "=f"(d[57]), "=f"(d[58]), "=f"(d[59]), "=f"(d[60]), "=f"(d[61]), "=f"(d[62]), "=f"(d[63]), "=f"(d[64]), "=f"(d[65]), "=f"(d[66]), "=f"(d[67]), "=f"(d[68]), "=f"(d[69]), "=f"(d[70]), "=f"(d[71]), "=f"(d[72]), "=f"(d[73]), "=f"(d[74]), "=f"(d[75]), "=f"(d[76]), "=f"(d[77]), "=f"(d[78]), "=f"(d[79]), "=f"(d[80]), "=f"(d[81]), "=f"(d[82]), "=f"(d[83]), "=f"(d[84]), "=f"(d[85]), "=f"(d[86]), "=f"(d[87]), "=f"(d[88]), "=f"(d[89]), "=f"(d[90]), "=f"(d[91]), "=f"(d[92]), "=f"(d[93]), "=f"(d[94]), "=f"(d[95])
      : "l"(da), "l"(db));
  }
}
template <int SD> __device__ __forceinline__ void wgmma_ss_n96_t1(float (&d)[48], uint64_t da, uint64_t db) {
  if constexpr (SD) {
    asm volatile("{\n.reg .pred p;\nsetp.ne.b32 p, 1, 0;\n"
      "wgmma.mma_async.sync.aligned.m64n96k16.f32.bf16.bf16 {%0, %1, %2, %3, %4, %5, %6, %7, %8, %9, %10, %11, %12, %13, %14, %15, %16, %17, %18, %19, %20, %21, %22, %23, %24, %25, %26, %27, %28, %29, %30, %31, %32, %33, %34, %35, %36, %37, %38, %39, %40, %41, %42, %43, %44, %45, %46, %47}, %48, %49, p, 1, 1, 0, 1;\n}\n"
      : "+f"(d[0]), "+f"(d[1]), "+f"(d[2]), "+f"(d[3]), "+f"(d[4]), "+f"(d[5]), "+f"(d[6]), "+f"(d[7]), "+f"(d[8]), "+f"(d[9]), "+f"(d[10]), "+f"(d[11]), "+f"(d[12]), "+f"(d[13]), "+f"(d[14]), "+f"(d[15]), "+f"(d[16]), "+f"(d[17]), "+f"(d[18]), "+f"(d[19]), "+f"(d[20]), "+f"(d[21]), "+f"(d[22]), "+f"(d[23]), "+f"(d[24]), "+f"(d[25]), "+f"(d[26]), "+f"(d[27]), "+f"(d[28]), "+f"(d[29]), "+f"(d[30]), "+f"(d[31]), "+f"(d[32]), "+f"(d[33]), "+f"(d[34]), "+f"(d[35]), "+f"(d[36]), "+f"(d[37]), "+f"(d[38]), "+f"(d[39]), "+f"(d[40]), "+f"(d[41]), "+f"(d[42]), "+f"(d[43]), "+f"(d[44]), "+f"(d[45]), "+f"(d[46]), "+f"(d[47])
      : "l"(da), "l"(db));
  } else {
    asm volatile("{\n.reg .pred p;\nsetp.ne.b32 p, 0, 0;\n"
      "wgmma.mma_async.sync.aligned.m64n96k16.f32.bf16.bf16 {%0, %1, %2, %3, %4, %5, %6, %7, %8, %9, %10, %11, %12, %13, %14, %15, %16, %17, %18, %19, %20, %21, %22, %23, %24, %25, %26, %27, %28, %29, %30, %31, %32, %33, %34, %35, %36, %37, %38, %39, %40, %41, %42, %43, %44, %45, %46, %47}, %48, %49, p, 1, 1, 0, 1;\n}\n"
      : "=f"(d[0]), "=f"(d[1]), "=f"(d[2]), "=f"(d[3]), "=f"(d[4]), "=f"(d[5]), "=f"(d[6]), "=f"(d[7]), "=f"(d[8]), "=f"(d[9]), "=f"(d[10]), "=f"(d[11]), "=f"(d[12]), "=f"(d[13]), "=f"(d[14]), "=f"(d[15]), "=f"(d[16]), "=f"(d[17]), "=f"(d[18]), "=f"(d[19]), "=f"(d[20]), "=f"(d[21]), "=f"(d[22]), "=f"(d[23]), "=f"(d[24]), "=f"(d[25]), "=f"(d[26]), "=f"(d[27]), "=f"(d[28]), "=f"(d[29]), "=f"(d[30]), "=f"(d[31]), "=f"(d[32]), "=f"(d[33]), "=f"(d[34]), "=f"(d[35]), "=f"(d[36]), "=f"(d[37]), "=f"(d[38]), "=f"(d[39]), "=f"(d[40]), "=f"(d[41]), "=f"(d[42]), "=f"(d[43]), "=f"(d[44]), "=f"(d[45]), "=f"(d[46]), "=f"(d[47])
      : "l"(da), "l"(db));
  }
}
template <int SD> __device__ __forceinline__ void wgmma_rs_n96_t1(float (&d)[48], uint32_t a0, uint32_t a1, uint32_t a2, uint32_t a3, uint64_t db) {
  if constexpr (SD) {
    asm volatile("{\n.reg .pred p;\nsetp.ne.b32 p, 1, 0;\n"
      "wgmma.mma_async.sync.aligned.m64n96k16.f32.bf16.bf16 {%0, %1, %2, %3, %4, %5, %6, %7, %8, %9, %10, %11, %12, %13, %14, %15, %16, %17, %18, %19, %20, %21, %22, %23, %24, %25, %26, %27, %28, %29, %30, %31, %32, %33, %34, %35, %36, %37, %38, %39, %40, %41, %42, %43, %44, %45, %46, %47}, {%48, %49, %50, %51}, %52, p, 1, 1, 1;\n}\n"
      : "+f"(d[0]), "+f"(d[1]), "+f"(d[2]), "+f"(d[3]), "+f"(d[4]), "+f"(d[5]), "+f"(d[6]), "+f"(d[7]), "+f"(d[8]), "+f"(d[9]), "+f"(d[10]), "+f"(d[11]), "+f"(d[12]), "+f"(d[13]), "+f"(d[14]), "+f"(d[15]), "+f"(d[16]), "+f"(d[17]), "+f"(d[18]), "+f"(d[19]), "+f"(d[20]), "+f"(d[21]), "+f"(d[22]), "+f"(d[23]), "+f"(d[24]), "+f"(d[25]), "+f"(d[26]), "+f"(d[27]), "+f"(d[28]), "+f"(d[29]), "+f"(d[30]), "+f"(d[31]), "+f"(d[32]), "+f"(d[33]), "+f"(d[34]), "+f"(d[35]), "+f"(d[36]), "+f"(d[37]), "+f"(d[38]), "+f"(d[39]), "+f"(d[40]), "+f"(d[41]), "+f"(d[42]), "+f"(d[43]), "+f"(d[44]), "+f"(d[45]), "+f"(d[46]), "+f"(d[47])
      : "r"(a0), "r"(a1), "r"(a2), "r"(a3), "l"(db));
  } else {
    asm volatile("{\n.reg .pred p;\nsetp.ne.b32 p, 0, 0;\n"
      "wgmma.mma_async.sync.aligned.m64n96k16.f32.bf16.bf16 {%0, %1, %2, %3, %4, %5, %6, %7, %8, %9, %10, %11, %12, %13, %14, %15, %16, %17, %18, %19, %20, %21, %22, %23, %24, %25, %26, %27, %28, %29, %30, %31, %32, %33, %34, %35, %36, %37, %38, %39, %40, %41, %42, %43, %44, %45, %46, %47}, {%48, %49, %50, %51}, %52, p, 1, 1, 1;\n}\n"
      : "=f"(d[0]), "=f"(d[1]), "=f"(d[2]), "=f"(d[3]), "=f"(d[4]), "=f"(d[5]), "=f"(d[6]), "=f"(d[7]), "=f"(d[8]), "=f"(d[9]), "=f"(d[10]), "=f"(d[11]), "=f"(d[12]), "=f"(d[13]), "=f"(d[14]), "=f"(d[15]), "=f"(d[16]), "=f"(d[17]), "=f"(d[18]), "=f"(d[19]), "=f"(d[20]), "=f"(d[21]), "=f"(d[22]), "=f"(d[23]), "=f"(d[24]), "=f"(d[25]), "=f"(d[26]), "=f"(d[27]), "=f"(d[28]), "=f"(d[29]), "=f"(d[30]), "=f"(d[31]), "=f"(d[32]), "=f"(d[33]), "=f"(d[34]), "=f"(d[35]), "=f"(d[36]), "=f"(d[37]), "=f"(d[38]), "=f"(d[39]), "=f"(d[40]), "=f"(d[41]), "=f"(d[42]), "=f"(d[43]), "=f"(d[44]), "=f"(d[45]), "=f"(d[46]), "=f"(d[47])
      : "r"(a0), "r"(a1), "r"(a2), "r"(a3), "l"(db));
  }
}
template <int SD> __device__ __forceinline__ void wgmma_rs_n64_t0(float (&d)[32], uint32_t a0, uint32_t a1, uint32_t a2, uint32_t a3, uint64_t db) {
  if constexpr (SD) {
    asm volatile("{\n.reg .pred p;\nsetp.ne.b32 p, 1, 0;\n"
      "wgmma.mma_async.sync.aligned.m64n64k16.f32.bf16.bf16 {%0, %1, %2, %3, %4, %5, %6, %7, %8, %9, %10, %11, %12, %13, %14, %15, %16, %17, %18, %19, %20, %21, %22, %23, %24, %25, %26, %27, %28, %29, %30, %31}, {%32, %33, %34, %35}, %36, p, 1, 1, 0;\n}\n"
      : "+f"(d[0]), "+f"(d[1]), "+f"(d[2]), "+f"(d[3]), "+f"(d[4]), "+f"(d[5]), "+f"(d[6]), "+f"(d[7]), "+f"(d[8]), "+f"(d[9]), "+f"(d[10]), "+f"(d[11]), "+f"(d[12]), "+f"(d[13]), "+f"(d[14]), "+f"(d[15]), "+f"(d[16]), "+f"(d[17]), "+f"(d[18]), "+f"(d[19]), "+f"(d[20]), "+f"(d[21]), "+f"(d[22]), "+f"(d[23]), "+f"(d[24]), "+f"(d[25]), "+f"(d[26]), "+f"(d[27]), "+f"(d[28]), "+f"(d[29]), "+f"(d[30]), "+f"(d[31])
      : "r"(a0), "r"(a1), "r"(a2), "r"(a3), "l"(db));
  } else {
    asm volatile("{\n.reg .pred p;\nsetp.ne.b32 p, 0, 0;\n"
      "wgmma.mma_async.sync.aligned.m64n64k16.f32.bf16.bf16 {%0, %1, %2, %3, %4, %5, %6, %7, %8, %9, %10, %11, %12, %13, %14, %15, %16, %17, %18, %19, %20, %21, %22, %23, %24, %25, %26, %27, %28, %29, %30, %31}, {%32, %33, %34, %35}, %36, p, 1, 1, 0;\n}\n"
      : "=f"(d[0]), "=f"(d[1]), "=f"(d[2]), "=f"(d[3]), "=f"(d[4]), "=f"(d[5]), "=f"(d[6]), "=f"(d[7]), "=f"(d[8]), "=f"(d[9]), "=f"(d[10]), "=f"(d[11]), "=f"(d[12]), "=f"(d[13]), "=f"(d[14]), "=f"(d[15]), "=f"(d[16]), "=f"(d[17]), "=f"(d[18]), "=f"(d[19]), "=f"(d[20]), "=f"(d[21]), "=f"(d[22]), "=f"(d[23]), "=f"(d[24]), "=f"(d[25]), "=f"(d[26]), "=f"(d[27]), "=f"(d[28]), "=f"(d[29]), "=f"(d[30]), "=f"(d[31])
      : "r"(a0), "r"(a1), "r"(a2), "r"(a3), "l"(db));
  }
}
template <int SD> __device__ __forceinline__ void wgmma_rs_n32_t1(float (&d)[16], uint32_t a0, uint32_t a1, uint32_t a2, uint32_t a3, uint64_t db) {
  if constexpr (SD) {
    asm volatile("{\n.reg .pred p;\nsetp.ne.b32 p, 1, 0;\n"
      "wgmma.mma_async.sync.aligned.m64n32k16.f32.bf16.bf16 {%0, %1, %2, %3, %4, %5, %6, %7, %8, %9, %10, %11, %12, %13, %14, %15}, {%16, %17, %18, %19}, %20, p, 1, 1, 1;\n}\n"
      : "+f"(d[0]), "+f"(d[1]), "+f"(d[2]), "+f"(d[3]), "+f"(d[4]), "+f"(d[5]), "+f"(d[6]), "+f"(d[7]), "+f"(d[8]), "+f"(d[9]), "+f"(d[10]), "+f"(d[11]), "+f"(d[12]), "+f"(d[13]), "+f"(d[14]), "+f"(d[15])
      : "r"(a0), "r"(a1), "r"(a2), "r"(a3), "l"(db));
  } else {
    asm volatile("{\n.reg .pred p;\nsetp.ne.b32 p, 0, 0;\n"
      "wgmma.mma_async.sync.aligned.m64n32k16.f32.bf16.bf16 {%0, %1, %2, %3, %4, %5, %6, %7, %8, %9, %10, %11, %12, %13, %14, %15}, {%16, %17, %18, %19}, %20, p, 1, 1, 1;\n}\n"
      : "=f"(d[0]), "=f"(d[1]), "=f"(d[2]), "=f"(d[3]), "=f"(d[4]), "=f"(d[5]), "=f"(d[6]), "=f"(d[7]), "=f"(d[8]), "=f"(d[9]), "=f"(d[10]), "=f"(d[11]), "=f"(d[12]), "=f"(d[13]), "=f"(d[14]), "=f"(d[15])
      : "r"(a0), "r"(a1), "r"(a2), "r"(a3), "l"(db));
  }
}
template <int SD> __device__ __forceinline__ void wgmma_rs_n8_t0(float (&d)[4], uint32_t a0, uint32_t a1, uint32_t a2, uint32_t a3, uint64_t db) {
  if constexpr (SD) {
    asm volatile("{\n.reg .pred p;\nsetp.ne.b32 p, 1, 0;\n"
      "wgmma.mma_async.sync.aligned.m64n8k16.f32.bf16.bf16 {%0, %1, %2, %3}, {%4, %5, %6, %7}, %8, p, 1, 1, 0;\n}\n"
      : "+f"(d[0]), "+f"(d[1]), "+f"(d[2]), "+f"(d[3])
      : "r"(a0), "r"(a1), "r"(a2), "r"(a3), "l"(db));
  } else {
    asm volatile("{\n.reg .pred p;\nsetp.ne.b32 p, 0, 0;\n"
      "wgmma.mma_async.sync.aligned.m64n8k16.f32.bf16.bf16 {%0, %1, %2, %3}, {%4, %5, %6, %7}, %8, p, 1, 1, 0;\n}\n"
      : "=f"(d[0]), "=f"(d[1]), "=f"(d[2]), "=f"(d[3])
      : "r"(a0), "r"(a1), "r"(a2), "r"(a3), "l"(db));
  }
}

__device__ __forceinline__ void wg_fence()  { asm volatile("wgmma.fence.sync.aligned;" ::: "memory"); }
__device__ __forceinline__ void wg_commit() { asm volatile("wgmma.commit_group.sync.aligned;" ::: "memory"); }
template <int N> __device__ __forceinline__ void wg_wait() { asm volatile("wgmma.wait_group.sync.aligned %0;" :: "n"(N) : "memory"); }
template <int N> __device__ __forceinline__ void fence_regs(float (&d)[N]) {
#pragma unroll
  for (int i = 0; i < N; i++) asm volatile("" : "+f"(d[i]) :: "memory");
}
__device__ __forceinline__ constexpr uint64_t mk_desc(uint32_t addr, uint32_t lbo, uint32_t sbo, uint32_t swz) {
  return (uint64_t)(addr >> 4) | ((uint64_t)(lbo >> 4) << 16) | ((uint64_t)(sbo >> 4) << 32) | ((uint64_t)swz << 62);
}
__device__ __forceinline__ uint32_t pack_bf16(float lo, float hi) {
  uint32_t r; asm("cvt.rn.bf16x2.f32 %0, %1, %2;" : "=r"(r) : "f"(hi), "f"(lo)); return r;
}
__device__ __forceinline__ uint32_t hmul2(uint32_t a, uint32_t b) {
  uint32_t r; asm("mul.rn.bf16x2 %0, %1, %2;" : "=r"(r) : "r"(a), "r"(b)); return r;
}
template <int HI> __device__ __forceinline__ uint32_t hmul2_b(uint32_t a, uint32_t b) {
  uint32_t r;
  if (HI) asm("{\n.reg .b16 l, h;\n.reg .b32 t;\nmov.b32 {l, h}, %2;\nmov.b32 t, {h, h};\nmul.rn.bf16x2 %0, %1, t;\n}\n" : "=r"(r) : "r"(a), "r"(b));
  else    asm("{\n.reg .b16 l, h;\n.reg .b32 t;\nmov.b32 {l, h}, %2;\nmov.b32 t, {l, l};\nmul.rn.bf16x2 %0, %1, t;\n}\n" : "=r"(r) : "r"(a), "r"(b));
  return r;
}
__device__ __forceinline__ uint32_t hfma2(uint32_t a, uint32_t b, uint32_t c) {
  uint32_t r; asm("fma.rn.bf16x2 %0, %1, %2, %3;" : "=r"(r) : "r"(a), "r"(b), "r"(c)); return r;
}
__device__ __forceinline__ float ex2(float x) { float r; asm("ex2.approx.ftz.f32 %0, %1;" : "=f"(r) : "f"(x)); return r; }
__device__ __forceinline__ float rsq(float x) { float r; asm("rsqrt.approx.ftz.f32 %0, %1;" : "=f"(r) : "f"(x)); return r; }
__device__ __forceinline__ float rcp(float x) { float r; asm("rcp.approx.ftz.f32 %0, %1;" : "=f"(r) : "f"(x)); return r; }
__device__ __forceinline__ void stsm4(uint32_t addr, uint32_t r0, uint32_t r1, uint32_t r2, uint32_t r3) {
  asm volatile("stmatrix.sync.aligned.m8n8.x4.shared.b16 [%0], {%1,%2,%3,%4};" :: "r"(addr), "r"(r0), "r"(r1), "r"(r2), "r"(r3) : "memory");
}
__device__ __forceinline__ void fence_async() { asm volatile("fence.proxy.async.shared::cta;" ::: "memory"); }
__device__ __forceinline__ void bar_sync_n(int id, int n) { asm volatile("bar.sync %0, %1;" :: "r"(id), "r"(n) : "memory"); }
__device__ __forceinline__ void bar_arrive_n(int id, int n) { asm volatile("bar.arrive %0, %1;" :: "r"(id), "r"(n) : "memory"); }
__device__ __forceinline__ bool bar_wg_or(int id, bool v) {
  uint32_t r;
  asm volatile("{\n.reg .pred p, q;\nsetp.ne.u32 q, %2, 0;\nbar.red.or.pred p, %1, 128, q;\nselp.u32 %0, 1, 0, p;\n}\n"
               : "=r"(r) : "r"(id), "r"((uint32_t)v) : "memory");
  return r != 0;
}
__device__ __forceinline__ void mbar_init(uint32_t bar, uint32_t cnt) { asm volatile("mbarrier.init.shared::cta.b64 [%0], %1;" :: "r"(bar), "r"(cnt) : "memory"); }
__device__ __forceinline__ void mbar_expect(uint32_t bar, uint32_t bytes) {
  asm volatile("mbarrier.arrive.expect_tx.shared::cta.b64 _, [%0], %1;" :: "r"(bar), "r"(bytes) : "memory");
}
__device__ __forceinline__ void mbar_arrive(uint32_t bar) { asm volatile("mbarrier.arrive.shared::cta.b64 _, [%0];" :: "r"(bar) : "memory"); }
__device__ __forceinline__ void mbar_wait(uint32_t bar, uint32_t parity) {
  asm volatile("{\n.reg .pred p;\n.reg .u32 n;\nmov.u32 n, 0;\n"
               "LW_%=:\nmbarrier.try_wait.parity.shared::cta.b64 p, [%0], %1;\n@p bra.uni LD_%=;\n"
               "add.u32 n, n, 1;\nsetp.lt.u32 p, n, 4194304;\n@p bra.uni LW_%=;\ntrap;\nLD_%=:\n}\n"
               :: "r"(bar), "r"(parity) : "memory");
}
__device__ __forceinline__ void tma5(uint32_t dst, const CUtensorMap* m, uint32_t bar, int c0, int c1, int c2, int c3, int c4) {
  asm volatile("cp.async.bulk.tensor.5d.shared::cluster.global.mbarrier::complete_tx::bytes [%0], [%1, {%3, %4, %5, %6, %7}], [%2];"
               :: "r"(dst), "l"(m), "r"(bar), "r"(c0), "r"(c1), "r"(c2), "r"(c3), "r"(c4) : "memory");
}
__device__ __forceinline__ void tma3(uint32_t dst, const CUtensorMap* m, uint32_t bar, int c0, int c1, int c2) {
  asm volatile("cp.async.bulk.tensor.3d.shared::cluster.global.mbarrier::complete_tx::bytes [%0], [%1, {%3, %4, %5}], [%2];"
               :: "r"(dst), "l"(m), "r"(bar), "r"(c0), "r"(c1), "r"(c2) : "memory");
}
__device__ __forceinline__ void bulk_g2s(uint32_t dst, const void* src, uint32_t bytes, uint32_t bar) {
  asm volatile("cp.async.bulk.shared::cluster.global.mbarrier::complete_tx::bytes [%0], [%1], %2, [%3];"
               :: "r"(dst), "l"(src), "r"(bytes), "r"(bar) : "memory");
}
__device__ __forceinline__ uint32_t lds32(uint32_t addr) {
  uint32_t v; asm volatile("ld.shared.u32 %0, [%1];" : "=r"(v) : "r"(addr)); return v;
}
__device__ __forceinline__ uint64_t opaque(uint64_t v) { asm volatile("" : "+l"(v)); return v; }
__device__ __forceinline__ uint4 lds128(uint32_t addr) {
  uint4 v; asm volatile("ld.shared.v4.u32 {%0,%1,%2,%3}, [%4];" : "=r"(v.x), "=r"(v.y), "=r"(v.z), "=r"(v.w) : "r"(addr)); return v;
}
__device__ __forceinline__ void sts128(uint32_t addr, uint32_t a, uint32_t b, uint32_t c, uint32_t d) {
  asm volatile("st.shared.v4.u32 [%0], {%1,%2,%3,%4};" :: "r"(addr), "r"(a), "r"(b), "r"(c), "r"(d) : "memory");
}
__device__ __forceinline__ uint4 ldg128_stream(const void* p) {
  uint4 v; asm volatile("ld.global.nc.L1::no_allocate.v4.u32 {%0,%1,%2,%3}, [%4];" : "=r"(v.x), "=r"(v.y), "=r"(v.z), "=r"(v.w) : "l"(p)); return v;
}
__device__ __forceinline__ void stg128(void* p, uint32_t a, uint32_t b, uint32_t c, uint32_t d) {
  asm volatile("st.global.v4.u32 [%0], {%1,%2,%3,%4};" :: "l"(p), "r"(a), "r"(b), "r"(c), "r"(d) : "memory");
}
__device__ __forceinline__ void prefetch_l2(const void* p, uint32_t bytes) {
  asm volatile("cp.async.bulk.prefetch.L2.global [%0], %1;" :: "l"(p), "r"(bytes) : "memory");
}
__device__ __forceinline__ bool elect_one() {
  uint32_t r; asm volatile("{\n.reg .pred p;\nelect.sync _|p, 0xffffffff;\nselp.u32 %0, 1, 0, p;\n}\n" : "=r"(r)); return r != 0;
}
__device__ __forceinline__ float bf_lo(uint32_t u) { return __uint_as_float(u << 16); }
__device__ __forceinline__ float bf_hi(uint32_t u) { return __uint_as_float(u & 0xFFFF0000u); }
__device__ __forceinline__ float rbf(float x) { return bf_lo(pack_bf16(x, 0.f)); }
__device__ __forceinline__ int orig_tok(int r) { return ((r & 31) >> 2) * 8 + (r >> 5) * 4 + (r & 3); }

__device__ __forceinline__ int slot_window(int s, bool g132) {
  constexpr int A0 = 396 + 264 + 60, A1 = A0 + 72, B0 = 3 * 396 + 264 + 60, B1 = B0 + 23;
  const int i = s - (s >= B1 ? 95 : s >= A1 ? 72 : 0);
  const int k = s >= B0 ? s - B0 + 72 : s - A0;
  const bool border = (s >= A0 && s < A1) || (s >= B0 && s < B1);
  const int iy = (i * 2789) >> 17, sy = (s * 2731) >> 17;
  const int wa = border ? (k < 48 ? (47 << 8 | k) : ((k - 48) << 8 | 47)) : (iy << 8 | (i - iy * 47));
  return g132 ? wa : (sy << 8 | (s - sy * 48));
}

#define EB_WORD(e, j, a) ((((a) ^ ((j) & 1)) == 0) ? (e).x : (((a) ^ ((j) & 1)) == 1) ? (e).y : (((a) ^ ((j) & 1)) == 2) ? (e).z : (e).w)

__device__ __forceinline__ void load_eb(uint32_t (&e)[16], uint32_t eb_addr) {
#pragma unroll
  for (int j = 0; j < 4; j++) {
    const uint4 v = lds128(eb_addr + j * 2048);
#pragma unroll
    for (int a = 0; a < 4; a++) e[4 * j + a] = EB_WORD(v, j, a);
  }
}
__device__ __forceinline__ void softmax_fast(const float (&s)[32], uint32_t (&p)[16]) {
#pragma unroll
  for (int i = 0; i < 16; i++) p[i] = hmul2(pack_bf16(ex2(s[2 * i]), ex2(s[2 * i + 1])), p[i]);
}
__device__ __forceinline__ uint32_t hmax2(uint32_t a, uint32_t b) {
  uint32_t r; asm("max.bf16x2 %0, %1, %2;" : "=r"(r) : "r"(a), "r"(b)); return r;
}
__device__ __forceinline__ uint32_t hmax2_nan(uint32_t a, uint32_t b) {
  uint32_t r; asm("max.NaN.bf16x2 %0, %1, %2;" : "=r"(r) : "r"(a), "r"(b)); return r;
}
__device__ __forceinline__ float quad_max(float m) {
  m = fmaxf(m, __shfl_xor_sync(0xffffffffu, m, 1));
  return fmaxf(m, __shfl_xor_sync(0xffffffffu, m, 2));
}
__device__ __forceinline__ void softmax_true_max(const float (&s)[32], uint32_t (&p)[16]) {
  float m0 = s[0], m1 = s[2];
#pragma unroll
  for (int g = 0; g < 8; g++) {
    m0 = fmaxf(m0, fmaxf(s[4 * g + 0], s[4 * g + 1]));
    m1 = fmaxf(m1, fmaxf(s[4 * g + 2], s[4 * g + 3]));
  }
  m0 = quad_max(m0); m1 = quad_max(m1);
  uint32_t n0 = 0, n1 = 0;
#pragma unroll
  for (int g = 0; g < 8; g++) {
    p[2 * g + 0] = hmul2(pack_bf16(ex2(s[4 * g + 0] - m0), ex2(s[4 * g + 1] - m0)), p[2 * g + 0]);
    p[2 * g + 1] = hmul2(pack_bf16(ex2(s[4 * g + 2] - m1), ex2(s[4 * g + 3] - m1)), p[2 * g + 1]);
    n0 = hmax2(n0, p[2 * g]); n1 = hmax2(n1, p[2 * g + 1]);
  }
  const uint32_t r = pack_bf16(rcp(quad_max(fmaxf(bf_lo(n0), bf_hi(n0)))), rcp(quad_max(fmaxf(bf_lo(n1), bf_hi(n1)))));
#pragma unroll
  for (int g = 0; g < 8; g++) { p[2 * g] = hmul2_b<0>(p[2 * g], r); p[2 * g + 1] = hmul2_b<1>(p[2 * g + 1], r); }
}
template <bool GEN> __device__ __forceinline__ void softmax_head(float (&s)[32], uint32_t (&p)[16], bool masked, bool tmax, uint32_t scr) {
  if (!GEN) { softmax_fast(s, p); return; }
  if (!tmax) {
    if (masked) {
#pragma unroll
      for (int j = 0; j < 4; j++) {
        const uint4 m = lds128(scr + j * 2048);
        p[4 * j] = hmul2(p[4 * j], m.x); p[4 * j + 1] = hmul2(p[4 * j + 1], m.y);
        p[4 * j + 2] = hmul2(p[4 * j + 2], m.z); p[4 * j + 3] = hmul2(p[4 * j + 3], m.w);
      }
    }
    softmax_fast(s, p);
  } else {
    if (masked) {
#pragma unroll
      for (int j = 0; j < 4; j++) {
        const uint4 m = lds128(scr + j * 2048);
        const uint32_t w[4] = {m.x, m.y, m.z, m.w};
#pragma unroll
        for (int a = 0; a < 4; a++) {
          s[8 * j + 2 * a] = fmaf(bf_lo(w[a]), LOG2E, s[8 * j + 2 * a]);
          s[8 * j + 2 * a + 1] = fmaf(bf_hi(w[a]), LOG2E, s[8 * j + 2 * a + 1]);
        }
      }
    }
    softmax_true_max(s, p);
  }
}
template <int H> __device__ __forceinline__ void issue_s(float (&s)[32], const uint32_t (&q)[24], uint64_t dK) {
  constexpr int Q0 = (H == 0 ? 0 : H == 1 ? 4 : H == 2 ? 12 : 16), P0 = (H == 0 ? 0 : H == 1 ? 3 : H == 2 ? 7 : 10);
  wgmma_rs_n64_t0<0>(s, q[Q0], q[Q0 + 1], q[Q0 + 2], q[Q0 + 3], dK + P0 * 64);
  wgmma_rs_n64_t0<1>(s, q[Q0 + 4], q[Q0 + 5], q[Q0 + 6], q[Q0 + 7], dK + P0 * 64 + 128);
}
template <int H> __device__ __forceinline__ void issue_pv(float (&o)[16], const uint32_t (&p)[16], uint64_t dV) {
  constexpr int P0 = (H == 0 ? 0 : H == 1 ? 3 : H == 2 ? 7 : 10);
  wgmma_rs_n32_t1<0>(o, p[0], p[1], p[2], p[3], dV + P0 * 64);
  wgmma_rs_n32_t1<1>(o, p[4], p[5], p[6], p[7], dV + P0 * 64 + 16);
  wgmma_rs_n32_t1<1>(o, p[8], p[9], p[10], p[11], dV + P0 * 64 + 32);
  wgmma_rs_n32_t1<1>(o, p[12], p[13], p[14], p[15], dV + P0 * 64 + 48);
}
__device__ __forceinline__ void issue_proj(float (&d)[48], uint64_t dX, uint64_t dW) {
#pragma unroll
  for (int s = 0; s < 6; s++) {
    const uint64_t a = dX + (s >> 1) * 256 + (s & 1) * 2, b = dW + s * 64;
    if (s == 0) wgmma_ss_n96_t1<0>(d, a, b); else wgmma_ss_n96_t1<1>(d, a, b);
  }
}
__device__ __forceinline__ void issue_qk(float (&d)[96], uint64_t dX, uint64_t dW) {
#pragma unroll
  for (int s = 0; s < 6; s++) {
    const uint64_t a = dX + (s >> 1) * 256 + (s & 1) * 2, b = dW + s * 128;
    if (s == 0) wgmma_ss_n192_t1<0>(d, a, b); else wgmma_ss_n192_t1<1>(d, a, b);
  }
}
__device__ __forceinline__ void pack_sumsq(const float* a, uint32_t (&f)[24], uint32_t (&sq)[8], uint32_t init) {
#pragma unroll
  for (int i = 0; i < 24; i++) f[i] = pack_bf16(a[2 * i], a[2 * i + 1]);
#pragma unroll
  for (int h = 0; h < 4; h++)
#pragma unroll
    for (int r = 0; r < 2; r++) {
      uint32_t u = f[6 * h + r], v = f[6 * h + 2 + r], w = f[6 * h + 4 + r];
      sq[2 * h + r] = hfma2(w, w, hfma2(v, v, hfma2(u, u, init)));
    }
}
__device__ __forceinline__ void scale_heads(uint32_t (&f)[24], const float (&r)[8]) {
#pragma unroll
  for (int h = 0; h < 4; h++) {
    const uint32_t p = pack_bf16(r[2 * h], r[2 * h + 1]);
#pragma unroll
    for (int c = 0; c < 3; c++) {
      f[6 * h + 2 * c] = hmul2_b<0>(f[6 * h + 2 * c], p);
      f[6 * h + 2 * c + 1] = hmul2_b<1>(f[6 * h + 2 * c + 1], p);
    }
  }
}
template <int ODD> __device__ __forceinline__ void norm_o(const float (&o)[16], uint32_t* of) {
  constexpr int SO = ODD ? 0 : 12, VO = ODD ? 4 : 0;
  const uint32_t p = pack_bf16(rcp(o[SO]), rcp(o[SO + 2]));
#pragma unroll
  for (int g = 0; g < 3; g++) {
    of[2 * g + 0] = hmul2_b<0>(pack_bf16(o[VO + 4 * g + 0], o[VO + 4 * g + 1]), p);
    of[2 * g + 1] = hmul2_b<1>(pack_bf16(o[VO + 4 * g + 2], o[VO + 4 * g + 3]), p);
  }
}

#define TL(i)
#define TG(i)

constexpr int BAR_KV = 1;
constexpr int BAR_AUX = 4;
constexpr int BAR_TAB = 7, BAR_SETUP = 8, BAR_RDY = 9;
constexpr uint32_t NO_TICKET = 0xFFFFFFFFu;
constexpr int MB_WQK = 0, MB_X = 8, MB_KV = 32, MB_WV = 56, MB_WO = 64, MB_TURN = 72, MB_M = 128;

#define X1EARLY 1

__global__ void __launch_bounds__(384, 1)
swin_kernel(const __grid_constant__ CUtensorMap tm_x, const __grid_constant__ CUtensorMap tm_xq, const __grid_constant__ CUtensorMap tm_wqk,
            const __grid_constant__ CUtensorMap tm_wv,
            const __nv_bfloat16* __restrict__ wo,
            const __nv_bfloat16* __restrict__ logit_scale, const __nv_bfloat16* __restrict__ w1, const __nv_bfloat16* __restrict__ w2,
            const __nv_bfloat16* __restrict__ coords, const int* __restrict__ rel_idx, const __nv_bfloat16* __restrict__ mask,
            __nv_bfloat16* __restrict__ out) {
  extern __shared__ __align__(1024) uint8_t smem[];
  constexpr uint32_t sb = 1024, mbar = sb + SM_BAR;
  const int tid = threadIdx.x, lane = tid & 31;
  const int warp = __shfl_sync(0xffffffffu, (tid >> 5) & 3, 0), wg = __shfl_sync(0xffffffffu, tid >> 7, 0);
  const uint32_t t16 = (tid & 127) * 16;
  const int G = gridDim.x;
  const uint32_t wgb = sb + SM_WG + wg * WG_SZ;
  const uint32_t bar_x = mbar + MB_X + 8 * wg;
  const char* mb = reinterpret_cast<const char*>(mask);
  TL(0); TG(14);

  auto load_x = [&](int w, int g) {
    const uint32_t dst = sb + SM_WG + g * WG_SZ + WG_X, bar = mbar + MB_X + 8 * g;
    const int wy = w >> 8, wx = w & 255;
    mbar_expect(bar, 12288);
    if (wy != NWX - 1 && wx != NWX - 1) {
      tma5(dst, &tm_x, bar, 0, 0, wy * 8 + 4, wx * 2 + 1, 0);
    } else {
#pragma unroll 1
      for (int i = 0; i < 12; i++) {
        const int q = i & 3, c = i >> 2;
        int y = wy * 8 + 4 + (q & 1) * 4; if (y >= IMG) y -= IMG;
        int xq = wx * 2 + 1 + (q >> 1);   if (xq >= IMG / 4) xq -= IMG / 4;
        tma5(dst + i * 1024, &tm_xq, bar, 0, 0, y, xq, c);
      }
    }
  };
  auto mask_off = [&](int w) { return (uint32_t)((w >> 8) * NWX + (w & 255)) * 8192u; };
  uint4 mw[4];
  auto load_mask = [&](uint32_t off) {
    const char* src = mb + (off + t16);
#pragma unroll
    for (int i = 0; i < 4; i++) mw[i] = ldg128_stream(src + i * 2048);
  };
  auto mask_or = [&](uint32_t seed) {
    uint32_t r = seed & 0x80008000u;
#pragma unroll
    for (int i = 0; i < 4; i++) {
      asm("lop3.b32 %0, %0, %1, %2, 0xFE;" : "+r"(r) : "r"(mw[i].x), "r"(mw[i].y));
      asm("lop3.b32 %0, %0, %1, %2, 0xFE;" : "+r"(r) : "r"(mw[i].z), "r"(mw[i].w));
    }
    return r;
  };
  auto lds_uniform = [&](uint32_t addr) { return __shfl_sync(0xffffffffu, lds32(addr), 0); };

  const bool g132 = G == 132;
  uint32_t cw = 0;
  int4 rid[4];
  if (wg == 0) {
    if (warp == 0) {
      if (elect_one()) {
#pragma unroll
        for (int i = 0; i < 13; i++) mbar_init(mbar + 8 * i, ((i >= 4 && i < 7) || i >= 9) ? 4 : 1);
        *reinterpret_cast<volatile uint32_t*>(smem + SM_TKT) = 0;
        fence_async();
        mbar_expect(mbar + MB_WQK, 3 * 12288);
        tma3(sb + SM_W, &tm_wqk, mbar + MB_WQK, 0, 0, 0);
        load_x(slot_window(blockIdx.x, g132), 0);
        mbar_expect(mbar + MB_WO, 18432);
        bulk_g2s(sb + SM_WOR, wo, 18432, mbar + MB_WO);
        mbar_expect(mbar + MB_WV, 3 * 6144);
        tma3(sb + SM_WV, &tm_wv, mbar + MB_WV, 0, 0, 0);
        load_x(slot_window(blockIdx.x + G, g132), 1);
#pragma unroll
        for (int i = 0; i < 4; i++) mbar_arrive(mbar + MB_TURN);
      }
      __syncwarp();
    }
  } else {
    const int i = tid - 128;
    if (i < 12) *reinterpret_cast<uint4*>(smem + SM_PAR + 16 * i) = __ldg(i < 4 ? reinterpret_cast<const uint4*>(w1) + i : reinterpret_cast<const uint4*>(w2) + (i - 4));
    if (i < 225) cw = __ldg(reinterpret_cast<const uint32_t*>(coords) + i);
#pragma unroll
    for (int c = 0; c < 4; c++) rid[c] = __ldg(reinterpret_cast<const int4*>(rel_idx) + c * 256 + i);
  }
  const uint2 lsw = __ldg(reinterpret_cast<const uint2*>(logit_scale));
  if ((uint32_t)__cvta_generic_to_shared(smem) != sb) __trap();
  auto const_tiles = [&]() {
    const int i = tid & 127;
    uint8_t* vt = smem + SM_WG + wg * WG_SZ + WG_V + (i < 64 ? 3 : 10) * 1024 + (i & 63) * 16;
    *reinterpret_cast<uint4*>(vt) = make_uint4(0x3F803F80u, 0x3F803F80u, 0x3F803F80u, 0x3F803F80u);
    *reinterpret_cast<uint4*>(vt - (WG_V - WG_K)) = make_uint4(0u, 0u, 0u, 0u);
  };
  if (wg != 0) const_tiles();
  else if (tid >= 32 && tid < 32 + 3 * NENT) {
    const int e = tid - 32, sl = blockIdx.x + (e / NENT) * G + (e % NENT) * 3 * G;
    const int w = sl < NWIN ? slot_window(sl, g132) : -1;
    const int wy = w >> 8, wx = w & 255;
    const uint32_t y0 = wy * 8 + 4, y1 = wy == NWX - 1 ? 0 : y0 + 4, x0 = wx * 8 + 4, x1 = wx == NWX - 1 ? 0 : x0 + 4;
    *reinterpret_cast<uint4*>(smem + SM_WIN + e * 32) = make_uint4((y0 * IMG + x0) * PIXB, (y1 * IMG + x0) * PIXB, (y0 * IMG + x1) * PIXB, (y1 * IMG + x1) * PIXB);
    *reinterpret_cast<uint4*>(smem + SM_WIN + e * 32 + 16) = make_uint4(w, mask_off(w), wy == NWX - 1 || wx == NWX - 1, 0);
  } else if (tid >= 96) {
    *reinterpret_cast<uint32_t*>(smem + SM_LANE + lane * 4) = ((lane >> 4) * IMG + ((lane >> 2) & 3)) * PIXB + (lane & 3) * 16;
    if (lane < 16) {
      const uint32_t v = (((lane >> 3) ^ lane) & 1) ? 0u : 0x3F803F80u;
      *reinterpret_cast<uint4*>(smem + SM_SEL + lane * 16) = make_uint4(v, v, v, v);
    }
  }
  float tau[4]; uint32_t slow_heads = 0;
  {
    const float ls[4] = {bf_lo(lsw.x), bf_hi(lsw.x), bf_lo(lsw.y), bf_hi(lsw.y)};
#pragma unroll
    for (int h = 0; h < 4; h++) {
      const float c = ls[h] < -100.f ? -100.f : (ls[h] > 4.59375f ? 4.59375f : ls[h]);
      tau[h] = rbf(ex2(c * LOG2E)) * LOG2E;
      if (!(tau[h] <= TAU_FAST_MAX)) slow_heads |= 1u << h;
    }
    slow_heads = __shfl_sync(0xffffffffu, slow_heads, 0);
  }
  TL(3);
  if (wg == 0) {
    if (tid == 0) {
      *reinterpret_cast<float4*>(smem + SM_MISC) = make_float4(slow_heads ? -tau[0] : tau[0], tau[1], tau[2], tau[3]);
      *reinterpret_cast<uint32_t*>(smem + SM_TKT + 16) = slow_heads;
    }
    fence_async();
    bar_arrive_n(BAR_SETUP, 384);
    bar_sync_n(BAR_AUX, 128);
  } else {
    const int i = tid - 128;
    bar_sync_n(BAR_TAB, 256);
    TL(4);
    if (i < 225) {
      const float c0 = bf_lo(cw), c1 = bf_hi(cw);
      float z[4] = {0.f, 0.f, 0.f, 0.f};
#pragma unroll
      for (int jj = 0; jj < 2; jj++) {
        const uint4 ua4 = lds128(sb + SM_PAR + 16 * jj), ub4 = lds128(sb + SM_PAR + 32 + 16 * jj);
        const uint32_t ua[4] = {ua4.x, ua4.y, ua4.z, ua4.w}, ub[4] = {ub4.x, ub4.y, ub4.z, ub4.w};
#pragma unroll
        for (int j = 0; j < 4; j++) {
          const uint4 wb = lds128(sb + SM_PAR + 64 + 64 * jj + 16 * j);
          const uint32_t hp = pack_bf16(fmaf(c1, bf_lo(ub[j]), c0 * bf_lo(ua[j])), fmaf(c1, bf_hi(ub[j]), c0 * bf_hi(ua[j])));
          float h0 = bf_lo(hp), h1 = bf_hi(hp);
          h0 = h0 > 0.f ? h0 : h0 * 0.f; h1 = h1 > 0.f ? h1 : h1 * 0.f;
          z[0] = fmaf(h0, bf_lo(wb.x), z[0]); z[1] = fmaf(h0, bf_hi(wb.x), z[1]); z[2] = fmaf(h0, bf_lo(wb.y), z[2]); z[3] = fmaf(h0, bf_hi(wb.y), z[3]);
          z[0] = fmaf(h1, bf_lo(wb.z), z[0]); z[1] = fmaf(h1, bf_hi(wb.z), z[1]); z[2] = fmaf(h1, bf_lo(wb.w), z[2]); z[3] = fmaf(h1, bf_hi(wb.w), z[3]);
        }
      }
      float e[4];
#pragma unroll
      for (int q = 0; q < 4; q++) {
        const float sh = ((slow_heads >> q) & 1) ? 0.f : fminf(0.f, 25.f - 1.02f * tau[q]);
        e[q] = ex2(fmaf(16.f * LOG2E, rbf(rcp(1.f + ex2(-LOG2E * rbf(z[q])))), sh));
      }
      *reinterpret_cast<uint2*>(smem + SM_TAB + 8 * i) = make_uint2(pack_bf16(e[0], e[1]), pack_bf16(e[2], e[3]));
    }
    TL(5);
    bar_sync_n(BAR_TAB, 256);
#pragma unroll
    for (int c = 0; c < 4; c++) asm volatile("" : "+r"(rid[c].x), "+r"(rid[c].y), "+r"(rid[c].z), "+r"(rid[c].w));
    {
      const int y = (i & 15) >> 1, xh = i & 1, j = 2 * xh + (y >> 2);
      const int X = (i >> 4) & 7, Yl = (i >> 7) & 1;
      uint8_t* dst = smem + SM_EB + j * 2048 + ((X >> 2) * 64 + (Yl * 4 + (X & 3)) * 4 + 2 * (y & 1)) * 16 + ((y >> 1) & 1) * 8;
#pragma unroll
      for (int c = 0; c < 4; c++) {
        const int ia0 = xh ? rid[c].z : rid[c].x, ia1 = xh ? rid[c].w : rid[c].y, ib0 = xh ? rid[c].x : rid[c].z, ib1 = xh ? rid[c].y : rid[c].w;
        const uint2 a0 = *reinterpret_cast<const uint2*>(smem + SM_TAB + 8 * ia0), a1 = *reinterpret_cast<const uint2*>(smem + SM_TAB + 8 * ia1);
        const uint2 b0 = *reinterpret_cast<const uint2*>(smem + SM_TAB + 8 * ib0), b1 = *reinterpret_cast<const uint2*>(smem + SM_TAB + 8 * ib1);
        uint8_t* d0 = dst + (c >> 1) * 512 + (((c & 1) ^ (j & 1)) * 4) + xh * 16;
        uint8_t* d1 = dst + (c >> 1) * 512 + (((c & 1) ^ (j & 1)) * 4) + (xh ^ 1) * 16;
        *reinterpret_cast<uint32_t*>(d0)         = __byte_perm(a0.x, a1.x, 0x5410); *reinterpret_cast<uint32_t*>(d1)         = __byte_perm(b0.x, b1.x, 0x5410);
        *reinterpret_cast<uint32_t*>(d0 + 8192)  = __byte_perm(a0.x, a1.x, 0x7632); *reinterpret_cast<uint32_t*>(d1 + 8192)  = __byte_perm(b0.x, b1.x, 0x7632);
        *reinterpret_cast<uint32_t*>(d0 + 16384) = __byte_perm(a0.y, a1.y, 0x5410); *reinterpret_cast<uint32_t*>(d1 + 16384) = __byte_perm(b0.y, b1.y, 0x5410);
        *reinterpret_cast<uint32_t*>(d0 + 24576) = __byte_perm(a0.y, a1.y, 0x7632); *reinterpret_cast<uint32_t*>(d1 + 24576) = __byte_perm(b0.y, b1.y, 0x7632);
      }
    }
    TL(6);
    fence_async();
    bar_arrive_n(BAR_RDY, 384);
    bar_sync_n(BAR_SETUP, 384);
  }
  uint32_t wl = sb + SM_WIN + wg * NENT * 32;
  load_mask(lds32(wl + 20));
  TL(1);
  mbar_wait(bar_x, 0);
  mbar_wait(mbar + MB_WQK, 0);
  TL(2);
  float qk[96];
  wg_fence();
  issue_qk(qk, mk_desc(WG_X, 16, 512, 2) + (wgb >> 4), mk_desc(sb + SM_W, 12288, 1024, 1)); wg_commit();
  if (warp == 0 && elect_one()) {
    if (wg == 0) {
      load_x(lds32(wl + 2 * NENT * 32 + 16), 2);
    }
    if ((int)lds32(wl + 48) >= 0) prefetch_l2(mb + lds32(wl + 52), 8192);
  }
  __syncwarp();
  if (wg == 0) {
    mbar_wait(mbar + MB_WO, 0);
#pragma unroll 1
    for (int r = 0; r < 3; r++) {
      uint4 v[3];
#pragma unroll
      for (int c = 0; c < 3; c++) v[c] = lds128(sb + SM_WOR + (r * 32 + (tid >> 2)) * 192 + c * 64 + (lane & 3) * 16);
      float sum = 0.f;
#pragma unroll
      for (int c = 0; c < 3; c++)
        sum += (bf_lo(v[c].x) + bf_hi(v[c].x)) + (bf_lo(v[c].y) + bf_hi(v[c].y)) + (bf_lo(v[c].z) + bf_hi(v[c].z)) + (bf_lo(v[c].w) + bf_hi(v[c].w));
      sum += __shfl_xor_sync(0xffffffffu, sum, 1);
      sum += __shfl_xor_sync(0xffffffffu, sum, 2);
      const float mu = sum * (1.f / 96.f);
      auto cen = [&](uint32_t u) { return pack_bf16(bf_lo(u) - mu, bf_hi(u) - mu); };
      uint8_t* dst = smem + SM_WO + (r * 4 + warp) * 128 + lane * 4;
#pragma unroll
      for (int j = 0; j < 3; j++) {
        *reinterpret_cast<uint32_t*>(dst + (4 * j + 0) * 1536) = cen(v[j].x);
        *reinterpret_cast<uint32_t*>(dst + (4 * j + 1) * 1536) = cen(v[j].y);
        *reinterpret_cast<uint32_t*>(dst + (4 * j + 2) * 1536) = cen(v[j].z);
        *reinterpret_cast<uint32_t*>(dst + (4 * j + 3) * 1536) = cen(v[j].w);
      }
    }
    bar_sync_n(BAR_AUX, 128);
    const_tiles();
    fence_async();
    bar_arrive_n(BAR_RDY + 1, 256);
    bar_arrive_n(BAR_RDY + 2, 256);
  }
  uint32_t mword = mask_or(0);
  TL(7);
  bar_sync_n(BAR_RDY + wg, wg == 0 ? 384 : 256);
  mbar_wait(mbar + MB_WV, 0);
  TL(8);

  const uint32_t k_dst = wgb + WG_K + (lane >> 4) * 7168 + warp * 256 + (lane & 15) * 16;
  const uint32_t eb_base = sb + SM_EB + t16;
  constexpr uint32_t EPS8 = 0x2A0D2A0Du;

  while (true) {
    const int nxt = lds_uniform(wl + 48);
    const bool more = nxt >= 0;
    const uint32_t z0 = wl >> 20, zw = z0 + (wgb >> 4);
    const uint64_t dX = opaque(mk_desc(WG_X, 16, 512, 2) + zw);
    TL(0);
    uint32_t qa[24], vote;
    {
      uint32_t ka[24], sk[8], sq[8];
      float k01[4], k23[4], q01[4], q23[4], vv[48];
      constexpr uint64_t dSel = mk_desc(sb + SM_SEL, 128, 256, 0);
      wg_wait<0>(); fence_regs(qk);
      TL(1);
      pack_sumsq(qk + 48, ka, sk, EPS8);
      pack_sumsq(qk, qa, sq, EPS8);
      wg_fence();
      wgmma_rs_n8_t0<0>(k01, sk[0], sk[1], sk[2], sk[3], dSel);
      wgmma_rs_n8_t0<0>(k23, sk[4], sk[5], sk[6], sk[7], dSel);
      wgmma_rs_n8_t0<0>(q01, sq[0], sq[1], sq[2], sq[3], dSel);
      wgmma_rs_n8_t0<0>(q23, sq[4], sq[5], sq[6], sq[7], dSel);
      wg_commit();
      issue_proj(vv, dX, opaque(mk_desc(sb + SM_WV, 6144, 512, 2) + z0)); wg_commit();
      const uint4 qs = lds128(sb + SM_MISC);
      if (warp == 1 && elect_one()) {
        uint32_t tk = NO_TICKET;
        if (lds32(wl + 24) == 0) asm volatile("atom.shared.add.u32 %0, [%1], 1;" : "=r"(tk) : "r"(sb + SM_TKT) : "memory");
        asm volatile("st.shared.u32 [%0], %1;" :: "r"(sb + SM_TKT + 4 + 4 * wg), "r"(tk) : "memory");
      }
      __syncwarp();
      TL(2);
      wg_wait<1>(); fence_regs(k01); fence_regs(k23); fence_regs(q01); fence_regs(q23);
      TL(3);
      const float rk[8] = {rsq(k01[0]), rsq(k01[2]), rsq(k01[1]), rsq(k01[3]), rsq(k23[0]), rsq(k23[2]), rsq(k23[1]), rsq(k23[3])};
      scale_heads(ka, rk);
#pragma unroll
      for (int i = 0; i < 6; i++) stsm4(k_dst + (i + (i >= 3)) * 1024, ka[2 * i], ka[2 * i + 1], ka[12 + 2 * i], ka[12 + 2 * i + 1]);
      TL(4);
      wg_wait<0>(); fence_regs(vv);
      TL(5);
#pragma unroll
      for (int i = 0; i < 6; i++)
        stsm4(k_dst + (WG_V - WG_K) + (i + (i >= 3)) * 1024, pack_bf16(vv[4 * i], vv[4 * i + 1]), pack_bf16(vv[4 * i + 2], vv[4 * i + 3]),
              pack_bf16(vv[24 + 4 * i], vv[24 + 4 * i + 1]), pack_bf16(vv[24 + 4 * i + 2], vv[24 + 4 * i + 3]));
      vote = (mword & 0x7FFF7FFFu) | (qs.x & 0x80000000u);
      const float s0 = fabsf(__uint_as_float(qs.x)), s1 = __uint_as_float(qs.y), s2 = __uint_as_float(qs.z), s3 = __uint_as_float(qs.w);
      const float rq[8] = {rsq(q01[0]) * s0, rsq(q01[2]) * s0, rsq(q01[1]) * s1, rsq(q01[3]) * s1,
                           rsq(q23[0]) * s2, rsq(q23[2]) * s2, rsq(q23[1]) * s3, rsq(q23[3]) * s3};
      scale_heads(qa, rq);
    }
    fence_async();
    const bool general = bar_wg_or(BAR_KV + wg, vote != 0u);
    TL(6);
    const uint64_t dK = opaque(mk_desc(WG_K, 1024, 128, 0) + zw), dV = opaque(mk_desc(WG_V, 128, 1024, 0) + zw);
    auto prefetch_next = [&]() {
      if (warp == 0 && more) {
        if (elect_one()) {
          load_x(nxt, wg);
          if ((int)lds32(wl + 80) >= 0) prefetch_l2(mb + lds32(wl + 84), 8192);
        }
        __syncwarp();
      }
    };

    const uint32_t tk = lds32(sb + SM_TKT + 4 + 4 * wg);
    auto wait_turn = [&]() { if (tk != NO_TICKET) mbar_wait(mbar + MB_TURN + (tk & 3) * 8, (tk >> 2) & 1); };
    auto pass_turn = [&]() { if (elect_one() && tk != NO_TICKET) mbar_arrive(mbar + MB_TURN + ((tk + 1) & 3) * 8); __syncwarp(); };
    uint32_t of[24];
    auto attention = [&](auto gen, bool masked, uint32_t tm) {
      constexpr bool GEN = decltype(gen)::value;
      const uint32_t scr = wgb + WG_X + t16;
      float sA[32], sB[32], oA[16], oB[16], oC[16], oD[16];
      uint32_t pA[16], pB[16], pC[16], pD[16];
      wg_fence();
      issue_s<0>(sA, qa, dK);
      issue_s<1>(sB, qa, dK); wg_commit();
      load_eb(pA, eb_base);
      if (!GEN || !masked) { prefetch_next(); wait_turn(); }
      wg_wait<0>(); fence_regs(sA); fence_regs(sB);
      TL(7);
      if (!GEN) load_eb(pB, eb_base + 8192);
      softmax_head<GEN>(sA, pA, masked, tm & 1, scr);
      if (GEN) load_eb(pB, eb_base + 8192);
      wg_fence();
      issue_s<2>(sA, qa, dK); wg_commit();
      issue_pv<0>(oA, pA, dV); wg_commit();
      TL(8);
      softmax_head<GEN>(sB, pB, masked, tm & 2, scr);
      load_eb(pC, eb_base + 2 * 8192);
      wg_wait<1>(); fence_regs(sA);
      wg_fence();
      issue_s<3>(sB, qa, dK); wg_commit();
      issue_pv<1>(oB, pB, dV); wg_commit();
      TL(9);
      softmax_head<GEN>(sA, pC, masked, tm & 4, scr);
      if (!GEN || !masked) pass_turn();
      load_eb(pD, eb_base + 3 * 8192);
      wg_wait<1>(); fence_regs(sB); fence_regs(oA);
      wg_fence();
      issue_pv<2>(oC, pC, dV); wg_commit();
      TL(10);
      norm_o<0>(oA, of);
      softmax_head<GEN>(sB, pD, masked, tm & 8, scr);
      wg_fence();
      issue_pv<3>(oD, pD, dV); wg_commit();
      if (GEN && masked) {
        fence_async();
        bar_sync_n(BAR_AUX + wg, 128);
        prefetch_next();
      }
      wg_wait<1>(); fence_regs(oB); fence_regs(oC);
      norm_o<1>(oB, of + 6);
      norm_o<0>(oC, of + 12);
      wg_wait<0>(); fence_regs(oD);
      norm_o<1>(oD, of + 18);
    };
    if (__builtin_expect(!general, 1)) {
      attention(std::false_type{}, false, 0u);
    } else {
      uint32_t tm = lds_uniform(sb + SM_TKT + 16);
      const bool masked = tm == 0 || bar_wg_or(BAR_AUX + wg, (vote & 0x7FFFFFFFu) != 0u);
      if (masked) {
        const uint32_t bar_m = mbar + MB_M + 8 * wg;
        if (warp == 0 && elect_one()) {
          mbar_init(bar_m, 1);
          fence_async();
          mbar_expect(bar_m, 8192);
          bulk_g2s(wgb + WG_X, mb + lds32(wl + 20), 8192, bar_m);
          if (more && lds32(wl + 56) == 0)
            asm volatile("cp.async.bulk.prefetch.tensor.5d.L2.global.tile [%0, {%1, %1, %2, %3, %1}];"
                         :: "l"(&tm_x), "r"(0), "r"((nxt >> 8) * 8 + 4), "r"((nxt & 255) * 2 + 1) : "memory");
        }
        bar_sync_n(BAR_AUX + wg, 128);
        wait_turn(); pass_turn();
        mbar_wait(bar_m, 0);
        uint32_t mk[16];
        const uint32_t mrow = wgb + WG_X + (orig_tok(16 * warp + (lane >> 2)) * 64 + ((lane >> 1) & 1) * 8 + (lane & 1) * 2) * 2;
#pragma unroll
        for (int Gk = 0; Gk < 8; Gk++) {
          mk[2 * Gk] = lds32(mrow + ((Gk & 3) * 16 + (Gk >> 2) * 4) * 2);
          mk[2 * Gk + 1] = lds32(mrow + (16 * 64 + (Gk & 3) * 16 + (Gk >> 2) * 4) * 2);
        }
        uint32_t x0 = mk[0], x1 = mk[1];
#pragma unroll
        for (int i = 2; i < 16; i += 2) { x0 = hmax2_nan(x0, mk[i]); x1 = hmax2_nan(x1, mk[i + 1]); }
        const bool nan_in = !(bf_lo(x0) == bf_lo(x0) && bf_hi(x0) == bf_hi(x0) && bf_lo(x1) == bf_lo(x1) && bf_hi(x1) == bf_hi(x1));
        const float r0 = quad_max(fmaxf(bf_lo(x0), bf_hi(x0))), r1 = quad_max(fmaxf(bf_lo(x1), bf_hi(x1)));
        if (bar_wg_or(BAR_AUX + wg, nan_in || !(fabsf(r0) <= 8.f && fabsf(r1) <= 8.f)) || tm != 0) {
          tm = 0xFu;
        } else {
#pragma unroll
          for (int i = 0; i < 16; i++) mk[i] = pack_bf16(ex2(bf_lo(mk[i]) * LOG2E), ex2(bf_hi(mk[i]) * LOG2E));
        }
#pragma unroll
        for (int j = 0; j < 4; j++) sts128(wgb + WG_X + t16 + j * 2048, mk[4 * j], mk[4 * j + 1], mk[4 * j + 2], mk[4 * j + 3]);
      }
      attention(std::true_type{}, masked, tm);
    }
    TL(11);

    float y[48];
    {
      const uint64_t dWo = opaque(mk_desc(sb + SM_WO, 128, 1536, 0) + z0);
      wg_fence();
#pragma unroll
      for (int s = 0; s < 6; s++) {
        if (s == 0) wgmma_rs_n96_t1<0>(y, of[0], of[1], of[2], of[3], dWo);
        else wgmma_rs_n96_t1<1>(y, of[4 * s], of[4 * s + 1], of[4 * s + 2], of[4 * s + 3], dWo + s * 16);
      }
      wg_commit();
    }
    char* const optr = reinterpret_cast<char*>(out) + (lds32(wl + 4 * warp) + lds32(sb + SM_LANE + ((t16 >> 2) & 124)));
    uint32_t yb[24];
    float var[4];
    auto ln_head = [&]() {
      uint32_t sy[8];
      wg_wait<0>(); fence_regs(y);
      TL(12);
      pack_sumsq(y, yb, sy, 0u);
      wg_fence();
      wgmma_rs_n8_t0<0>(var, sy[0], sy[1], sy[2], sy[3], dV + 3 * 64);
      wgmma_rs_n8_t0<1>(var, sy[4], sy[5], sy[6], sy[7], dV + 3 * 64);
      wg_commit();
    };
    auto ln_tail = [&]() {
      fence_regs(var);
      TL(13);
      uint32_t last;
      const uint32_t nn = pack_bf16(rsq(fmaf(var[0], 1.f / 96.f, 1e-5f)), rsq(fmaf(var[2], 1.f / 96.f, 1e-5f)));
#pragma unroll
      for (int j = 0; j < 3; j++) {
        stg128(optr + j * 64, hmul2_b<0>(yb[8 * j], nn), hmul2_b<0>(yb[8 * j + 2], nn), hmul2_b<0>(yb[8 * j + 4], nn), hmul2_b<0>(yb[8 * j + 6], nn));
        last = hmul2_b<1>(yb[8 * j + 7], nn);
        stg128(optr + 2 * ROWB + j * 64, hmul2_b<1>(yb[8 * j + 1], nn), hmul2_b<1>(yb[8 * j + 3], nn), hmul2_b<1>(yb[8 * j + 5], nn), last);
      }
      return last;
    };
    if (!more) { ln_head(); wg_wait<0>(); ln_tail(); TL(14); break; }
    load_mask(lds32(wl + 52));
    if (elect_one()) mbar_arrive(bar_x + (MB_KV - MB_X));
    __syncwarp();
    const uint32_t xphase = (wl >> 5) & 1;
    mbar_wait(bar_x, xphase ^ 1);
    mbar_wait(bar_x + (MB_KV - MB_X), xphase);
    ln_head();
    issue_qk(qk, dX, opaque(mk_desc(sb + SM_W, 12288, 1024, 1) + z0)); wg_commit();
    wg_wait<1>();
    mword = mask_or(ln_tail());
    TL(14);
    wl += 32;
  }
  TG(15);
}

typedef CUresult (*EncodeFn)(CUtensorMap*, CUtensorMapDataType, cuuint32_t, void*, const cuuint64_t*, const cuuint64_t*,
                             const cuuint32_t*, const cuuint32_t*, CUtensorMapInterleave, CUtensorMapSwizzle,
                             CUtensorMapL2promotion, CUtensorMapFloatOOBfill);

}

extern "C" void kernel_launch(void* const* d_in, const int* in_sizes, int n_in, void* d_out, int out_size) {
  static int sms = 0;
  static EncodeFn encode = nullptr;
  if (sms == 0) {
    int dev = 0;
    cudaGetDevice(&dev);
    cudaDeviceGetAttribute(&sms, cudaDevAttrMultiProcessorCount, dev);
    cudaFuncSetAttribute(swin_kernel, cudaFuncAttributeMaxDynamicSharedMemorySize, SM_TOTAL);
    cudaDriverEntryPointQueryResult qr;
    void* fn = nullptr;
    cudaGetDriverEntryPoint("cuTensorMapEncodeTiled", &fn, cudaEnableDefault, &qr);
    encode = (EncodeFn)fn;
  }
  CUtensorMap tm_x, tm_xq, tm_wqk, tm_wv;
  {
    cuuint64_t dims[5] = {32, 4, IMG, IMG / 4, 3};
    cuuint64_t strides[4] = {PIXB, ROWB, 4 * PIXB, 64};
    cuuint32_t es[5] = {1, 1, 1, 1, 1};
    cuuint32_t box[5] = {32, 4, 8, 2, 3}, boxq[5] = {32, 4, 4, 1, 1};
    encode(&tm_x, CU_TENSOR_MAP_DATA_TYPE_BFLOAT16, 5, d_in[0], dims, strides, box, es, CU_TENSOR_MAP_INTERLEAVE_NONE,
           CU_TENSOR_MAP_SWIZZLE_64B, CU_TENSOR_MAP_L2_PROMOTION_L2_128B, CU_TENSOR_MAP_FLOAT_OOB_FILL_NONE);
    encode(&tm_xq, CU_TENSOR_MAP_DATA_TYPE_BFLOAT16, 5, d_in[0], dims, strides, boxq, es, CU_TENSOR_MAP_INTERLEAVE_NONE,
           CU_TENSOR_MAP_SWIZZLE_64B, CU_TENSOR_MAP_L2_PROMOTION_L2_128B, CU_TENSOR_MAP_FLOAT_OOB_FILL_NONE);
    cuuint64_t qd[3] = {64, 96, 3}, qs[2] = {576, 128}, vd[3] = {32, 96, 3}, vs[2] = {576, 64};
    cuuint32_t qb[3] = {64, 96, 3}, vb[3] = {32, 96, 3};
    encode(&tm_wqk, CU_TENSOR_MAP_DATA_TYPE_BFLOAT16, 3, d_in[1], qd, qs, qb, es, CU_TENSOR_MAP_INTERLEAVE_NONE,
           CU_TENSOR_MAP_SWIZZLE_128B, CU_TENSOR_MAP_L2_PROMOTION_L2_256B, CU_TENSOR_MAP_FLOAT_OOB_FILL_NONE);
    encode(&tm_wv, CU_TENSOR_MAP_DATA_TYPE_BFLOAT16, 3, (char*)d_in[1] + 384, vd, vs, vb, es, CU_TENSOR_MAP_INTERLEAVE_NONE,
           CU_TENSOR_MAP_SWIZZLE_64B, CU_TENSOR_MAP_L2_PROMOTION_L2_256B, CU_TENSOR_MAP_FLOAT_OOB_FILL_NONE);
  }
  swin_kernel<<<sms, 384, SM_TOTAL>>>(
      tm_x, tm_xq, tm_wqk, tm_wv, (const __nv_bfloat16*)d_in[2], (const __nv_bfloat16*)d_in[3],
      (const __nv_bfloat16*)d_in[4], (const __nv_bfloat16*)d_in[5], (const __nv_bfloat16*)d_in[6], (const int*)d_in[7],
      (const __nv_bfloat16*)d_in[8], (__nv_bfloat16*)d_out);
}
```

```cpp
#include <cuda_runtime.h>
#include <cuda.h>
#include <cuda_bf16.h>
#include <stdint.h>
#include <type_traits>

#define TOKEN 3
namespace {

constexpr int IMG   = 384;
constexpr int NWX   = 48;
constexpr int NWIN  = NWX * NWX;
constexpr int PIXB  = 192;
constexpr int ROWB  = IMG * PIXB;
constexpr float LOG2E = 1.4426950408889634f;
constexpr float TAU_FAST_MAX = 50.f;

constexpr int SM_W    = 0;
constexpr int SM_WV   = 3 * 12288;
constexpr int SM_WO   = SM_W + 9 * 6144;
constexpr int SM_EB   = SM_WO + 12 * 1536;
constexpr int SM_WG   = SM_EB + 32768;
constexpr int WG_X    = 0;
constexpr int WG_K    = 12288;
constexpr int WG_V    = WG_K + 14336;
constexpr int WG_SZ   = WG_V + 14336;
constexpr int SM_TAB  = SM_WG + WG_SZ + WG_V + 4096;
constexpr int SM_WOR  = SM_WG + 2 * WG_SZ + WG_K;
constexpr int SM_SEL  = SM_WG + 3 * WG_SZ;
constexpr int SM_MISC = SM_SEL + 256;
constexpr int SM_BAR  = SM_MISC + 16;
constexpr int SM_SLOW = SM_BAR + 104;
constexpr int SM_PAR  = SM_BAR + 160;
constexpr int NENT    = 10;
constexpr int SM_WIN  = SM_PAR + 192;
constexpr int SM_GEN  = SM_WIN + 3 * NENT * 4;
constexpr int SM_TOTAL = SM_GEN + 3 * NENT * 4;
static_assert((SM_WIN & 7) == 0 && (NENT & 1) == 0, "list parity");

template <int SD> __device__ __forceinline__ void wgmma_ss_n192_t1(float (&d)[96], uint64_t da, uint64_t db) {
  if constexpr (SD) {
    asm volatile("{\n.reg .pred p;\nsetp.ne.b32 p, 1, 0;\n"
      "wgmma.mma_async.sync.aligned.m64n192k16.f32.bf16.bf16 {%0, %1, %2, %3, %4, %5, %6, %7, %8, %9, %10, %11, %12, %13, %14, %15, %16, %17, %18, %19, %20, %21, %22, %23, %24, %25, %26, %27, %28, %29, %30, %31, %32, %33, %34, %35, %36, %37, %38, %39, %40, %41, %42, %43, %44, %45, %46, %47, %48, %49, %50, %51, %52, %53, %54, %55, %56, %57, %58, %59, %60, %61, %62, %63, %64, %65, %66, %67, %68, %69, %70, %71, %72, %73, %74, %75, %76, %77, %78, %79, %80, %81, %82, %83, %84, %85, %86, %87, %88, %89, %90, %91, %92, %93, %94, %95}, %96, %97, p, 1, 1, 0, 1;\n}\n"
      : "+f"(d[0]), "+f"(d[1]), "+f"(d[2]), "+f"(d[3]), "+f"(d[4]), "+f"(d[5]), "+f"(d[6]), "+f"(d[7]), "+f"(d[8]), "+f"(d[9]), "+f"(d[10]), "+f"(d[11]), "+f"(d[12]), "+f"(d[13]), "+f"(d[14]), "+f"(d[15]), "+f"(d[16]), "+f"(d[17]), "+f"(d[18]), "+f"(d[19]), "+f"(d[20]), "+f"(d[21]), "+f"(d[22]), "+f"(d[23]), "+f"(d[24]), "+f"(d[25]), "+f"(d[26]), "+f"(d[27]), "+f"(d[28]), "+f"(d[29]), "+f"(d[30]), "+f"(d[31]), "+f"(d[32]), "+f"(d[33]), "+f"(d[34]), "+f"(d[35]), "+f"(d[36]), "+f"(d[37]), "+f"(d[38]), "+f"(d[39]), "+f"(d[40]), "+f"(d[41]), "+f"(d[42]), "+f"(d[43]), "+f"(d[44]), "+f"(d[45]), "+f"(d[46]), "+f"(d[47]), "+f"(d[48]), "+f"(d[49]), "+f"(d[50]), "+f"(d[51]), "+f"(d[52]), "+f"(d[53]), "+f"(d[54]), "+f"(d[55]), "+f"(d[56]), "+f"(d[57]), "+f"(d[58]), "+f"(d[59]), "+f"(d[60]), "+f"(d[61]), "+f"(d[62]), "+f"(d[63]), "+f"(d[64]), "+f"(d[65]), "+f"(d[66]), "+f"(d[67]), "+f"(d[68]), "+f"(d[69]), "+f"(d[70]), "+f"(d[71]), "+f"(d[72]), "+f"(d[73]), "+f"(d[74]), "+f"(d[75]), "+f"(d[76]), "+f"(d[77]), "+f"(d[78]), "+f"(d[79]), "+f"(d[80]), "+f"(d[81]), "+f"(d[82]), "+f"(d[83]), "+f"(d[84]), "+f"(d[85]), "+f"(d[86]), "+f"(d[87]), "+f"(d[88]), "+f"(d[89]), "+f"(d[90]), "+f"(d[91]), "+f"(d[92]), "+f"(d[93]), "+f"(d[94]), "+f"(d[95])
      : "l"(da), "l"(db));
  } else {
    asm volatile("{\n.reg .pred p;\nsetp.ne.b32 p, 0, 0;\n"
      "wgmma.mma_async.sync.aligned.m64n192k16.f32.bf16.bf16 {%0, %1, %2, %3, %4, %5, %6, %7, %8, %9, %10, %11, %12, %13, %14, %15, %16, %17, %18, %19, %20, %21, %22, %23, %24, %25, %26, %27, %28, %29, %30, %31, %32, %33, %34, %35, %36, %37, %38, %39, %40, %41, %42, %43, %44, %45, %46, %47, %48, %49, %50, %51, %52, %53, %54, %55, %56, %57, %58, %59, %60, %61, %62, %63, %64, %65, %66, %67, %68, %69, %70, %71, %72, %73, %74, %75, %76, %77, %78, %79, %80, %81, %82, %83, %84, %85, %86, %87, %88, %89, %90, %91, %92, %93, %94, %95}, %96, %97, p, 1, 1, 0, 1;\n}\n"
      : "=f"(d[0]), "=f"(d[1]), "=f"(d[2]), "=f"(d[3]), "=f"(d[4]), "=f"(d[5]), "=f"(d[6]), "=f"(d[7]), "=f"(d[8]), "=f"(d[9]), "=f"(d[10]), "=f"(d[11]), "=f"(d[12]), "=f"(d[13]), "=f"(d[14]), "=f"(d[15]), "=f"(d[16]), "=f"(d[17]), "=f"(d[18]), "=f"(d[19]), "=f"(d[20]), "=f"(d[21]), "=f"(d[22]), "=f"(d[23]), "=f"(d[24]), "=f"(d[25]), "=f"(d[26]), "=f"(d[27]), "=f"(d[28]), "=f"(d[29]), "=f"(d[30]), "=f"(d[31]), "=f"(d[32]), "=f"(d[33]), "=f"(d[34]), "=f"(d[35]), "=f"(d[36]), "=f"(d[37]), "=f"(d[38]), "=f"(d[39]), "=f"(d[40]), "=f"(d[41]), "=f"(d[42]), "=f"(d[43]), "=f"(d[44]), "=f"(d[45]), "=f"(d[46]), "=f"(d[47]), "=f"(d[48]), "=f"(d[49]), "=f"(d[50]), "=f"(d[51]), "=f"(d[52]), "=f"(d[53]), "=f"(d[54]), "=f"(d[55]), "=f"(d[56]), "=f"(d[57]), "=f"(d[58]), "=f"(d[59]), "=f"(d[60]), "=f"(d[61]), "=f"(d[62]), "=f"(d[63]), "=f"(d[64]), "=f"(d[65]), "=f"(d[66]), "=f"(d[67]), "=f"(d[68]), "=f"(d[69]), "=f"(d[70]), "=f"(d[71]), "=f"(d[72]), "=f"(d[73]), "=f"(d[74]), "=f"(d[75]), "=f"(d[76]), "=f"(d[77]), "=f"(d[78]), "=f"(d[79]), "=f"(d[80]), "=f"(d[81]), "=f"(d[82]), "=f"(d[83]), "=f"(d[84]), "=f"(d[85]), "=f"(d[86]), "=f"(d[87]), "=f"(d[88]), "=f"(d[89]), "=f"(d[90]), "=f"(d[91]), "=f"(d[92]), "=f"(d[93]), "=f"(d[94]), "=f"(d[95])
      : "l"(da), "l"(db));
  }
}
template <int SD> __device__ __forceinline__ void wgmma_ss_n96_t1(float (&d)[48], uint64_t da, uint64_t db) {
  if constexpr (SD) {
    asm volatile("{\n.reg .pred p;\nsetp.ne.b32 p, 1, 0;\n"
      "wgmma.mma_async.sync.aligned.m64n96k16.f32.bf16.bf16 {%0, %1, %2, %3, %4, %5, %6, %7, %8, %9, %10, %11, %12, %13, %14, %15, %16, %17, %18, %19, %20, %21, %22, %23, %24, %25, %26, %27, %28, %29, %30, %31, %32, %33, %34, %35, %36, %37, %38, %39, %40, %41, %42, %43, %44, %45, %46, %47}, %48, %49, p, 1, 1, 0, 1;\n}\n"
      : "+f"(d[0]), "+f"(d[1]), "+f"(d[2]), "+f"(d[3]), "+f"(d[4]), "+f"(d[5]), "+f"(d[6]), "+f"(d[7]), "+f"(d[8]), "+f"(d[9]), "+f"(d[10]), "+f"(d[11]), "+f"(d[12]), "+f"(d[13]), "+f"(d[14]), "+f"(d[15]), "+f"(d[16]), "+f"(d[17]), "+f"(d[18]), "+f"(d[19]), "+f"(d[20]), "+f"(d[21]), "+f"(d[22]), "+f"(d[23]), "+f"(d[24]), "+f"(d[25]), "+f"(d[26]), "+f"(d[27]), "+f"(d[28]), "+f"(d[29]), "+f"(d[30]), "+f"(d[31]), "+f"(d[32]), "+f"(d[33]), "+f"(d[34]), "+f"(d[35]), "+f"(d[36]), "+f"(d[37]), "+f"(d[38]), "+f"(d[39]), "+f"(d[40]), "+f"(d[41]), "+f"(d[42]), "+f"(d[43]), "+f"(d[44]), "+f"(d[45]), "+f"(d[46]), "+f"(d[47])
      : "l"(da), "l"(db));
  } else {
    asm volatile("{\n.reg .pred p;\nsetp.ne.b32 p, 0, 0;\n"
      "wgmma.mma_async.sync.aligned.m64n96k16.f32.bf16.bf16 {%0, %1, %2, %3, %4, %5, %6, %7, %8, %9, %10, %11, %12, %13, %14, %15, %16, %17, %18, %19, %20, %21, %22, %23, %24, %25, %26, %27, %28, %29, %30, %31, %32, %33, %34, %35, %36, %37, %38, %39, %40, %41, %42, %43, %44, %45, %46, %47}, %48, %49, p, 1, 1, 0, 1;\n}\n"
      : "=f"(d[0]), "=f"(d[1]), "=f"(d[2]), "=f"(d[3]), "=f"(d[4]), "=f"(d[5]), "=f"(d[6]), "=f"(d[7]), "=f"(d[8]), "=f"(d[9]), "=f"(d[10]), "=f"(d[11]), "=f"(d[12]), "=f"(d[13]), "=f"(d[14]), "=f"(d[15]), "=f"(d[16]), "=f"(d[17]), "=f"(d[18]), "=f"(d[19]), "=f"(d[20]), "=f"(d[21]), "=f"(d[22]), "=f"(d[23]), "=f"(d[24]), "=f"(d[25]), "=f"(d[26]), "=f"(d[27]), "=f"(d[28]), "=f"(d[29]), "=f"(d[30]), "=f"(d[31]), "=f"(d[32]), "=f"(d[33]), "=f"(d[34]), "=f"(d[35]), "=f"(d[36]), "=f"(d[37]), "=f"(d[38]), "=f"(d[39]), "=f"(d[40]), "=f"(d[41]), "=f"(d[42]), "=f"(d[43]), "=f"(d[44]), "=f"(d[45]), "=f"(d[46]), "=f"(d[47])
      : "l"(da), "l"(db));
  }
}
template <int SD> __device__ __forceinline__ void wgmma_rs_n96_t1(float (&d)[48], uint32_t a0, uint32_t a1, uint32_t a2, uint32_t a3, uint64_t db) {
  if constexpr (SD) {
    asm volatile("{\n.reg .pred p;\nsetp.ne.b32 p, 1, 0;\n"
      "wgmma.mma_async.sync.aligned.m64n96k16.f32.bf16.bf16 {%0, %1, %2, %3, %4, %5, %6, %7, %8, %9, %10, %11, %12, %13, %14, %15, %16, %17, %18, %19, %20, %21, %22, %23, %24, %25, %26, %27, %28, %29, %30, %31, %32, %33, %34, %35, %36, %37, %38, %39, %40, %41, %42, %43, %44, %45, %46, %47}, {%48, %49, %50, %51}, %52, p, 1, 1, 1;\n}\n"
      : "+f"(d[0]), "+f"(d[1]), "+f"(d[2]), "+f"(d[3]), "+f"(d[4]), "+f"(d[5]), "+f"(d[6]), "+f"(d[7]), "+f"(d[8]), "+f"(d[9]), "+f"(d[10]), "+f"(d[11]), "+f"(d[12]), "+f"(d[13]), "+f"(d[14]), "+f"(d[15]), "+f"(d[16]), "+f"(d[17]), "+f"(d[18]), "+f"(d[19]), "+f"(d[20]), "+f"(d[21]), "+f"(d[22]), "+f"(d[23]), "+f"(d[24]), "+f"(d[25]), "+f"(d[26]), "+f"(d[27]), "+f"(d[28]), "+f"(d[29]), "+f"(d[30]), "+f"(d[31]), "+f"(d[32]), "+f"(d[33]), "+f"(d[34]), "+f"(d[35]), "+f"(d[36]), "+f"(d[37]), "+f"(d[38]), "+f"(d[39]), "+f"(d[40]), "+f"(d[41]), "+f"(d[42]), "+f"(d[43]), "+f"(d[44]), "+f"(d[45]), "+f"(d[46]), "+f"(d[47])
      : "r"(a0), "r"(a1), "r"(a2), "r"(a3), "l"(db));
  } else {
    asm volatile("{\n.reg .pred p;\nsetp.ne.b32 p, 0, 0;\n"
      "wgmma.mma_async.sync.aligned.m64n96k16.f32.bf16.bf16 {%0, %1, %2, %3, %4, %5, %6, %7, %8, %9, %10, %11, %12, %13, %14, %15, %16, %17, %18, %19, %20, %21, %22, %23, %24, %25, %26, %27, %28, %29, %30, %31, %32, %33, %34, %35, %36, %37, %38, %39, %40, %41, %42, %43, %44, %45, %46, %47}, {%48, %49, %50, %51}, %52, p, 1, 1, 1;\n}\n"
      : "=f"(d[0]), "=f"(d[1]), "=f"(d[2]), "=f"(d[3]), "=f"(d[4]), "=f"(d[5]), "=f"(d[6]), "=f"(d[7]), "=f"(d[8]), "=f"(d[9]), "=f"(d[10]), "=f"(d[11]), "=f"(d[12]), "=f"(d[13]), "=f"(d[14]), "=f"(d[15]), "=f"(d[16]), "=f"(d[17]), "=f"(d[18]), "=f"(d[19]), "=f"(d[20]), "=f"(d[21]), "=f"(d[22]), "=f"(d[23]), "=f"(d[24]), "=f"(d[25]), "=f"(d[26]), "=f"(d[27]), "=f"(d[28]), "=f"(d[29]), "=f"(d[30]), "=f"(d[31]), "=f"(d[32]), "=f"(d[33]), "=f"(d[34]), "=f"(d[35]), "=f"(d[36]), "=f"(d[37]), "=f"(d[38]), "=f"(d[39]), "=f"(d[40]), "=f"(d[41]), "=f"(d[42]), "=f"(d[43]), "=f"(d[44]), "=f"(d[45]), "=f"(d[46]), "=f"(d[47])
      : "r"(a0), "r"(a1), "r"(a2), "r"(a3), "l"(db));
  }
}
template <int SD> __device__ __forceinline__ void wgmma_rs_n64_t0(float (&d)[32], uint32_t a0, uint32_t a1, uint32_t a2, uint32_t a3, uint64_t db) {
  if constexpr (SD) {
    asm volatile("{\n.reg .pred p;\nsetp.ne.b32 p, 1, 0;\n"
      "wgmma.mma_async.sync.aligned.m64n64k16.f32.bf16.bf16 {%0, %1, %2, %3, %4, %5, %6, %7, %8, %9, %10, %11, %12, %13, %14, %15, %16, %17, %18, %19, %20, %21, %22, %23, %24, %25, %26, %27, %28, %29, %30, %31}, {%32, %33, %34, %35}, %36, p, 1, 1, 0;\n}\n"
      : "+f"(d[0]), "+f"(d[1]), "+f"(d[2]), "+f"(d[3]), "+f"(d[4]), "+f"(d[5]), "+f"(d[6]), "+f"(d[7]), "+f"(d[8]), "+f"(d[9]), "+f"(d[10]), "+f"(d[11]), "+f"(d[12]), "+f"(d[13]), "+f"(d[14]), "+f"(d[15]), "+f"(d[16]), "+f"(d[17]), "+f"(d[18]), "+f"(d[19]), "+f"(d[20]), "+f"(d[21]), "+f"(d[22]), "+f"(d[23]), "+f"(d[24]), "+f"(d[25]), "+f"(d[26]), "+f"(d[27]), "+f"(d[28]), "+f"(d[29]), "+f"(d[30]), "+f"(d[31])
      : "r"(a0), "r"(a1), "r"(a2), "r"(a3), "l"(db));
  } else {
    asm volatile("{\n.reg .pred p;\nsetp.ne.b32 p, 0, 0;\n"
      "wgmma.mma_async.sync.aligned.m64n64k16.f32.bf16.bf16 {%0, %1, %2, %3, %4, %5, %6, %7, %8, %9, %10, %11, %12, %13, %14, %15, %16, %17, %18, %19, %20, %21, %22, %23, %24, %25, %26, %27, %28, %29, %30, %31}, {%32, %33, %34, %35}, %36, p, 1, 1, 0;\n}\n"
      : "=f"(d[0]), "=f"(d[1]), "=f"(d[2]), "=f"(d[3]), "=f"(d[4]), "=f"(d[5]), "=f"(d[6]), "=f"(d[7]), "=f"(d[8]), "=f"(d[9]), "=f"(d[10]), "=f"(d[11]), "=f"(d[12]), "=f"(d[13]), "=f"(d[14]), "=f"(d[15]), "=f"(d[16]), "=f"(d[17]), "=f"(d[18]), "=f"(d[19]), "=f"(d[20]), "=f"(d[21]), "=f"(d[22]), "=f"(d[23]), "=f"(d[24]), "=f"(d[25]), "=f"(d[26]), "=f"(d[27]), "=f"(d[28]), "=f"(d[29]), "=f"(d[30]), "=f"(d[31])
      : "r"(a0), "r"(a1), "r"(a2), "r"(a3), "l"(db));
  }
}
template <int SD> __device__ __forceinline__ void wgmma_rs_n32_t1(float (&d)[16], uint32_t a0, uint32_t a1, uint32_t a2, uint32_t a3, uint64_t db) {
  if constexpr (SD) {
    asm volatile("{\n.reg .pred p;\nsetp.ne.b32 p, 1, 0;\n"
      "wgmma.mma_async.sync.aligned.m64n32k16.f32.bf16.bf16 {%0, %1, %2, %3, %4, %5, %6, %7, %8, %9, %10, %11, %12, %13, %14, %15}, {%16, %17, %18, %19}, %20, p, 1, 1, 1;\n}\n"
      : "+f"(d[0]), "+f"(d[1]), "+f"(d[2]), "+f"(d[3]), "+f"(d[4]), "+f"(d[5]), "+f"(d[6]), "+f"(d[7]), "+f"(d[8]), "+f"(d[9]), "+f"(d[10]), "+f"(d[11]), "+f"(d[12]), "+f"(d[13]), "+f"(d[14]), "+f"(d[15])
      : "r"(a0), "r"(a1), "r"(a2), "r"(a3), "l"(db));
  } else {
    asm volatile("{\n.reg .pred p;\nsetp.ne.b32 p, 0, 0;\n"
      "wgmma.mma_async.sync.aligned.m64n32k16.f32.bf16.bf16 {%0, %1, %2, %3, %4, %5, %6, %7, %8, %9, %10, %11, %12, %13, %14, %15}, {%16, %17, %18, %19}, %20, p, 1, 1, 1;\n}\n"
      : "=f"(d[0]), "=f"(d[1]), "=f"(d[2]), "=f"(d[3]), "=f"(d[4]), "=f"(d[5]), "=f"(d[6]), "=f"(d[7]), "=f"(d[8]), "=f"(d[9]), "=f"(d[10]), "=f"(d[11]), "=f"(d[12]), "=f"(d[13]), "=f"(d[14]), "=f"(d[15])
      : "r"(a0), "r"(a1), "r"(a2), "r"(a3), "l"(db));
  }
}
template <int SD> __device__ __forceinline__ void wgmma_rs_n8_t0(float (&d)[4], uint32_t a0, uint32_t a1, uint32_t a2, uint32_t a3, uint64_t db) {
  if constexpr (SD) {
    asm volatile("{\n.reg .pred p;\nsetp.ne.b32 p, 1, 0;\n"
      "wgmma.mma_async.sync.aligned.m64n8k16.f32.bf16.bf16 {%0, %1, %2, %3}, {%4, %5, %6, %7}, %8, p, 1, 1, 0;\n}\n"
      : "+f"(d[0]), "+f"(d[1]), "+f"(d[2]), "+f"(d[3])
      : "r"(a0), "r"(a1), "r"(a2), "r"(a3), "l"(db));
  } else {
    asm volatile("{\n.reg .pred p;\nsetp.ne.b32 p, 0, 0;\n"
      "wgmma.mma_async.sync.aligned.m64n8k16.f32.bf16.bf16 {%0, %1, %2, %3}, {%4, %5, %6, %7}, %8, p, 1, 1, 0;\n}\n"
      : "=f"(d[0]), "=f"(d[1]), "=f"(d[2]), "=f"(d[3])
      : "r"(a0), "r"(a1), "r"(a2), "r"(a3), "l"(db));
  }
}

__device__ __forceinline__ void wg_fence()  { asm volatile("wgmma.fence.sync.aligned;" ::: "memory"); }
__device__ __forceinline__ void wg_commit() { asm volatile("wgmma.commit_group.sync.aligned;" ::: "memory"); }
template <int N> __device__ __forceinline__ void wg_wait() { asm volatile("wgmma.wait_group.sync.aligned %0;" :: "n"(N) : "memory"); }
template <int N> __device__ __forceinline__ void fence_regs(float (&d)[N]) {
#pragma unroll
  for (int i = 0; i < N; i++) asm volatile("" : "+f"(d[i]) :: "memory");
}
__device__ __forceinline__ constexpr uint64_t mk_desc(uint32_t addr, uint32_t lbo, uint32_t sbo, uint32_t swz) {
  return (uint64_t)(addr >> 4) | ((uint64_t)(lbo >> 4) << 16) | ((uint64_t)(sbo >> 4) << 32) | ((uint64_t)swz << 62);
}
__device__ __forceinline__ uint32_t pack_bf16(float lo, float hi) {
  uint32_t r; asm("cvt.rn.bf16x2.f32 %0, %1, %2;" : "=r"(r) : "f"(hi), "f"(lo)); return r;
}
__device__ __forceinline__ uint32_t hmul2(uint32_t a, uint32_t b) {
  uint32_t r; asm("mul.rn.bf16x2 %0, %1, %2;" : "=r"(r) : "r"(a), "r"(b)); return r;
}
template <int HI> __device__ __forceinline__ uint32_t hmul2_b(uint32_t a, uint32_t b) {
  uint32_t r;
  if (HI) asm("{\n.reg .b16 l, h;\n.reg .b32 t;\nmov.b32 {l, h}, %2;\nmov.b32 t, {h, h};\nmul.rn.bf16x2 %0, %1, t;\n}\n" : "=r"(r) : "r"(a), "r"(b));
  else    asm("{\n.reg .b16 l, h;\n.reg .b32 t;\nmov.b32 {l, h}, %2;\nmov.b32 t, {l, l};\nmul.rn.bf16x2 %0, %1, t;\n}\n" : "=r"(r) : "r"(a), "r"(b));
  return r;
}
__device__ __forceinline__ uint32_t hfma2(uint32_t a, uint32_t b, uint32_t c) {
  uint32_t r; asm("fma.rn.bf16x2 %0, %1, %2, %3;" : "=r"(r) : "r"(a), "r"(b), "r"(c)); return r;
}
__device__ __forceinline__ float ex2(float x) { float r; asm("ex2.approx.ftz.f32 %0, %1;" : "=f"(r) : "f"(x)); return r; }
__device__ __forceinline__ float rsq(float x) { float r; asm("rsqrt.approx.ftz.f32 %0, %1;" : "=f"(r) : "f"(x)); return r; }
__device__ __forceinline__ float rcp(float x) { float r; asm("rcp.approx.ftz.f32 %0, %1;" : "=f"(r) : "f"(x)); return r; }
__device__ __forceinline__ void stsm4(uint32_t addr, uint32_t r0, uint32_t r1, uint32_t r2, uint32_t r3) {
  asm volatile("stmatrix.sync.aligned.m8n8.x4.shared.b16 [%0], {%1,%2,%3,%4};" :: "r"(addr), "r"(r0), "r"(r1), "r"(r2), "r"(r3) : "memory");
}
__device__ __forceinline__ void fence_async() { asm volatile("fence.proxy.async.shared::cta;" ::: "memory"); }
__device__ __forceinline__ void bar_sync_n(int id, int n) { asm volatile("bar.sync %0, %1;" :: "r"(id), "r"(n) : "memory"); }
__device__ __forceinline__ void bar_arrive_n(int id, int n) { asm volatile("bar.arrive %0, %1;" :: "r"(id), "r"(n) : "memory"); }
__device__ __forceinline__ bool bar_wg_or(int id, bool v) {
  uint32_t r;
  asm volatile("{\n.reg .pred p, q;\nsetp.ne.u32 q, %2, 0;\nbar.red.or.pred p, %1, 128, q;\nselp.u32 %0, 0, 1, p;\n}\n"
               : "=r"(r) : "r"(id), "r"((uint32_t)v) : "memory");
  return r == 0;
}
__device__ __forceinline__ void mbar_init(uint32_t bar, uint32_t cnt) { asm volatile("mbarrier.init.shared::cta.b64 [%0], %1;" :: "r"(bar), "r"(cnt) : "memory"); }
__device__ __forceinline__ void mbar_expect(uint32_t bar, uint32_t bytes) {
  asm volatile("mbarrier.arrive.expect_tx.shared::cta.b64 _, [%0], %1;" :: "r"(bar), "r"(bytes) : "memory");
}
__device__ __forceinline__ void mbar_arrive(uint32_t bar) { asm volatile("mbarrier.arrive.shared::cta.b64 _, [%0];" :: "r"(bar) : "memory"); }
__device__ __forceinline__ void mbar_wait(uint32_t bar, uint32_t parity) {
  asm volatile("{\n.reg .pred p;\n.reg .u32 n;\nmov.u32 n, 0;\n"
               "LW_%=:\nmbarrier.try_wait.parity.shared::cta.b64 p, [%0], %1;\n@p bra.uni LD_%=;\n"
               "add.u32 n, n, 1;\nsetp.lt.u32 p, n, 4194304;\n@p bra.uni LW_%=;\ntrap;\nLD_%=:\n}\n"
               :: "r"(bar), "r"(parity) : "memory");
}
__device__ __forceinline__ void tma5(uint32_t dst, const CUtensorMap* m, uint32_t bar, int c0, int c1, int c2, int c3, int c4) {
  asm volatile("cp.async.bulk.tensor.5d.shared::cluster.global.mbarrier::complete_tx::bytes [%0], [%1, {%3, %4, %5, %6, %7}], [%2];"
               :: "r"(dst), "l"(m), "r"(bar), "r"(c0), "r"(c1), "r"(c2), "r"(c3), "r"(c4) : "memory");
}
__device__ __forceinline__ void tma3(uint32_t dst, const CUtensorMap* m, uint32_t bar, int c0, int c1, int c2) {
  asm volatile("cp.async.bulk.tensor.3d.shared::cluster.global.mbarrier::complete_tx::bytes [%0], [%1, {%3, %4, %5}], [%2];"
               :: "r"(dst), "l"(m), "r"(bar), "r"(c0), "r"(c1), "r"(c2) : "memory");
}
__device__ __forceinline__ void bulk_g2s(uint32_t dst, const void* src, uint32_t bytes, uint32_t bar) {
  asm volatile("cp.async.bulk.shared::cluster.global.mbarrier::complete_tx::bytes [%0], [%1], %2, [%3];"
               :: "r"(dst), "l"(src), "r"(bytes), "r"(bar) : "memory");
}
__device__ __forceinline__ uint32_t lds32(uint32_t addr) {
  uint32_t v; asm volatile("ld.shared.u32 %0, [%1];" : "=r"(v) : "r"(addr)); return v;
}
__device__ __forceinline__ uint64_t opaque(uint64_t v) { asm volatile("" : "+l"(v)); return v; }
__device__ __forceinline__ uint4 lds128(uint32_t addr) {
  uint4 v; asm volatile("ld.shared.v4.u32 {%0,%1,%2,%3}, [%4];" : "=r"(v.x), "=r"(v.y), "=r"(v.z), "=r"(v.w) : "r"(addr)); return v;
}
__device__ __forceinline__ uint4 ldg128_stream(const void* p) {
  uint4 v; asm volatile("ld.global.nc.L1::no_allocate.v4.u32 {%0,%1,%2,%3}, [%4];" : "=r"(v.x), "=r"(v.y), "=r"(v.z), "=r"(v.w) : "l"(p)); return v;
}
__device__ __forceinline__ void stg128(void* p, uint32_t a, uint32_t b, uint32_t c, uint32_t d) {
  asm volatile("st.global.v4.u32 [%0], {%1,%2,%3,%4};" :: "l"(p), "r"(a), "r"(b), "r"(c), "r"(d) : "memory");
}
__device__ __forceinline__ void prefetch_l2(const void* p, uint32_t bytes) {
  asm volatile("cp.async.bulk.prefetch.L2.global [%0], %1;" :: "l"(p), "r"(bytes) : "memory");
}
__device__ __forceinline__ bool elect_one() {
  uint32_t r; asm volatile("{\n.reg .pred p;\nelect.sync _|p, 0xffffffff;\nselp.u32 %0, 1, 0, p;\n}\n" : "=r"(r)); return r != 0;
}
__device__ __forceinline__ float bf_lo(uint32_t u) { return __uint_as_float(u << 16); }
__device__ __forceinline__ float bf_hi(uint32_t u) { return __uint_as_float(u & 0xFFFF0000u); }
__device__ __forceinline__ float rbf(float x) { return bf_lo(pack_bf16(x, 0.f)); }
__device__ __forceinline__ int orig_tok(int r) { return ((r & 31) >> 2) * 8 + (r >> 5) * 4 + (r & 3); }

__device__ __forceinline__ int slot_window(int s, bool g132) {
  constexpr int A0 = 396 + 264 + 60, A1 = A0 + 72, B0 = 3 * 396 + 264 + 60, B1 = B0 + 23;
  const int i = s - (s >= B1 ? 95 : s >= A1 ? 72 : 0);
  const int k = s >= B0 ? s - B0 + 72 : s - A0;
  const bool border = (s >= A0 && s < A1) || (s >= B0 && s < B1);
  const int iy = (i * 2789) >> 17, sy = (s * 2731) >> 17;
  const int wa = border ? (k < 48 ? (47 << 8 | k) : ((k - 48) << 8 | 47)) : (iy << 8 | (i - iy * 47));
  return g132 ? wa : (sy << 8 | (s - sy * 48));
}

#define EB_WORD(e, j, a) ((((a) ^ ((j) & 1)) == 0) ? (e).x : (((a) ^ ((j) & 1)) == 1) ? (e).y : (((a) ^ ((j) & 1)) == 2) ? (e).z : (e).w)

__device__ __forceinline__ void load_eb(uint32_t (&e)[16], uint32_t eb_addr) {
#pragma unroll
  for (int j = 0; j < 4; j++) {
    const uint4 v = lds128(eb_addr + j * 2048);
#pragma unroll
    for (int a = 0; a < 4; a++) e[4 * j + a] = EB_WORD(v, j, a);
  }
}
__device__ __forceinline__ void softmax_fast(const float (&s)[32], uint32_t (&p)[16]) {
#pragma unroll
  for (int i = 0; i < 16; i++) p[i] = hmul2(pack_bf16(ex2(s[2 * i]), ex2(s[2 * i + 1])), p[i]);
}
__device__ __forceinline__ uint32_t hmax2(uint32_t a, uint32_t b) {
  uint32_t r; asm("max.bf16x2 %0, %1, %2;" : "=r"(r) : "r"(a), "r"(b)); return r;
}
__device__ __forceinline__ uint32_t hmax2_nan(uint32_t a, uint32_t b) {
  uint32_t r; asm("max.NaN.bf16x2 %0, %1, %2;" : "=r"(r) : "r"(a), "r"(b)); return r;
}
__device__ __forceinline__ float quad_max(float m) {
  m = fmaxf(m, __shfl_xor_sync(0xffffffffu, m, 1));
  return fmaxf(m, __shfl_xor_sync(0xffffffffu, m, 2));
}
__device__ __forceinline__ void softmax_true_max(const float (&s)[32], uint32_t (&p)[16]) {
  float m0 = s[0], m1 = s[2];
#pragma unroll
  for (int g = 0; g < 8; g++) {
    m0 = fmaxf(m0, fmaxf(s[4 * g + 0], s[4 * g + 1]));
    m1 = fmaxf(m1, fmaxf(s[4 * g + 2], s[4 * g + 3]));
  }
  m0 = quad_max(m0); m1 = quad_max(m1);
  uint32_t n0 = 0, n1 = 0;
#pragma unroll
  for (int g = 0; g < 8; g++) {
    p[2 * g + 0] = hmul2(pack_bf16(ex2(s[4 * g + 0] - m0), ex2(s[4 * g + 1] - m0)), p[2 * g + 0]);
    p[2 * g + 1] = hmul2(pack_bf16(ex2(s[4 * g + 2] - m1), ex2(s[4 * g + 3] - m1)), p[2 * g + 1]);
    n0 = hmax2(n0, p[2 * g]); n1 = hmax2(n1, p[2 * g + 1]);
  }
  const uint32_t r = pack_bf16(rcp(quad_max(fmaxf(bf_lo(n0), bf_hi(n0)))), rcp(quad_max(fmaxf(bf_lo(n1), bf_hi(n1)))));
#pragma unroll
  for (int g = 0; g < 8; g++) { p[2 * g] = hmul2_b<0>(p[2 * g], r); p[2 * g + 1] = hmul2_b<1>(p[2 * g + 1], r); }
}
template <int H> __device__ __forceinline__ void issue_s(float (&s)[32], const uint32_t (&q)[24], uint64_t dK) {
  constexpr int Q0 = (H == 0 ? 0 : H == 1 ? 4 : H == 2 ? 12 : 16), P0 = (H == 0 ? 0 : H == 1 ? 3 : H == 2 ? 7 : 10);
  wgmma_rs_n64_t0<0>(s, q[Q0], q[Q0 + 1], q[Q0 + 2], q[Q0 + 3], dK + P0 * 64);
  wgmma_rs_n64_t0<1>(s, q[Q0 + 4], q[Q0 + 5], q[Q0 + 6], q[Q0 + 7], dK + P0 * 64 + 128);
}
template <int H> __device__ __forceinline__ void issue_pv(float (&o)[16], const uint32_t (&p)[16], uint64_t dV) {
  constexpr int P0 = (H == 0 ? 0 : H == 1 ? 3 : H == 2 ? 7 : 10);
  wgmma_rs_n32_t1<0>(o, p[0], p[1], p[2], p[3], dV + P0 * 64);
  wgmma_rs_n32_t1<1>(o, p[4], p[5], p[6], p[7], dV + P0 * 64 + 16);
  wgmma_rs_n32_t1<1>(o, p[8], p[9], p[10], p[11], dV + P0 * 64 + 32);
  wgmma_rs_n32_t1<1>(o, p[12], p[13], p[14], p[15], dV + P0 * 64 + 48);
}
__device__ __forceinline__ void issue_proj(float (&d)[48], uint64_t dX, uint64_t dW) {
#pragma unroll
  for (int s = 0; s < 6; s++) {
    const uint64_t a = dX + (s >> 1) * 256 + (s & 1) * 2, b = dW + s * 64;
    if (s == 0) wgmma_ss_n96_t1<0>(d, a, b); else wgmma_ss_n96_t1<1>(d, a, b);
  }
}
__device__ __forceinline__ void issue_qk(float (&d)[96], uint64_t dX, uint64_t dW) {
#pragma unroll
  for (int s = 0; s < 6; s++) {
    const uint64_t a = dX + (s >> 1) * 256 + (s & 1) * 2, b = dW + s * 128;
    if (s == 0) wgmma_ss_n192_t1<0>(d, a, b); else wgmma_ss_n192_t1<1>(d, a, b);
  }
}
__device__ __forceinline__ void pack_sumsq(const float* a, uint32_t (&f)[24], uint32_t (&sq)[8], uint32_t init) {
#pragma unroll
  for (int i = 0; i < 24; i++) f[i] = pack_bf16(a[2 * i], a[2 * i + 1]);
#pragma unroll
  for (int h = 0; h < 4; h++)
#pragma unroll
    for (int r = 0; r < 2; r++) {
      uint32_t u = f[6 * h + r], v = f[6 * h + 2 + r], w = f[6 * h + 4 + r];
      sq[2 * h + r] = hfma2(w, w, hfma2(v, v, hfma2(u, u, init)));
    }
}
__device__ __forceinline__ void scale_heads(uint32_t (&f)[24], const float (&r)[8]) {
#pragma unroll
  for (int h = 0; h < 4; h++) {
    const uint32_t p = pack_bf16(r[2 * h], r[2 * h + 1]);
#pragma unroll
    for (int c = 0; c < 3; c++) {
      f[6 * h + 2 * c] = hmul2_b<0>(f[6 * h + 2 * c], p);
      f[6 * h + 2 * c + 1] = hmul2_b<1>(f[6 * h + 2 * c + 1], p);
    }
  }
}
template <int ODD> __device__ __forceinline__ void norm_o(const float (&o)[16], uint32_t* of) {
  constexpr int SO = ODD ? 0 : 12, VO = ODD ? 4 : 0;
  const uint32_t p = pack_bf16(rcp(o[SO]), rcp(o[SO + 2]));
#pragma unroll
  for (int g = 0; g < 3; g++) {
    of[2 * g + 0] = hmul2_b<0>(pack_bf16(o[VO + 4 * g + 0], o[VO + 4 * g + 1]), p);
    of[2 * g + 1] = hmul2_b<1>(pack_bf16(o[VO + 4 * g + 2], o[VO + 4 * g + 3]), p);
  }
}

#define TL(i)
#define TG(i)

constexpr int BAR_KV = 1;
constexpr int BAR_AUX = 4;
constexpr int BAR_TAB = 7, BAR_SETUP = 8;
constexpr int MB_WQK = 0, MB_X = 8, MB_KV = 32, MB_WV = 56, MB_WO = 64, MB_TURN = 72, MB_RDY = 128;
constexpr uint32_t sb = 1024, mbar = sb + SM_BAR;
constexpr uint32_t EPS8 = 0x2A0D2A0Du;

__device__ __forceinline__ void load_x(const CUtensorMap* tm_x, const CUtensorMap* tm_xq, int w, int g) {
  const uint32_t dst = sb + SM_WG + g * WG_SZ + WG_X, bar = mbar + MB_X + 8 * g;
  const int wy = (w >> 8) & 255, wx = w & 255;
  mbar_expect(bar, 12288);
  if (wy != NWX - 1 && wx != NWX - 1) {
    tma5(dst, tm_x, bar, 0, 0, wy * 8 + 4, wx * 2 + 1, 0);
  } else {
#pragma unroll 1
    for (int i = 0; i < 12; i++) {
      const int q = i & 3, c = i >> 2;
      int y = wy * 8 + 4 + (q & 1) * 4; if (y >= IMG) y -= IMG;
      int xq = wx * 2 + 1 + (q >> 1);   if (xq >= IMG / 4) xq -= IMG / 4;
      tma5(dst + i * 1024, tm_xq, bar, 0, 0, y, xq, c);
    }
  }
}
__device__ __forceinline__ uint32_t mask_off(int w) { return (uint32_t)(((w >> 8) & 255) * NWX + (w & 255)) * 8192u; }
__device__ __forceinline__ int lds_uniform(uint32_t addr) { return __shfl_sync(0xffffffffu, lds32(addr), 0); }

__device__ __forceinline__ void qkv_epilogue(float (&qk)[96], uint32_t (&qa)[24], uint64_t dX, uint64_t dWv, uint32_t k_dst) {
  uint32_t ka[24], sk[8], sq[8];
  float k01[4], k23[4], q01[4], q23[4], vv[48];
  constexpr uint64_t dSel = mk_desc(sb + SM_SEL, 128, 256, 0);
  wg_wait<0>(); fence_regs(qk);
  pack_sumsq(qk + 48, ka, sk, EPS8);
  pack_sumsq(qk, qa, sq, EPS8);
  wg_fence();
  wgmma_rs_n8_t0<0>(k01, sk[0], sk[1], sk[2], sk[3], dSel);
  wgmma_rs_n8_t0<0>(k23, sk[4], sk[5], sk[6], sk[7], dSel);
  wgmma_rs_n8_t0<0>(q01, sq[0], sq[1], sq[2], sq[3], dSel);
  wgmma_rs_n8_t0<0>(q23, sq[4], sq[5], sq[6], sq[7], dSel);
  wg_commit();
  issue_proj(vv, dX, dWv); wg_commit();
  const uint4 qs = lds128(sb + SM_MISC);
  wg_wait<1>(); fence_regs(k01); fence_regs(k23); fence_regs(q01); fence_regs(q23);
  const float rk[8] = {rsq(k01[0]), rsq(k01[2]), rsq(k01[1]), rsq(k01[3]), rsq(k23[0]), rsq(k23[2]), rsq(k23[1]), rsq(k23[3])};
  scale_heads(ka, rk);
#pragma unroll
  for (int i = 0; i < 6; i++) stsm4(k_dst + (i + (i >= 3)) * 1024, ka[2 * i], ka[2 * i + 1], ka[12 + 2 * i], ka[12 + 2 * i + 1]);
  wg_wait<0>(); fence_regs(vv);
#pragma unroll
  for (int i = 0; i < 6; i++)
    stsm4(k_dst + (WG_V - WG_K) + (i + (i >= 3)) * 1024, pack_bf16(vv[4 * i], vv[4 * i + 1]), pack_bf16(vv[4 * i + 2], vv[4 * i + 3]),
          pack_bf16(vv[24 + 4 * i], vv[24 + 4 * i + 1]), pack_bf16(vv[24 + 4 * i + 2], vv[24 + 4 * i + 3]));
  const float s0 = __uint_as_float(qs.x), s1 = __uint_as_float(qs.y), s2 = __uint_as_float(qs.z), s3 = __uint_as_float(qs.w);
  const float rq[8] = {rsq(q01[0]) * s0, rsq(q01[2]) * s0, rsq(q01[1]) * s1, rsq(q01[3]) * s1,
                       rsq(q23[0]) * s2, rsq(q23[2]) * s2, rsq(q23[1]) * s3, rsq(q23[3]) * s3};
  scale_heads(qa, rq);
  fence_async();
}
__device__ __forceinline__ void issue_out(float (&y)[48], const uint32_t (&of)[24], uint64_t dWo) {
  wg_fence();
#pragma unroll
  for (int s = 0; s < 6; s++) {
    if (s == 0) wgmma_rs_n96_t1<0>(y, of[0], of[1], of[2], of[3], dWo);
    else wgmma_rs_n96_t1<1>(y, of[4 * s], of[4 * s + 1], of[4 * s + 2], of[4 * s + 3], dWo + s * 16);
  }
  wg_commit();
}
__device__ __forceinline__ void ln_head(float (&y)[48], uint32_t (&yb)[24], float (&var)[4], uint64_t dOnes) {
  uint32_t sy[8];
  wg_wait<0>(); fence_regs(y);
  pack_sumsq(y, yb, sy, 0u);
  wg_fence();
  wgmma_rs_n8_t0<0>(var, sy[0], sy[1], sy[2], sy[3], dOnes);
  wgmma_rs_n8_t0<1>(var, sy[4], sy[5], sy[6], sy[7], dOnes);
  wg_commit();
}
__device__ __forceinline__ char* out_ptr(__nv_bfloat16* out, int win, int warp, uint32_t t16) {
  int py = ((win >> 8) & 255) * 8 + 4 + (warp & 1) * 4;  if (py >= IMG) py -= IMG;
  int px = (win & 255) * 8 + 4 + (warp >> 1) * 4;        if (px >= IMG) px -= IMG;
  return reinterpret_cast<char*>(out) + ((uint32_t)(py * IMG + px) * PIXB - warp * 512 + t16 + ((t16 & 0xC0) << 1) + (t16 & 0x100) * 287);
}
__device__ __forceinline__ uint32_t ln_tail(const uint32_t (&yb)[24], float (&var)[4], char* optr) {
  fence_regs(var);
  uint32_t last;
  const uint32_t nn = pack_bf16(rsq(fmaf(var[0], 1.f / 96.f, 1e-5f)), rsq(fmaf(var[2], 1.f / 96.f, 1e-5f)));
#pragma unroll
  for (int j = 0; j < 3; j++) {
    stg128(optr + j * 64, hmul2_b<0>(yb[8 * j], nn), hmul2_b<0>(yb[8 * j + 2], nn), hmul2_b<0>(yb[8 * j + 4], nn), hmul2_b<0>(yb[8 * j + 6], nn));
    last = hmul2_b<1>(yb[8 * j + 7], nn);
    stg128(optr + 2 * ROWB + j * 64, hmul2_b<1>(yb[8 * j + 1], nn), hmul2_b<1>(yb[8 * j + 3], nn), hmul2_b<1>(yb[8 * j + 5], nn), last);
  }
  return last;
}

__device__ __forceinline__ void general_windows(const CUtensorMap* tm_x, const CUtensorMap* tm_xq, const char* mb, __nv_bfloat16* out, uint32_t xph) {
  int tid;
  asm volatile("mov.u32 %0, %%tid.x;" : "=r"(tid));
  const int lane = tid & 31;
  const int warp = __shfl_sync(0xffffffffu, (tid >> 5) & 3, 0), wg = __shfl_sync(0xffffffffu, tid >> 7, 0);
  const uint32_t t16 = (tid & 127) * 16, wgb = sb + SM_WG + wg * WG_SZ, bar_x = mbar + MB_X + 8 * wg;
  const uint32_t k_dst = wgb + WG_K + (lane >> 4) * 7168 + warp * 256 + (lane & 15) * 16;
  const uint32_t slow_heads = lds_uniform(sb + SM_SLOW);
  const uint64_t dX = mk_desc(WG_X, 16, 512, 2) + (wgb >> 4), dK = mk_desc(WG_K, 1024, 128, 0) + (wgb >> 4), dV = mk_desc(WG_V, 128, 1024, 0) + (wgb >> 4);
#pragma unroll 1
  for (uint32_t gl = sb + SM_GEN + wg * NENT * 4;; gl += 4) {
    const int win = lds_uniform(gl);
    if (win < 0) break;
    uint32_t qa[24], of[24];
    {
      float qk[96];
      mbar_wait(bar_x, xph); xph ^= 1;
      wg_fence();
      issue_qk(qk, dX, mk_desc(sb + SM_W, 12288, 1024, 1)); wg_commit();
      bar_sync_n(BAR_AUX + wg, 128);
      qkv_epilogue(qk, qa, dX, mk_desc(sb + SM_WV, 6144, 512, 2), k_dst);
    }
    bar_sync_n(BAR_AUX + wg, 128);
    if (warp == 0 && elect_one()) { mbar_expect(bar_x, 8192); bulk_g2s(wgb + WG_X, mb + mask_off(win), 8192, bar_x); }
    __syncwarp();
    mbar_wait(bar_x, xph); xph ^= 1;
    uint32_t mk[16], em[16];
    {
      const uint32_t mrow = wgb + WG_X + (orig_tok(16 * warp + (lane >> 2)) * 64 + ((lane >> 1) & 1) * 8 + (lane & 1) * 2) * 2;
#pragma unroll
      for (int i = 0; i < 8; i++) {
        const int Gk = (i + (lane >> 2)) & 7;
        mk[2 * i] = lds32(mrow + (Gk & 3) * 32 + (Gk >> 2) * 8);
        mk[2 * i + 1] = lds32(mrow + 2048 + (Gk & 3) * 32 + (Gk >> 2) * 8);
      }
    }
    uint32_t x0 = mk[0], x1 = mk[1];
#pragma unroll
    for (int i = 2; i < 16; i += 2) { x0 = hmax2_nan(x0, mk[i]); x1 = hmax2_nan(x1, mk[i + 1]); }
    const bool nan_in = !(bf_lo(x0) == bf_lo(x0) && bf_hi(x0) == bf_hi(x0) && bf_lo(x1) == bf_lo(x1) && bf_hi(x1) == bf_hi(x1));
    const float r0 = quad_max(fmaxf(bf_lo(x0), bf_hi(x0))), r1 = quad_max(fmaxf(bf_lo(x1), bf_hi(x1)));
    const uint32_t tm = bar_wg_or(BAR_KV + wg, nan_in || !(fabsf(r0) <= 8.f && fabsf(r1) <= 8.f)) ? 0xFu : slow_heads;
#pragma unroll
    for (int i = 0; i < 8; i++) {
      const int Gk = (i + (lane >> 2)) & 7;
      asm volatile("st.shared.v2.u32 [%0], {%1,%2};" :: "r"(wgb + WG_X + t16 + (Gk >> 1) * 2048 + (Gk & 1) * 8), "r"(mk[2 * i]), "r"(mk[2 * i + 1]) : "memory");
    }
#pragma unroll
    for (int j = 0; j < 4; j++) {
      const uint4 m = lds128(wgb + WG_X + t16 + j * 2048);
      mk[4 * j] = m.x; mk[4 * j + 1] = m.y; mk[4 * j + 2] = m.z; mk[4 * j + 3] = m.w;
    }
#pragma unroll
    for (int i = 0; i < 16; i++) em[i] = pack_bf16(ex2(bf_lo(mk[i]) * LOG2E), ex2(bf_hi(mk[i]) * LOG2E));
    fence_async();
    bar_sync_n(BAR_AUX + wg, 128);
    if (warp == 0 && elect_one()) {
      const int nxt = lds32(gl + 4);
      if (nxt >= 0) { load_x(tm_x, tm_xq, nxt, wg); prefetch_l2(mb + mask_off(nxt), 8192); }
    }
    __syncwarp();
#pragma unroll
    for (int i = 0; i < 24; i++) of[i] = 0;
#pragma unroll 1
    for (int h = 0; h < 4; h++) {
      float sc[32], o[16]; uint32_t p[16];
      const uint32_t po = (h * 3 + (h >> 1)) * 64;
      wg_fence(); issue_s<0>(sc, qa, dK + po); wg_commit();
      load_eb(p, sb + SM_EB + t16 + h * 8192);
      const bool tmax = (tm >> h) & 1;
      if (!tmax) {
#pragma unroll
        for (int i = 0; i < 16; i++) p[i] = hmul2(p[i], em[i]);
      }
      wg_wait<0>(); fence_regs(sc);
      if (tmax) {
#pragma unroll
        for (int i = 0; i < 16; i++) {
          sc[2 * i] = fmaf(bf_lo(mk[i]), LOG2E, sc[2 * i]); sc[2 * i + 1] = fmaf(bf_hi(mk[i]), LOG2E, sc[2 * i + 1]);
        }
        softmax_true_max(sc, p);
      } else {
        softmax_fast(sc, p);
      }
      wg_fence(); issue_pv<0>(o, p, dV + po); wg_commit();
#pragma unroll
      for (int i = 0; i < 20; i++) qa[i] = (h & 1) ? (i < 16 ? qa[i + 8] : 0u) : qa[i + 4];
#pragma unroll
      for (int i = 0; i < 18; i++) of[i] = of[i + 6];
      wg_wait<0>(); fence_regs(o);
      if (h & 1) norm_o<1>(o, of + 18); else norm_o<0>(o, of + 18);
    }
    float y[48], var[4]; uint32_t yb[24];
    issue_out(y, of, mk_desc(sb + SM_WO, 128, 1536, 0));
    ln_head(y, yb, var, dV + 3 * 64);
    wg_wait<0>();
    ln_tail(yb, var, out_ptr(out, win, warp, t16));
  }
}

__global__ void __launch_bounds__(384, 1)
swin_kernel(const __grid_constant__ CUtensorMap tm_x, const __grid_constant__ CUtensorMap tm_xq, const __grid_constant__ CUtensorMap tm_wqk,
            const __grid_constant__ CUtensorMap tm_wv,
            const __nv_bfloat16* __restrict__ wo,
            const __nv_bfloat16* __restrict__ logit_scale, const __nv_bfloat16* __restrict__ w1, const __nv_bfloat16* __restrict__ w2,
            const __nv_bfloat16* __restrict__ coords, const int* __restrict__ rel_idx, const __nv_bfloat16* __restrict__ mask,
            __nv_bfloat16* __restrict__ out) {
  extern __shared__ __align__(1024) uint8_t smem[];
  const int tid = threadIdx.x, lane = tid & 31;
  const int warp = __shfl_sync(0xffffffffu, (tid >> 5) & 3, 0), wg = __shfl_sync(0xffffffffu, tid >> 7, 0);
  const uint32_t t16 = (tid & 127) * 16;
  const int G = gridDim.x;
  const uint32_t wgb = sb + SM_WG + wg * WG_SZ;
  const uint32_t bar_x = mbar + MB_X + 8 * wg;
  const char* mb = reinterpret_cast<const char*>(mask);
  TL(0); TG(14);

  uint4 mw[4];
  auto load_mask = [&](uint32_t off) {
    const char* src = mb + (off + t16);
#pragma unroll
    for (int i = 0; i < 4; i++) mw[i] = ldg128_stream(src + i * 2048);
  };
  auto mask_or = [&](uint32_t seed) {
    uint32_t r = seed & 0x80008000u;
#pragma unroll
    for (int i = 0; i < 4; i++) {
      asm("lop3.b32 %0, %0, %1, %2, 0xFE;" : "+r"(r) : "r"(mw[i].x), "r"(mw[i].y));
      asm("lop3.b32 %0, %0, %1, %2, 0xFE;" : "+r"(r) : "r"(mw[i].z), "r"(mw[i].w));
    }
    return r;
  };

  const bool g132 = G == 132;
  const uint2 lsw = __ldg(reinterpret_cast<const uint2*>(logit_scale));
  uint32_t cw = 0;
  int4 rid[4];
  if (wg == 0) {
    if (warp == 0) {
      if (elect_one()) {
#pragma unroll
        for (int i = 0; i < 13; i++) mbar_init(mbar + 8 * i, ((i >= 4 && i < 7) || i >= 9) ? 4 : 1);
        mbar_init(mbar + MB_RDY, 8);
        fence_async();
        mbar_expect(mbar + MB_WQK, 3 * 12288);
        tma3(sb + SM_W, &tm_wqk, mbar + MB_WQK, 0, 0, 0);
        load_x(&tm_x, &tm_xq, slot_window(blockIdx.x, g132), 0);
        mbar_expect(mbar + MB_WV, 3 * 6144);
        tma3(sb + SM_WV, &tm_wv, mbar + MB_WV, 0, 0, 0);
        mbar_expect(mbar + MB_WO, 18432);
        bulk_g2s(sb + SM_WOR, wo, 18432, mbar + MB_WO);
      }
      __syncwarp();
    }
  } else {
    const int i = tid - 128;
    if (i < 12) *reinterpret_cast<uint4*>(smem + SM_PAR + 16 * i) = __ldg(i < 4 ? reinterpret_cast<const uint4*>(w1) + i : reinterpret_cast<const uint4*>(w2) + (i - 4));
    if (i < 225) cw = __ldg(reinterpret_cast<const uint32_t*>(coords) + i);
  }
  if ((uint32_t)__cvta_generic_to_shared(smem) != sb) __trap();
  auto const_tiles = [&]() {
    const int i = tid & 127;
    uint8_t* vt = smem + SM_WG + wg * WG_SZ + WG_V + (i < 64 ? 3 : 10) * 1024 + (i & 63) * 16;
    *reinterpret_cast<uint4*>(vt) = make_uint4(0x3F803F80u, 0x3F803F80u, 0x3F803F80u, 0x3F803F80u);
    *reinterpret_cast<uint4*>(vt - (WG_V - WG_K)) = make_uint4(0u, 0u, 0u, 0u);
  };
  if (wg != 2) const_tiles();
  float tau[4]; uint32_t slow_heads = 0;
  {
    const float ls[4] = {bf_lo(lsw.x), bf_hi(lsw.x), bf_lo(lsw.y), bf_hi(lsw.y)};
#pragma unroll
    for (int h = 0; h < 4; h++) {
      const float c = ls[h] < -100.f ? -100.f : (ls[h] > 4.59375f ? 4.59375f : ls[h]);
      tau[h] = rbf(ex2(c * LOG2E)) * LOG2E;
      if (!(tau[h] <= TAU_FAST_MAX)) slow_heads |= 1u << h;
    }
    slow_heads = __shfl_sync(0xffffffffu, slow_heads, 0);
  }
  if (wg == 0 && warp == 1) {
    const int eg = lane / NENT, ei = lane - eg * NENT, sl = blockIdx.x + eg * G + ei * 3 * G;
    const int w = (sl < NWIN && eg < 3) ? slot_window(sl, g132) : -1;
    const bool fast = w >= 0 && slow_heads == 0 && (ei == 0 || ((w >> 8) != NWX - 1 && (w & 255) != NWX - 1));
    const uint32_t fm = __ballot_sync(0xffffffffu, fast), gm = __ballot_sync(0xffffffffu, w >= 0 && !fast);
    const uint32_t below = ((1u << ei) - 1) << (eg * NENT);
    const int pos = __popc((fast ? fm : gm) & below);
    int ticket = 0;
#pragma unroll
    for (int g = 0; g < 3; g++) ticket += min(__popc((fm >> (g * NENT)) & ((1u << NENT) - 1)), pos + (g < eg));
    if (eg < 3) {
      *reinterpret_cast<int*>(smem + SM_WIN + lane * 4) = -1;
      *reinterpret_cast<int*>(smem + SM_GEN + lane * 4) = -1;
    }
    __syncwarp();
    if (w >= 0) *reinterpret_cast<int*>(smem + (fast ? SM_WIN : SM_GEN) + (eg * NENT + pos) * 4) = w | ticket << 16;
  }
  if (wg == 0 && warp == 3 && lane < 16) {
    const uint32_t v = (((lane >> 3) ^ lane) & 1) ? 0u : 0x3F803F80u;
    *reinterpret_cast<uint4*>(smem + SM_SEL + lane * 16) = make_uint4(v, v, v, v);
  }
  TL(3);
  if (wg == 0) {
    if (tid == 0) {
      *reinterpret_cast<float4*>(smem + SM_MISC) = make_float4(tau[0], tau[1], tau[2], tau[3]);
      *reinterpret_cast<uint32_t*>(smem + SM_SLOW) = slow_heads;
    }
    fence_async();
    bar_arrive_n(BAR_SETUP, 384);
    bar_sync_n(BAR_AUX, 128);
  } else {
    const int i = tid - 128;
#pragma unroll
    for (int c = 0; c < 4; c++) {
      const uint4 r = ldg128_stream(reinterpret_cast<const int4*>(rel_idx) + c * 256 + i);
      rid[c] = make_int4(r.x, r.y, r.z, r.w);
    }
    bar_sync_n(BAR_TAB, 256);
    TL(4);
    if (i < 225) {
      const float c0 = bf_lo(cw), c1 = bf_hi(cw);
      float z[4] = {0.f, 0.f, 0.f, 0.f};
#pragma unroll
      for (int jj = 0; jj < 2; jj++) {
        const uint4 ua4 = lds128(sb + SM_PAR + 16 * jj), ub4 = lds128(sb + SM_PAR + 32 + 16 * jj);
        const uint32_t ua[4] = {ua4.x, ua4.y, ua4.z, ua4.w}, ub[4] = {ub4.x, ub4.y, ub4.z, ub4.w};
#pragma unroll
        for (int j = 0; j < 4; j++) {
          const uint4 wb = lds128(sb + SM_PAR + 64 + 64 * jj + 16 * j);
          const uint32_t hp = pack_bf16(fmaf(c1, bf_lo(ub[j]), c0 * bf_lo(ua[j])), fmaf(c1, bf_hi(ub[j]), c0 * bf_hi(ua[j])));
          float h0 = bf_lo(hp), h1 = bf_hi(hp);
          h0 = h0 > 0.f ? h0 : h0 * 0.f; h1 = h1 > 0.f ? h1 : h1 * 0.f;
          z[0] = fmaf(h0, bf_lo(wb.x), z[0]); z[1] = fmaf(h0, bf_hi(wb.x), z[1]); z[2] = fmaf(h0, bf_lo(wb.y), z[2]); z[3] = fmaf(h0, bf_hi(wb.y), z[3]);
          z[0] = fmaf(h1, bf_lo(wb.z), z[0]); z[1] = fmaf(h1, bf_hi(wb.z), z[1]); z[2] = fmaf(h1, bf_lo(wb.w), z[2]); z[3] = fmaf(h1, bf_hi(wb.w), z[3]);
        }
      }
      float e[4];
#pragma unroll
      for (int q = 0; q < 4; q++) {
        const float sh = ((slow_heads >> q) & 1) ? 0.f : fminf(0.f, 25.f - 1.02f * tau[q]);
        e[q] = ex2(fmaf(16.f * LOG2E, rbf(rcp(1.f + ex2(-LOG2E * rbf(z[q])))), sh));
      }
      *reinterpret_cast<uint2*>(smem + SM_TAB + 8 * i) = make_uint2(pack_bf16(e[0], e[1]), pack_bf16(e[2], e[3]));
    }
    TL(5);
    bar_sync_n(BAR_SETUP, 384);
    if (tid == 128 + 127) {
      const int w = slot_window(blockIdx.x + G, g132);
      load_x(&tm_x, &tm_xq, w, 1);
      prefetch_l2(mb + mask_off(w), 8192);
    }
    __syncwarp();
#pragma unroll
    for (int c = 0; c < 4; c++) asm volatile("" : "+r"(rid[c].x), "+r"(rid[c].y), "+r"(rid[c].z), "+r"(rid[c].w));
    {
      const int y = (i & 15) >> 1, xh = i & 1, j = 2 * xh + (y >> 2);
      const int X = (i >> 4) & 7, Yl = (i >> 7) & 1;
      uint8_t* dst = smem + SM_EB + j * 2048 + ((X >> 2) * 64 + (Yl * 4 + (X & 3)) * 4 + 2 * (y & 1)) * 16 + ((y >> 1) & 1) * 8;
#pragma unroll
      for (int c = 0; c < 4; c++) {
        const int ia0 = xh ? rid[c].z : rid[c].x, ia1 = xh ? rid[c].w : rid[c].y, ib0 = xh ? rid[c].x : rid[c].z, ib1 = xh ? rid[c].y : rid[c].w;
        const uint2 a0 = *reinterpret_cast<const uint2*>(smem + SM_TAB + 8 * ia0), a1 = *reinterpret_cast<const uint2*>(smem + SM_TAB + 8 * ia1);
        const uint2 b0 = *reinterpret_cast<const uint2*>(smem + SM_TAB + 8 * ib0), b1 = *reinterpret_cast<const uint2*>(smem + SM_TAB + 8 * ib1);
        uint8_t* d0 = dst + (c >> 1) * 512 + (((c & 1) ^ (j & 1)) * 4) + xh * 16;
        uint8_t* d1 = dst + (c >> 1) * 512 + (((c & 1) ^ (j & 1)) * 4) + (xh ^ 1) * 16;
        *reinterpret_cast<uint32_t*>(d0)         = __byte_perm(a0.x, a1.x, 0x5410); *reinterpret_cast<uint32_t*>(d1)         = __byte_perm(b0.x, b1.x, 0x5410);
        *reinterpret_cast<uint32_t*>(d0 + 8192)  = __byte_perm(a0.x, a1.x, 0x7632); *reinterpret_cast<uint32_t*>(d1 + 8192)  = __byte_perm(b0.x, b1.x, 0x7632);
        *reinterpret_cast<uint32_t*>(d0 + 16384) = __byte_perm(a0.y, a1.y, 0x5410); *reinterpret_cast<uint32_t*>(d1 + 16384) = __byte_perm(b0.y, b1.y, 0x5410);
        *reinterpret_cast<uint32_t*>(d0 + 24576) = __byte_perm(a0.y, a1.y, 0x7632); *reinterpret_cast<uint32_t*>(d1 + 24576) = __byte_perm(b0.y, b1.y, 0x7632);
      }
    }
    TL(6);
    if (tid == 256) {
      const int w = slot_window(blockIdx.x + 2 * G, g132);
      load_x(&tm_x, &tm_xq, w, 2);
      prefetch_l2(mb + mask_off(w), 8192);
    }
    __syncwarp();
    fence_async();
    if (elect_one()) mbar_arrive(mbar + MB_RDY);
    __syncwarp();
    bar_sync_n(BAR_TAB, 256);
    if (wg == 2) {
      mbar_wait(mbar + MB_WO, 0);
      uint4 v[9];
#pragma unroll
      for (int c = 0; c < 9; c++) v[c] = lds128(sb + SM_WOR + ((c / 3) * 32 + ((tid & 127) >> 2)) * 192 + (c % 3) * 64 + (lane & 3) * 16);
      bar_sync_n(BAR_AUX + 2, 128);
      const_tiles();
#pragma unroll
      for (int r = 0; r < 3; r++) {
        float sum = 0.f;
#pragma unroll
        for (int c = 3 * r; c < 3 * r + 3; c++)
          sum += (bf_lo(v[c].x) + bf_hi(v[c].x)) + (bf_lo(v[c].y) + bf_hi(v[c].y)) + (bf_lo(v[c].z) + bf_hi(v[c].z)) + (bf_lo(v[c].w) + bf_hi(v[c].w));
        sum += __shfl_xor_sync(0xffffffffu, sum, 1);
        sum += __shfl_xor_sync(0xffffffffu, sum, 2);
        const float mu = sum * (1.f / 96.f);
        auto cen = [&](uint32_t u) { return pack_bf16(bf_lo(u) - mu, bf_hi(u) - mu); };
        uint8_t* dst = smem + SM_WO + (r * 4 + warp) * 128 + lane * 4;
#pragma unroll
        for (int j = 0; j < 3; j++) {
          *reinterpret_cast<uint32_t*>(dst + (4 * j + 0) * 1536) = cen(v[3 * r + j].x);
          *reinterpret_cast<uint32_t*>(dst + (4 * j + 1) * 1536) = cen(v[3 * r + j].y);
          *reinterpret_cast<uint32_t*>(dst + (4 * j + 2) * 1536) = cen(v[3 * r + j].z);
          *reinterpret_cast<uint32_t*>(dst + (4 * j + 3) * 1536) = cen(v[3 * r + j].w);
        }
      }
      fence_async();
      __syncwarp();
      if (elect_one()) mbar_arrive(mbar + MB_TURN);
      __syncwarp();
    }
  }
  uint32_t wl = sb + SM_WIN + wg * NENT * 4;
  int win = lds_uniform(wl), nxt = lds_uniform(wl + 4);
  TL(1);
  mbar_wait(mbar + MB_WQK, 0);
  if (win >= 0) {
    float qk[96];
    load_mask(mask_off(win));
    mbar_wait(bar_x, 0);
    TL(2);
    wg_fence();
    issue_qk(qk, mk_desc(WG_X, 16, 512, 2) + (wgb >> 4), mk_desc(sb + SM_W, 12288, 1024, 1)); wg_commit();
    if (warp == 0 && nxt >= 0 && elect_one()) prefetch_l2(mb + mask_off(nxt), 8192);
    __syncwarp();
    uint32_t mword = mask_or(0);
    TL(7);
    mbar_wait(mbar + MB_WV, 0);
    mbar_wait(mbar + MB_RDY, 0);
    TL(8);

    const uint32_t k_dst = wgb + WG_K + (lane >> 4) * 7168 + warp * 256 + (lane & 15) * 16;
    const uint32_t eb_base = sb + SM_EB + t16;
    while (true) {
      const int nxt2 = lds_uniform(wl + 8), tk = win >> 16;
      const bool more = nxt >= 0;
      const uint32_t z0 = wl >> 20, zw = z0 + (wgb >> 4);
      const uint64_t dX = opaque(mk_desc(WG_X, 16, 512, 2) + zw);
      TL(0);
      uint32_t qa[24];
      qkv_epilogue(qk, qa, dX, opaque(mk_desc(sb + SM_WV, 6144, 512, 2) + z0), k_dst);
      TL(5);
      const bool masked = bar_wg_or(BAR_KV + wg, (mword & 0x7FFF7FFFu) != 0u);
      TL(6);
      const uint64_t dK = opaque(mk_desc(WG_K, 1024, 128, 0) + zw), dV = opaque(mk_desc(WG_V, 128, 1024, 0) + zw);
      auto prefetch_next = [&]() {
        if (warp == 0) {
          if (elect_one()) {
            const int w = more ? nxt : (int)lds32(wl + (SM_GEN - SM_WIN) - ((wl - (sb + SM_WIN)) % (NENT * 4)));
            if (w >= 0) load_x(&tm_x, &tm_xq, w, wg);
            const int w2 = more ? nxt2 : w;
            if (w2 >= 0) prefetch_l2(mb + mask_off(w2), 8192);
          }
          __syncwarp();
        }
      };
      auto wait_turn = [&]() { mbar_wait(mbar + MB_TURN + (tk & 3) * 8, (tk >> 2) & 1); };
      auto pass_turn = [&]() { if (elect_one()) mbar_arrive(mbar + MB_TURN + ((tk + 1) & 3) * 8); __syncwarp(); };
      auto next_qk = [&]() { issue_qk(qk, dX, opaque(mk_desc(sb + SM_W, 12288, 1024, 1) + z0)); wg_commit(); };
      auto tiles_ready = [&]() {
        if (elect_one()) mbar_arrive(bar_x + (MB_KV - MB_X));
        __syncwarp();
        const uint32_t xphase = (wl >> 2) & 1;
        mbar_wait(bar_x, xphase ^ 1);
        mbar_wait(bar_x + (MB_KV - MB_X), xphase);
      };
      if (__builtin_expect(!masked, 1)) {
        uint32_t of[24];
        {
          float sA[32], sB[32], oA[16], oB[16], oC[16], oD[16];
          uint32_t pA[16], pB[16], pC[16], pD[16];
          wg_fence();
          issue_s<0>(sA, qa, dK);
          issue_s<1>(sB, qa, dK); wg_commit();
          load_eb(pA, eb_base);
          prefetch_next();
          wait_turn();
          wg_wait<0>(); fence_regs(sA); fence_regs(sB);
          TL(7);
          load_eb(pB, eb_base + 8192);
          softmax_fast(sA, pA);
          wg_fence();
          issue_s<2>(sA, qa, dK); wg_commit();
          issue_pv<0>(oA, pA, dV); wg_commit();
          TL(8);
          softmax_fast(sB, pB);
          load_eb(pC, eb_base + 2 * 8192);
          wg_wait<1>(); fence_regs(sA);
          wg_fence();
          issue_s<3>(sB, qa, dK); wg_commit();
          issue_pv<1>(oB, pB, dV); wg_commit();
          TL(9);
          softmax_fast(sA, pC);
          pass_turn();
          load_eb(pD, eb_base + 3 * 8192);
          wg_wait<1>(); fence_regs(sB); fence_regs(oA);
          wg_fence();
          issue_pv<2>(oC, pC, dV); wg_commit();
          TL(10);
          norm_o<0>(oA, of);
          softmax_fast(sB, pD);
          wg_fence();
          issue_pv<3>(oD, pD, dV); wg_commit();
          load_mask(mask_off(more ? nxt : win));
          wg_wait<1>(); fence_regs(oB); fence_regs(oC);
          norm_o<1>(oB, of + 6);
          norm_o<0>(oC, of + 12);
          wg_wait<0>(); fence_regs(oD);
          norm_o<1>(oD, of + 18);
        }
        TL(11);
        float y[48], var[4]; uint32_t yb[24];
        issue_out(y, of, opaque(mk_desc(sb + SM_WO, 128, 1536, 0) + z0));
        char* const optr = out_ptr(out, win, warp, t16);
        if (!more) { ln_head(y, yb, var, dV + 3 * 64); wg_wait<0>(); ln_tail(yb, var, optr); TL(14); break; }
        tiles_ready();
        ln_head(y, yb, var, dV + 3 * 64);
        TL(12);
        next_qk();
        wg_wait<1>();
        TL(13);
        mword = mask_or(ln_tail(yb, var, optr));
      } else {
        if (t16 == 0) {
          uint32_t gl = sb + SM_GEN + wg * NENT * 4;
          while ((int)lds32(gl) >= 0) gl += 4;
          asm volatile("st.shared.u32 [%0], %1;" :: "r"(gl), "r"(win) : "memory");
        }
        __syncwarp();
        prefetch_next();
        wait_turn(); pass_turn();
        if (!more) break;
        load_mask(mask_off(nxt));
        tiles_ready();
        wg_fence();
        next_qk();
        mword = mask_or(0);
      }
      TL(14);
      wl += 4;
      win = nxt; nxt = nxt2;
    }
    wl += 4;
  } else {
    mbar_wait(mbar + MB_WV, 0);
    mbar_wait(mbar + MB_RDY, 0);
    mbar_wait(mbar + MB_TURN, 0);
  }
  bar_sync_n(BAR_AUX + wg, 128);
  if (lds_uniform(sb + SM_GEN + wg * NENT * 4) >= 0) general_windows(&tm_x, &tm_xq, mb, out, (wl >> 2) & 1);
  TG(15);
}

typedef CUresult (*EncodeFn)(CUtensorMap*, CUtensorMapDataType, cuuint32_t, void*, const cuuint64_t*, const cuuint64_t*,
                             const cuuint32_t*, const cuuint32_t*, CUtensorMapInterleave, CUtensorMapSwizzle,
                             CUtensorMapL2promotion, CUtensorMapFloatOOBfill);

}

extern "C" void kernel_launch(void* const* d_in, const int* in_sizes, int n_in, void* d_out, int out_size) {
  static int sms = 0;
  static EncodeFn encode = nullptr;
  if (sms == 0) {
    int dev = 0;
    cudaGetDevice(&dev);
    cudaDeviceGetAttribute(&sms, cudaDevAttrMultiProcessorCount, dev);
    if (sms < 96) sms = 96;
    cudaFuncSetAttribute(swin_kernel, cudaFuncAttributeMaxDynamicSharedMemorySize, SM_TOTAL);
    cudaDriverEntryPointQueryResult qr;
    void* fn = nullptr;
    cudaGetDriverEntryPoint("cuTensorMapEncodeTiled", &fn, cudaEnableDefault, &qr);
    encode = (EncodeFn)fn;
  }
  CUtensorMap tm_x, tm_xq, tm_wqk, tm_wv;
  {
    cuuint64_t dims[5] = {32, 4, IMG, IMG / 4, 3};
    cuuint64_t strides[4] = {PIXB, ROWB, 4 * PIXB, 64};
    cuuint32_t es[5] = {1, 1, 1, 1, 1};
    cuuint32_t box[5] = {32, 4, 8, 2, 3}, boxq[5] = {32, 4, 4, 1, 1};
    encode(&tm_x, CU_TENSOR_MAP_DATA_TYPE_BFLOAT16, 5, d_in[0], dims, strides, box, es, CU_TENSOR_MAP_INTERLEAVE_NONE,
           CU_TENSOR_MAP_SWIZZLE_64B, CU_TENSOR_MAP_L2_PROMOTION_L2_128B, CU_TENSOR_MAP_FLOAT_OOB_FILL_NONE);
    encode(&tm_xq, CU_TENSOR_MAP_DATA_TYPE_BFLOAT16, 5, d_in[0], dims, strides, boxq, es, CU_TENSOR_MAP_INTERLEAVE_NONE,
           CU_TENSOR_MAP_SWIZZLE_64B, CU_TENSOR_MAP_L2_PROMOTION_L2_128B, CU_TENSOR_MAP_FLOAT_OOB_FILL_NONE);
    cuuint64_t qd[3] = {64, 96, 3}, qs[2] = {576, 128}, vd[3] = {32, 96, 3}, vs[2] = {576, 64};
    cuuint32_t qb[3] = {64, 96, 3}, vb[3] = {32, 96, 3};
    encode(&tm_wqk, CU_TENSOR_MAP_DATA_TYPE_BFLOAT16, 3, d_in[1], qd, qs, qb, es, CU_TENSOR_MAP_INTERLEAVE_NONE,
           CU_TENSOR_MAP_SWIZZLE_128B, CU_TENSOR_MAP_L2_PROMOTION_L2_256B, CU_TENSOR_MAP_FLOAT_OOB_FILL_NONE);
    encode(&tm_wv, CU_TENSOR_MAP_DATA_TYPE_BFLOAT16, 3, (char*)d_in[1] + 384, vd, vs, vb, es, CU_TENSOR_MAP_INTERLEAVE_NONE,
           CU_TENSOR_MAP_SWIZZLE_64B, CU_TENSOR_MAP_L2_PROMOTION_L2_256B, CU_TENSOR_MAP_FLOAT_OOB_FILL_NONE);
  }
  swin_kernel<<<sms, 384, SM_TOTAL>>>(
      tm_x, tm_xq, tm_wqk, tm_wv, (const __nv_bfloat16*)d_in[2], (const __nv_bfloat16*)d_in[3],
      (const __nv_bfloat16*)d_in[4], (const __nv_bfloat16*)d_in[5], (const __nv_bfloat16*)d_in[6], (const int*)d_in[7],
      (const __nv_bfloat16*)d_in[8], (__nv_bfloat16*)d_out);
}
```

```cpp
#include <cuda_runtime.h>
#include <cuda.h>
#include <cuda_bf16.h>
#include <stdint.h>
#include <type_traits>

#define TOKEN 3
namespace {

constexpr int IMG   = 384;
constexpr int NWX   = 48;
constexpr int NWIN  = NWX * NWX;
constexpr int PIXB  = 192;
constexpr int ROWB  = IMG * PIXB;
constexpr float LOG2E = 1.4426950408889634f;
constexpr float TAU_FAST_MAX = 50.f;

constexpr int SM_W    = 0;
constexpr int SM_WV   = 3 * 12288;
constexpr int SM_WO   = SM_W + 9 * 6144;
constexpr int SM_EB   = SM_WO + 12 * 1536;
constexpr int SM_WG   = SM_EB + 32768;
constexpr int WG_X    = 0;
constexpr int WG_K    = 12288;
constexpr int WG_V    = WG_K + 14336;
constexpr int WG_SZ   = WG_V + 14336;
constexpr int SM_TAB  = SM_WG + WG_SZ + WG_V + 4096;
constexpr int SM_WOR  = SM_WG + 2 * WG_SZ + WG_K;
constexpr int SM_SEL  = SM_WG + 3 * WG_SZ;
constexpr int SM_MISC = SM_SEL + 256;
constexpr int SM_BAR  = SM_MISC + 16;
constexpr int SM_SLOW = SM_BAR + 104;
constexpr int SM_PAR  = SM_BAR + 160;
constexpr int NENT    = 10;
constexpr int SM_WIN  = SM_PAR + 192;
constexpr int SM_GEN  = SM_WIN + 3 * NENT * 4;
constexpr int SM_TOTAL = SM_GEN + 3 * NENT * 4;
static_assert((SM_WIN & 7) == 0 && (NENT & 1) == 0, "list parity");

template <int SD> __device__ __forceinline__ void wgmma_ss_n192_t1(float (&d)[96], uint64_t da, uint64_t db) {
  if constexpr (SD) {
    asm volatile("{\n.reg .pred p;\nsetp.ne.b32 p, 1, 0;\n"
      "wgmma.mma_async.sync.aligned.m64n192k16.f32.bf16.bf16 {%0, %1, %2, %3, %4, %5, %6, %7, %8, %9, %10, %11, %12, %13, %14, %15, %16, %17, %18, %19, %20, %21, %22, %23, %24, %25, %26, %27, %28, %29, %30, %31, %32, %33, %34, %35, %36, %37, %38, %39, %40, %41, %42, %43, %44, %45, %46, %47, %48, %49, %50, %51, %52, %53, %54, %55, %56, %57, %58, %59, %60, %61, %62, %63, %64, %65, %66, %67, %68, %69, %70, %71, %72, %73, %74, %75, %76, %77, %78, %79, %80, %81, %82, %83, %84, %85, %86, %87, %88, %89, %90, %91, %92, %93, %94, %95}, %96, %97, p, 1, 1, 0, 1;\n}\n"
      : "+f"(d[0]), "+f"(d[1]), "+f"(d[2]), "+f"(d[3]), "+f"(d[4]), "+f"(d[5]), "+f"(d[6]), "+f"(d[7]), "+f"(d[8]), "+f"(d[9]), "+f"(d[10]), "+f"(d[11]), "+f"(d[12]), "+f"(d[13]), "+f"(d[14]), "+f"(d[15]), "+f"(d[16]), "+f"(d[17]), "+f"(d[18]), "+f"(d[19]), "+f"(d[20]), "+f"(d[21]), "+f"(d[22]), "+f"(d[23]), "+f"(d[24]), "+f"(d[25]), "+f"(d[26]), "+f"(d[27]), "+f"(d[28]), "+f"(d[29]), "+f"(d[30]), "+f"(d[31]), "+f"(d[32]), "+f"(d[33]), "+f"(d[34]), "+f"(d[35]), "+f"(d[36]), "+f"(d[37]), "+f"(d[38]), "+f"(d[39]), "+f"(d[40]), "+f"(d[41]), "+f"(d[42]), "+f"(d[43]), "+f"(d[44]), "+f"(d[45]), "+f"(d[46]), "+f"(d[47]), "+f"(d[48]), "+f"(d[49]), "+f"(d[50]), "+f"(d[51]), "+f"(d[52]), "+f"(d[53]), "+f"(d[54]), "+f"(d[55]), "+f"(d[56]), "+f"(d[57]), "+f"(d[58]), "+f"(d[59]), "+f"(d[60]), "+f"(d[61]), "+f"(d[62]), "+f"(d[63]), "+f"(d[64]), "+f"(d[65]), "+f"(d[66]), "+f"(d[67]), "+f"(d[68]), "+f"(d[69]), "+f"(d[70]), "+f"(d[71]), "+f"(d[72]), "+f"(d[73]), "+f"(d[74]), "+f"(d[75]), "+f"(d[76]), "+f"(d[77]), "+f"(d[78]), "+f"(d[79]), "+f"(d[80]), "+f"(d[81]), "+f"(d[82]), "+f"(d[83]), "+f"(d[84]), "+f"(d[85]), "+f"(d[86]), "+f"(d[87]), "+f"(d[88]), "+f"(d[89]), "+f"(d[90]), "+f"(d[91]), "+f"(d[92]), "+f"(d[93]), "+f"(d[94]), "+f"(d[95])
      : "l"(da), "l"(db));
  } else {
    asm volatile("{\n.reg .pred p;\nsetp.ne.b32 p, 0, 0;\n"
      "wgmma.mma_async.sync.aligned.m64n192k16.f32.bf16.bf16 {%0, %1, %2, %3, %4, %5, %6, %7, %8, %9, %10, %11, %12, %13, %14, %15, %16, %17, %18, %19, %20, %21, %22, %23, %24, %25, %26, %27, %28, %29, %30, %31, %32, %33, %34, %35, %36, %37, %38, %39, %40, %41, %42, %43, %44, %45, %46, %47, %48, %49, %50, %51, %52, %53, %54, %55, %56, %57, %58, %59, %60, %61, %62, %63, %64, %65, %66, %67, %68, %69, %70, %71, %72, %73, %74, %75, %76, %77, %78, %79, %80, %81, %82, %83, %84, %85, %86, %87, %88, %89, %90, %91, %92, %93, %94, %95}, %96, %97, p, 1, 1, 0, 1;\n}\n"
      : "=f"(d[0]), "=f"(d[1]), "=f"(d[2]), "=f"(d[3]), "=f"(d[4]), "=f"(d[5]), "=f"(d[6]), "=f"(d[7]), "=f"(d[8]), "=f"(d[9]), "=f"(d[10]), "=f"(d[11]), "=f"(d[12]), "=f"(d[13]), "=f"(d[14]), "=f"(d[15]), "=f"(d[16]), "=f"(d[17]), "=f"(d[18]), "=f"(d[19]), "=f"(d[20]), "=f"(d[21]), "=f"(d[22]), "=f"(d[23]), "=f"(d[24]), "=f"(d[25]), "=f"(d[26]), "=f"(d[27]), "=f"(d[28]), "=f"(d[29]), "=f"(d[30]), "=f"(d[31]), "=f"(d[32]), "=f"(d[33]), "=f"(d[34]), "=f"(d[35]), "=f"(d[36]), "=f"(d[37]), "=f"(d[38]), "=f"(d[39]), "=f"(d[40]), "=f"(d[41]), "=f"(d[42]), "=f"(d[43]), "=f"(d[44]), "=f"(d[45]), "=f"(d[46]), "=f"(d[47]), "=f"(d[48]), "=f"(d[49]), "=f"(d[50]), "=f"(d[51]), "=f"(d[52]), "=f"(d[53]), "=f"(d[54]), "=f"(d[55]), "=f"(d[56]), "=f"(d[57]), "=f"(d[58]), "=f"(d[59]), "=f"(d[60]), "=f"(d[61]), "=f"(d[62]), "=f"(d[63]), "=f"(d[64]), "=f"(d[65]), "=f"(d[66]), "=f"(d[67]), "=f"(d[68]), "=f"(d[69]), "=f"(d[70]), "=f"(d[71]), "=f"(d[72]), "=f"(d[73]), "=f"(d[74]), "=f"(d[75]), "=f"(d[76]), "=f"(d[77]), "=f"(d[78]), "=f"(d[79]), "=f"(d[80]), "=f"(d[81]), "=f"(d[82]), "=f"(d[83]), "=f"(d[84]), "=f"(d[85]), "=f"(d[86]), "=f"(d[87]), "=f"(d[88]), "=f"(d[89]), "=f"(d[90]), "=f"(d[91]), "=f"(d[92]), "=f"(d[93]), "=f"(d[94]), "=f"(d[95])
      : "l"(da), "l"(db));
  }
}
template <int SD> __device__ __forceinline__ void wgmma_ss_n96_t1(float (&d)[48], uint64_t da, uint64_t db) {
  if constexpr (SD) {
    asm volatile("{\n.reg .pred p;\nsetp.ne.b32 p, 1, 0;\n"
      "wgmma.mma_async.sync.aligned.m64n96k16.f32.bf16.bf16 {%0, %1, %2, %3, %4, %5, %6, %7, %8, %9, %10, %11, %12, %13, %14, %15, %16, %17, %18, %19, %20, %21, %22, %23, %24, %25, %26, %27, %28, %29, %30, %31, %32, %33, %34, %35, %36, %37, %38, %39, %40, %41, %42, %43, %44, %45, %46, %47}, %48, %49, p, 1, 1, 0, 1;\n}\n"
      : "+f"(d[0]), "+f"(d[1]), "+f"(d[2]), "+f"(d[3]), "+f"(d[4]), "+f"(d[5]), "+f"(d[6]), "+f"(d[7]), "+f"(d[8]), "+f"(d[9]), "+f"(d[10]), "+f"(d[11]), "+f"(d[12]), "+f"(d[13]), "+f"(d[14]), "+f"(d[15]), "+f"(d[16]), "+f"(d[17]), "+f"(d[18]), "+f"(d[19]), "+f"(d[20]), "+f"(d[21]), "+f"(d[22]), "+f"(d[23]), "+f"(d[24]), "+f"(d[25]), "+f"(d[26]), "+f"(d[27]), "+f"(d[28]), "+f"(d[29]), "+f"(d[30]), "+f"(d[31]), "+f"(d[32]), "+f"(d[33]), "+f"(d[34]), "+f"(d[35]), "+f"(d[36]), "+f"(d[37]), "+f"(d[38]), "+f"(d[39]), "+f"(d[40]), "+f"(d[41]), "+f"(d[42]), "+f"(d[43]), "+f"(d[44]), "+f"(d[45]), "+f"(d[46]), "+f"(d[47])
      : "l"(da), "l"(db));
  } else {
    asm volatile("{\n.reg .pred p;\nsetp.ne.b32 p, 0, 0;\n"
      "wgmma.mma_async.sync.aligned.m64n96k16.f32.bf16.bf16 {%0, %1, %2, %3, %4, %5, %6, %7, %8, %9, %10, %11, %12, %13, %14, %15, %16, %17, %18, %19, %20, %21, %22, %23, %24, %25, %26, %27, %28, %29, %30, %31, %32, %33, %34, %35, %36, %37, %38, %39, %40, %41, %42, %43, %44, %45, %46, %47}, %48, %49, p, 1, 1, 0, 1;\n}\n"
      : "=f"(d[0]), "=f"(d[1]), "=f"(d[2]), "=f"(d[3]), "=f"(d[4]), "=f"(d[5]), "=f"(d[6]), "=f"(d[7]), "=f"(d[8]), "=f"(d[9]), "=f"(d[10]), "=f"(d[11]), "=f"(d[12]), "=f"(d[13]), "=f"(d[14]), "=f"(d[15]), "=f"(d[16]), "=f"(d[17]), "=f"(d[18]), "=f"(d[19]), "=f"(d[20]), "=f"(d[21]), "=f"(d[22]), "=f"(d[23]), "=f"(d[24]), "=f"(d[25]), "=f"(d[26]), "=f"(d[27]), "=f"(d[28]), "=f"(d[29]), "=f"(d[30]), "=f"(d[31]), "=f"(d[32]), "=f"(d[33]), "=f"(d[34]), "=f"(d[35]), "=f"(d[36]), "=f"(d[37]), "=f"(d[38]), "=f"(d[39]), "=f"(d[40]), "=f"(d[41]), "=f"(d[42]), "=f"(d[43]), "=f"(d[44]), "=f"(d[45]), "=f"(d[46]), "=f"(d[47])
      : "l"(da), "l"(db));
  }
}
template <int SD> __device__ __forceinline__ void wgmma_rs_n96_t1(float (&d)[48], uint32_t a0, uint32_t a1, uint32_t a2, uint32_t a3, uint64_t db) {
  if constexpr (SD) {
    asm volatile("{\n.reg .pred p;\nsetp.ne.b32 p, 1, 0;\n"
      "wgmma.mma_async.sync.aligned.m64n96k16.f32.bf16.bf16 {%0, %1, %2, %3, %4, %5, %6, %7, %8, %9, %10, %11, %12, %13, %14, %15, %16, %17, %18, %19, %20, %21, %22, %23, %24, %25, %26, %27, %28, %29, %30, %31, %32, %33, %34, %35, %36, %37, %38, %39, %40, %41, %42, %43, %44, %45, %46, %47}, {%48, %49, %50, %51}, %52, p, 1, 1, 1;\n}\n"
      : "+f"(d[0]), "+f"(d[1]), "+f"(d[2]), "+f"(d[3]), "+f"(d[4]), "+f"(d[5]), "+f"(d[6]), "+f"(d[7]), "+f"(d[8]), "+f"(d[9]), "+f"(d[10]), "+f"(d[11]), "+f"(d[12]), "+f"(d[13]), "+f"(d[14]), "+f"(d[15]), "+f"(d[16]), "+f"(d[17]), "+f"(d[18]), "+f"(d[19]), "+f"(d[20]), "+f"(d[21]), "+f"(d[22]), "+f"(d[23]), "+f"(d[24]), "+f"(d[25]), "+f"(d[26]), "+f"(d[27]), "+f"(d[28]), "+f"(d[29]), "+f"(d[30]), "+f"(d[31]), "+f"(d[32]), "+f"(d[33]), "+f"(d[34]), "+f"(d[35]), "+f"(d[36]), "+f"(d[37]), "+f"(d[38]), "+f"(d[39]), "+f"(d[40]), "+f"(d[41]), "+f"(d[42]), "+f"(d[43]), "+f"(d[44]), "+f"(d[45]), "+f"(d[46]), "+f"(d[47])
      : "r"(a0), "r"(a1), "r"(a2), "r"(a3), "l"(db));
  } else {
    asm volatile("{\n.reg .pred p;\nsetp.ne.b32 p, 0, 0;\n"
      "wgmma.mma_async.sync.aligned.m64n96k16.f32.bf16.bf16 {%0, %1, %2, %3, %4, %5, %6, %7, %8, %9, %10, %11, %12, %13, %14, %15, %16, %17, %18, %19, %20, %21, %22, %23, %24, %25, %26, %27, %28, %29, %30, %31, %32, %33, %34, %35, %36, %37, %38, %39, %40, %41, %42, %43, %44, %45, %46, %47}, {%48, %49, %50, %51}, %52, p, 1, 1, 1;\n}\n"
      : "=f"(d[0]), "=f"(d[1]), "=f"(d[2]), "=f"(d[3]), "=f"(d[4]), "=f"(d[5]), "=f"(d[6]), "=f"(d[7]), "=f"(d[8]), "=f"(d[9]), "=f"(d[10]), "=f"(d[11]), "=f"(d[12]), "=f"(d[13]), "=f"(d[14]), "=f"(d[15]), "=f"(d[16]), "=f"(d[17]), "=f"(d[18]), "=f"(d[19]), "=f"(d[20]), "=f"(d[21]), "=f"(d[22]), "=f"(d[23]), "=f"(d[24]), "=f"(d[25]), "=f"(d[26]), "=f"(d[27]), "=f"(d[28]), "=f"(d[29]), "=f"(d[30]), "=f"(d[31]), "=f"(d[32]), "=f"(d[33]), "=f"(d[34]), "=f"(d[35]), "=f"(d[36]), "=f"(d[37]), "=f"(d[38]), "=f"(d[39]), "=f"(d[40]), "=f"(d[41]), "=f"(d[42]), "=f"(d[43]), "=f"(d[44]), "=f"(d[45]), "=f"(d[46]), "=f"(d[47])
      : "r"(a0), "r"(a1), "r"(a2), "r"(a3), "l"(db));
  }
}
template <int SD> __device__ __forceinline__ void wgmma_rs_n64_t0(float (&d)[32], uint32_t a0, uint32_t a1, uint32_t a2, uint32_t a3, uint64_t db) {
  if constexpr (SD) {
    asm volatile("{\n.reg .pred p;\nsetp.ne.b32 p, 1, 0;\n"
      "wgmma.mma_async.sync.aligned.m64n64k16.f32.bf16.bf16 {%0, %1, %2, %3, %4, %5, %6, %7, %8, %9, %10, %11, %12, %13, %14, %15, %16, %17, %18, %19, %20, %21, %22, %23, %24, %25, %26, %27, %28, %29, %30, %31}, {%32, %33, %34, %35}, %36, p, 1, 1, 0;\n}\n"
      : "+f"(d[0]), "+f"(d[1]), "+f"(d[2]), "+f"(d[3]), "+f"(d[4]), "+f"(d[5]), "+f"(d[6]), "+f"(d[7]), "+f"(d[8]), "+f"(d[9]), "+f"(d[10]), "+f"(d[11]), "+f"(d[12]), "+f"(d[13]), "+f"(d[14]), "+f"(d[15]), "+f"(d[16]), "+f"(d[17]), "+f"(d[18]), "+f"(d[19]), "+f"(d[20]), "+f"(d[21]), "+f"(d[22]), "+f"(d[23]), "+f"(d[24]), "+f"(d[25]), "+f"(d[26]), "+f"(d[27]), "+f"(d[28]), "+f"(d[29]), "+f"(d[30]), "+f"(d[31])
      : "r"(a0), "r"(a1), "r"(a2), "r"(a3), "l"(db));
  } else {
    asm volatile("{\n.reg .pred p;\nsetp.ne.b32 p, 0, 0;\n"
      "wgmma.mma_async.sync.aligned.m64n64k16.f32.bf16.bf16 {%0, %1, %2, %3, %4, %5, %6, %7, %8, %9, %10, %11, %12, %13, %14, %15, %16, %17, %18, %19, %20, %21, %22, %23, %24, %25, %26, %27, %28, %29, %30, %31}, {%32, %33, %34, %35}, %36, p, 1, 1, 0;\n}\n"
      : "=f"(d[0]), "=f"(d[1]), "=f"(d[2]), "=f"(d[3]), "=f"(d[4]), "=f"(d[5]), "=f"(d[6]), "=f"(d[7]), "=f"(d[8]), "=f"(d[9]), "=f"(d[10]), "=f"(d[11]), "=f"(d[12]), "=f"(d[13]), "=f"(d[14]), "=f"(d[15]), "=f"(d[16]), "=f"(d[17]), "=f"(d[18]), "=f"(d[19]), "=f"(d[20]), "=f"(d[21]), "=f"(d[22]), "=f"(d[23]), "=f"(d[24]), "=f"(d[25]), "=f"(d[26]), "=f"(d[27]), "=f"(d[28]), "=f"(d[29]), "=f"(d[30]), "=f"(d[31])
      : "r"(a0), "r"(a1), "r"(a2), "r"(a3), "l"(db));
  }
}
template <int SD> __device__ __forceinline__ void wgmma_rs_n32_t1(float (&d)[16], uint32_t a0, uint32_t a1, uint32_t a2, uint32_t a3, uint64_t db) {
  if constexpr (SD) {
    asm volatile("{\n.reg .pred p;\nsetp.ne.b32 p, 1, 0;\n"
      "wgmma.mma_async.sync.aligned.m64n32k16.f32.bf16.bf16 {%0, %1, %2, %3, %4, %5, %6, %7, %8, %9, %10, %11, %12, %13, %14, %15}, {%16, %17, %18, %19}, %20, p, 1, 1, 1;\n}\n"
      : "+f"(d[0]), "+f"(d[1]), "+f"(d[2]), "+f"(d[3]), "+f"(d[4]), "+f"(d[5]), "+f"(d[6]), "+f"(d[7]), "+f"(d[8]), "+f"(d[9]), "+f"(d[10]), "+f"(d[11]), "+f"(d[12]), "+f"(d[13]), "+f"(d[14]), "+f"(d[15])
      : "r"(a0), "r"(a1), "r"(a2), "r"(a3), "l"(db));
  } else {
    asm volatile("{\n.reg .pred p;\nsetp.ne.b32 p, 0, 0;\n"
      "wgmma.mma_async.sync.aligned.m64n32k16.f32.bf16.bf16 {%0, %1, %2, %3, %4, %5, %6, %7, %8, %9, %10, %11, %12, %13, %14, %15}, {%16, %17, %18, %19}, %20, p, 1, 1, 1;\n}\n"
      : "=f"(d[0]), "=f"(d[1]), "=f"(d[2]), "=f"(d[3]), "=f"(d[4]), "=f"(d[5]), "=f"(d[6]), "=f"(d[7]), "=f"(d[8]), "=f"(d[9]), "=f"(d[10]), "=f"(d[11]), "=f"(d[12]), "=f"(d[13]), "=f"(d[14]), "=f"(d[15])
      : "r"(a0), "r"(a1), "r"(a2), "r"(a3), "l"(db));
  }
}
template <int SD> __device__ __forceinline__ void wgmma_rs_n8_t0(float (&d)[4], uint32_t a0, uint32_t a1, uint32_t a2, uint32_t a3, uint64_t db) {
  if constexpr (SD) {
    asm volatile("{\n.reg .pred p;\nsetp.ne.b32 p, 1, 0;\n"
      "wgmma.mma_async.sync.aligned.m64n8k16.f32.bf16.bf16 {%0, %1, %2, %3}, {%4, %5, %6, %7}, %8, p, 1, 1, 0;\n}\n"
      : "+f"(d[0]), "+f"(d[1]), "+f"(d[2]), "+f"(d[3])
      : "r"(a0), "r"(a1), "r"(a2), "r"(a3), "l"(db));
  } else {
    asm volatile("{\n.reg .pred p;\nsetp.ne.b32 p, 0, 0;\n"
      "wgmma.mma_async.sync.aligned.m64n8k16.f32.bf16.bf16 {%0, %1, %2, %3}, {%4, %5, %6, %7}, %8, p, 1, 1, 0;\n}\n"
      : "=f"(d[0]), "=f"(d[1]), "=f"(d[2]), "=f"(d[3])
      : "r"(a0), "r"(a1), "r"(a2), "r"(a3), "l"(db));
  }
}

__device__ __forceinline__ void wg_fence()  { asm volatile("wgmma.fence.sync.aligned;" ::: "memory"); }
__device__ __forceinline__ void wg_commit() { asm volatile("wgmma.commit_group.sync.aligned;" ::: "memory"); }
template <int N> __device__ __forceinline__ void wg_wait() { asm volatile("wgmma.wait_group.sync.aligned %0;" :: "n"(N) : "memory"); }
template <int N> __device__ __forceinline__ void fence_regs(float (&d)[N]) {
#pragma unroll
  for (int i = 0; i < N; i++) asm volatile("" : "+f"(d[i]) :: "memory");
}
__device__ __forceinline__ constexpr uint64_t mk_desc(uint32_t addr, uint32_t lbo, uint32_t sbo, uint32_t swz) {
  return (uint64_t)(addr >> 4) | ((uint64_t)(lbo >> 4) << 16) | ((uint64_t)(sbo >> 4) << 32) | ((uint64_t)swz << 62);
}
__device__ __forceinline__ uint32_t pack_bf16(float lo, float hi) {
  uint32_t r; asm("cvt.rn.bf16x2.f32 %0, %1, %2;" : "=r"(r) : "f"(hi), "f"(lo)); return r;
}
__device__ __forceinline__ uint32_t hmul2(uint32_t a, uint32_t b) {
  uint32_t r; asm("mul.rn.bf16x2 %0, %1, %2;" : "=r"(r) : "r"(a), "r"(b)); return r;
}
template <int HI> __device__ __forceinline__ uint32_t hmul2_b(uint32_t a, uint32_t b) {
  uint32_t r;
  if (HI) asm("{\n.reg .b16 l, h;\n.reg .b32 t;\nmov.b32 {l, h}, %2;\nmov.b32 t, {h, h};\nmul.rn.bf16x2 %0, %1, t;\n}\n" : "=r"(r) : "r"(a), "r"(b));
  else    asm("{\n.reg .b16 l, h;\n.reg .b32 t;\nmov.b32 {l, h}, %2;\nmov.b32 t, {l, l};\nmul.rn.bf16x2 %0, %1, t;\n}\n" : "=r"(r) : "r"(a), "r"(b));
  return r;
}
__device__ __forceinline__ uint32_t hfma2(uint32_t a, uint32_t b, uint32_t c) {
  uint32_t r; asm("fma.rn.bf16x2 %0, %1, %2, %3;" : "=r"(r) : "r"(a), "r"(b), "r"(c)); return r;
}
__device__ __forceinline__ float ex2(float x) { float r; asm("ex2.approx.ftz.f32 %0, %1;" : "=f"(r) : "f"(x)); return r; }
__device__ __forceinline__ float rsq(float x) { float r; asm("rsqrt.approx.ftz.f32 %0, %1;" : "=f"(r) : "f"(x)); return r; }
__device__ __forceinline__ float rcp(float x) { float r; asm("rcp.approx.ftz.f32 %0, %1;" : "=f"(r) : "f"(x)); return r; }
__device__ __forceinline__ void stsm4(uint32_t addr, uint32_t r0, uint32_t r1, uint32_t r2, uint32_t r3) {
  asm volatile("stmatrix.sync.aligned.m8n8.x4.shared.b16 [%0], {%1,%2,%3,%4};" :: "r"(addr), "r"(r0), "r"(r1), "r"(r2), "r"(r3) : "memory");
}
__device__ __forceinline__ void fence_async() { asm volatile("fence.proxy.async.shared::cta;" ::: "memory"); }
__device__ __forceinline__ void bar_sync_n(int id, int n) { asm volatile("bar.sync %0, %1;" :: "r"(id), "r"(n) : "memory"); }
__device__ __forceinline__ void bar_arrive_n(int id, int n) { asm volatile("bar.arrive %0, %1;" :: "r"(id), "r"(n) : "memory"); }
__device__ __forceinline__ bool bar_wg_or(int id, bool v) {
  uint32_t r;
  asm volatile("{\n.reg .pred p, q;\nsetp.ne.u32 q, %2, 0;\nbar.red.or.pred p, %1, 128, q;\nselp.u32 %0, 0, 1, p;\n}\n"
               : "=r"(r) : "r"(id), "r"((uint32_t)v) : "memory");
  return __ballot_sync(0xffffffffu, r != 0) == 0;
}
__device__ __forceinline__ void mbar_init(uint32_t bar, uint32_t cnt) { asm volatile("mbarrier.init.shared::cta.b64 [%0], %1;" :: "r"(bar), "r"(cnt) : "memory"); }
__device__ __forceinline__ void mbar_expect(uint32_t bar, uint32_t bytes) {
  asm volatile("mbarrier.arrive.expect_tx.shared::cta.b64 _, [%0], %1;" :: "r"(bar), "r"(bytes) : "memory");
}
__device__ __forceinline__ void mbar_arrive(uint32_t bar) { asm volatile("mbarrier.arrive.shared::cta.b64 _, [%0];" :: "r"(bar) : "memory"); }
__device__ __forceinline__ void mbar_wait(uint32_t bar, uint32_t parity) {
  asm volatile("{\n.reg .pred p;\n.reg .u32 n;\nmov.u32 n, 0;\n"
               "LW_%=:\nmbarrier.try_wait.parity.shared::cta.b64 p, [%0], %1;\n@p bra.uni LD_%=;\n"
               "add.u32 n, n, 1;\nsetp.lt.u32 p, n, 4194304;\n@p bra.uni LW_%=;\ntrap;\nLD_%=:\n}\n"
               :: "r"(bar), "r"(parity) : "memory");
}
__device__ __forceinline__ void tma5(uint32_t dst, const CUtensorMap* m, uint32_t bar, int c0, int c1, int c2, int c3, int c4) {
  asm volatile("cp.async.bulk.tensor.5d.shared::cluster.global.mbarrier::complete_tx::bytes [%0], [%1, {%3, %4, %5, %6, %7}], [%2];"
               :: "r"(dst), "l"(m), "r"(bar), "r"(c0), "r"(c1), "r"(c2), "r"(c3), "r"(c4) : "memory");
}
__device__ __forceinline__ void tma3(uint32_t dst, const CUtensorMap* m, uint32_t bar, int c0, int c1, int c2) {
  asm volatile("cp.async.bulk.tensor.3d.shared::cluster.global.mbarrier::complete_tx::bytes [%0], [%1, {%3, %4, %5}], [%2];"
               :: "r"(dst), "l"(m), "r"(bar), "r"(c0), "r"(c1), "r"(c2) : "memory");
}
__device__ __forceinline__ void bulk_g2s(uint32_t dst, const void* src, uint32_t bytes, uint32_t bar) {
  asm volatile("cp.async.bulk.shared::cluster.global.mbarrier::complete_tx::bytes [%0], [%1], %2, [%3];"
               :: "r"(dst), "l"(src), "r"(bytes), "r"(bar) : "memory");
}
__device__ __forceinline__ uint32_t lds32(uint32_t addr) {
  uint32_t v; asm volatile("ld.shared.u32 %0, [%1];" : "=r"(v) : "r"(addr)); return v;
}
__device__ __forceinline__ uint64_t opaque(uint64_t v) { asm volatile("" : "+l"(v)); return v; }
__device__ __forceinline__ uint4 lds128(uint32_t addr) {
  uint4 v; asm volatile("ld.shared.v4.u32 {%0,%1,%2,%3}, [%4];" : "=r"(v.x), "=r"(v.y), "=r"(v.z), "=r"(v.w) : "r"(addr)); return v;
}
__device__ __forceinline__ uint4 ldg128_stream(const void* p) {
  uint4 v; asm volatile("ld.global.nc.L1::no_allocate.v4.u32 {%0,%1,%2,%3}, [%4];" : "=r"(v.x), "=r"(v.y), "=r"(v.z), "=r"(v.w) : "l"(p)); return v;
}
__device__ __forceinline__ void stg128(void* p, uint32_t a, uint32_t b, uint32_t c, uint32_t d) {
  asm volatile("st.global.v4.u32 [%0], {%1,%2,%3,%4};" :: "l"(p), "r"(a), "r"(b), "r"(c), "r"(d) : "memory");
}
__device__ __forceinline__ void prefetch_l2(const void* p, uint32_t bytes) {
  asm volatile("cp.async.bulk.prefetch.L2.global [%0], %1;" :: "l"(p), "r"(bytes) : "memory");
}
__device__ __forceinline__ bool elect_one() {
  uint32_t r; asm volatile("{\n.reg .pred p;\nelect.sync _|p, 0xffffffff;\nselp.u32 %0, 1, 0, p;\n}\n" : "=r"(r)); return r != 0;
}
__device__ __forceinline__ float bf_lo(uint32_t u) { return __uint_as_float(u << 16); }
__device__ __forceinline__ float bf_hi(uint32_t u) { return __uint_as_float(u & 0xFFFF0000u); }
__device__ __forceinline__ float rbf(float x) { return bf_lo(pack_bf16(x, 0.f)); }
__device__ __forceinline__ int orig_tok(int r) { return ((r & 31) >> 2) * 8 + (r >> 5) * 4 + (r & 3); }

__device__ __forceinline__ int slot_window(int s, bool g132) {
  constexpr int A0 = 396 + 264 + 60, A1 = A0 + 72, B0 = 3 * 396 + 264 + 60, B1 = B0 + 23;
  const int i = s - (s >= B1 ? 95 : s >= A1 ? 72 : 0);
  const int k = s >= B0 ? s - B0 + 72 : s - A0;
  const bool border = (s >= A0 && s < A1) || (s >= B0 && s < B1);
  const int iy = (i * 2789) >> 17, sy = (s * 2731) >> 17;
  const int wa = border ? (k < 48 ? (47 << 8 | k) : ((k - 48) << 8 | 47)) : (iy << 8 | (i - iy * 47));
  return g132 ? wa : (sy << 8 | (s - sy * 48));
}

#define EB_WORD(e, j, a) ((((a) ^ ((j) & 1)) == 0) ? (e).x : (((a) ^ ((j) & 1)) == 1) ? (e).y : (((a) ^ ((j) & 1)) == 2) ? (e).z : (e).w)

__device__ __forceinline__ void load_eb(uint32_t (&e)[16], uint32_t eb_addr) {
#pragma unroll
  for (int j = 0; j < 4; j++) {
    const uint4 v = lds128(eb_addr + j * 2048);
#pragma unroll
    for (int a = 0; a < 4; a++) e[4 * j + a] = EB_WORD(v, j, a);
  }
}
__device__ __forceinline__ void softmax_fast(const float (&s)[32], uint32_t (&p)[16]) {
#pragma unroll
  for (int i = 0; i < 16; i++) p[i] = hmul2(pack_bf16(ex2(s[2 * i]), ex2(s[2 * i + 1])), p[i]);
}
__device__ __forceinline__ uint32_t hmax2(uint32_t a, uint32_t b) {
  uint32_t r; asm("max.bf16x2 %0, %1, %2;" : "=r"(r) : "r"(a), "r"(b)); return r;
}
__device__ __forceinline__ uint32_t hmax2_nan(uint32_t a, uint32_t b) {
  uint32_t r; asm("max.NaN.bf16x2 %0, %1, %2;" : "=r"(r) : "r"(a), "r"(b)); return r;
}
__device__ __forceinline__ float quad_max(float m) {
  m = fmaxf(m, __shfl_xor_sync(0xffffffffu, m, 1));
  return fmaxf(m, __shfl_xor_sync(0xffffffffu, m, 2));
}
__device__ __forceinline__ void softmax_true_max(const float (&s)[32], uint32_t (&p)[16]) {
  float m0 = s[0], m1 = s[2];
#pragma unroll
  for (int g = 0; g < 8; g++) {
    m0 = fmaxf(m0, fmaxf(s[4 * g + 0], s[4 * g + 1]));
    m1 = fmaxf(m1, fmaxf(s[4 * g + 2], s[4 * g + 3]));
  }
  m0 = quad_max(m0); m1 = quad_max(m1);
  uint32_t n0 = 0, n1 = 0;
#pragma unroll
  for (int g = 0; g < 8; g++) {
    p[2 * g + 0] = hmul2(pack_bf16(ex2(s[4 * g + 0] - m0), ex2(s[4 * g + 1] - m0)), p[2 * g + 0]);
    p[2 * g + 1] = hmul2(pack_bf16(ex2(s[4 * g + 2] - m1), ex2(s[4 * g + 3] - m1)), p[2 * g + 1]);
    n0 = hmax2(n0, p[2 * g]); n1 = hmax2(n1, p[2 * g + 1]);
  }
  const uint32_t r = pack_bf16(rcp(quad_max(fmaxf(bf_lo(n0), bf_hi(n0)))), rcp(quad_max(fmaxf(bf_lo(n1), bf_hi(n1)))));
#pragma unroll
  for (int g = 0; g < 8; g++) { p[2 * g] = hmul2_b<0>(p[2 * g], r); p[2 * g + 1] = hmul2_b<1>(p[2 * g + 1], r); }
}
template <int H> __device__ __forceinline__ void issue_s(float (&s)[32], const uint32_t (&q)[24], uint64_t dK) {
  constexpr int Q0 = (H == 0 ? 0 : H == 1 ? 4 : H == 2 ? 12 : 16), P0 = (H == 0 ? 0 : H == 1 ? 3 : H == 2 ? 7 : 10);
  wgmma_rs_n64_t0<0>(s, q[Q0], q[Q0 + 1], q[Q0 + 2], q[Q0 + 3], dK + P0 * 64);
  wgmma_rs_n64_t0<1>(s, q[Q0 + 4], q[Q0 + 5], q[Q0 + 6], q[Q0 + 7], dK + P0 * 64 + 128);
}
template <int H> __device__ __forceinline__ void issue_pv(float (&o)[16], const uint32_t (&p)[16], uint64_t dV) {
  constexpr int P0 = (H == 0 ? 0 : H == 1 ? 3 : H == 2 ? 7 : 10);
  wgmma_rs_n32_t1<0>(o, p[0], p[1], p[2], p[3], dV + P0 * 64);
  wgmma_rs_n32_t1<1>(o, p[4], p[5], p[6], p[7], dV + P0 * 64 + 16);
  wgmma_rs_n32_t1<1>(o, p[8], p[9], p[10], p[11], dV + P0 * 64 + 32);
  wgmma_rs_n32_t1<1>(o, p[12], p[13], p[14], p[15], dV + P0 * 64 + 48);
}
__device__ __forceinline__ void issue_proj(float (&d)[48], uint64_t dX, uint64_t dW) {
#pragma unroll
  for (int s = 0; s < 6; s++) {
    const uint64_t a = dX + (s >> 1) * 256 + (s & 1) * 2, b = dW + s * 64;
    if (s == 0) wgmma_ss_n96_t1<0>(d, a, b); else wgmma_ss_n96_t1<1>(d, a, b);
  }
}
__device__ __forceinline__ void issue_qk(float (&d)[96], uint64_t dX, uint64_t dW) {
#pragma unroll
  for (int s = 0; s < 6; s++) {
    const uint64_t a = dX + (s >> 1) * 256 + (s & 1) * 2, b = dW + s * 128;
    if (s == 0) wgmma_ss_n192_t1<0>(d, a, b); else wgmma_ss_n192_t1<1>(d, a, b);
  }
}
__device__ __forceinline__ void pack_sumsq(const float* a, uint32_t (&f)[24], uint32_t (&sq)[8], uint32_t init) {
#pragma unroll
  for (int i = 0; i < 24; i++) f[i] = pack_bf16(a[2 * i], a[2 * i + 1]);
#pragma unroll
  for (int h = 0; h < 4; h++)
#pragma unroll
    for (int r = 0; r < 2; r++) {
      uint32_t u = f[6 * h + r], v = f[6 * h + 2 + r], w = f[6 * h + 4 + r];
      sq[2 * h + r] = hfma2(w, w, hfma2(v, v, hfma2(u, u, init)));
    }
}
__device__ __forceinline__ void scale_heads(uint32_t (&f)[24], const float (&r)[8]) {
#pragma unroll
  for (int h = 0; h < 4; h++) {
    const uint32_t p = pack_bf16(r[2 * h], r[2 * h + 1]);
#pragma unroll
    for (int c = 0; c < 3; c++) {
      f[6 * h + 2 * c] = hmul2_b<0>(f[6 * h + 2 * c], p);
      f[6 * h + 2 * c + 1] = hmul2_b<1>(f[6 * h + 2 * c + 1], p);
    }
  }
}
template <int ODD> __device__ __forceinline__ void norm_o(const float (&o)[16], uint32_t* of) {
  constexpr int SO = ODD ? 0 : 12, VO = ODD ? 4 : 0;
  const uint32_t p = pack_bf16(rcp(o[SO]), rcp(o[SO + 2]));
#pragma unroll
  for (int g = 0; g < 3; g++) {
    of[2 * g + 0] = hmul2_b<0>(pack_bf16(o[VO + 4 * g + 0], o[VO + 4 * g + 1]), p);
    of[2 * g + 1] = hmul2_b<1>(pack_bf16(o[VO + 4 * g + 2], o[VO + 4 * g + 3]), p);
  }
}

#define TL(i)
#define TG(i)

constexpr int BAR_KV = 1;
constexpr int BAR_AUX = 4;
constexpr int BAR_TAB = 7, BAR_SETUP = 8;
constexpr int MB_WQK = 0, MB_X = 8, MB_KV = 32, MB_WV = 56, MB_WO = 64, MB_TURN = 72, MB_RDY = 128;
constexpr uint32_t sb = 1024, mbar = sb + SM_BAR;
constexpr uint32_t EPS8 = 0x2A0D2A0Du;

__device__ __forceinline__ void load_x(const CUtensorMap* tm_x, const CUtensorMap* tm_xq, int w, int g) {
  const uint32_t dst = sb + SM_WG + g * WG_SZ + WG_X, bar = mbar + MB_X + 8 * g;
  const int wy = (w >> 8) & 255, wx = w & 255;
  mbar_expect(bar, 12288);
  if (wy != NWX - 1 && wx != NWX - 1) {
    tma5(dst, tm_x, bar, 0, 0, wy * 8 + 4, wx * 2 + 1, 0);
  } else {
#pragma unroll 1
    for (int i = 0; i < 12; i++) {
      const int q = i & 3, c = i >> 2;
      int y = wy * 8 + 4 + (q & 1) * 4; if (y >= IMG) y -= IMG;
      int xq = wx * 2 + 1 + (q >> 1);   if (xq >= IMG / 4) xq -= IMG / 4;
      tma5(dst + i * 1024, tm_xq, bar, 0, 0, y, xq, c);
    }
  }
}
__device__ __forceinline__ uint32_t mask_off(int w) { return (uint32_t)(((w >> 8) & 255) * NWX + (w & 255)) * 8192u; }
__device__ __forceinline__ int lds_uniform(uint32_t addr) { return __shfl_sync(0xffffffffu, lds32(addr), 0); }

__device__ __forceinline__ void qkv_epilogue(float (&qk)[96], uint32_t (&qa)[24], uint64_t dX, uint64_t dWv, uint32_t k_dst) {
  uint32_t ka[24], sk[8], sq[8];
  float k01[4], k23[4], q01[4], q23[4], vv[48];
  constexpr uint64_t dSel = mk_desc(sb + SM_SEL, 128, 256, 0);
  wg_wait<0>(); fence_regs(qk);
  pack_sumsq(qk + 48, ka, sk, EPS8);
  pack_sumsq(qk, qa, sq, EPS8);
  wg_fence();
  wgmma_rs_n8_t0<0>(k01, sk[0], sk[1], sk[2], sk[3], dSel);
  wgmma_rs_n8_t0<0>(k23, sk[4], sk[5], sk[6], sk[7], dSel);
  wgmma_rs_n8_t0<0>(q01, sq[0], sq[1], sq[2], sq[3], dSel);
  wgmma_rs_n8_t0<0>(q23, sq[4], sq[5], sq[6], sq[7], dSel);
  wg_commit();
  issue_proj(vv, dX, dWv); wg_commit();
  const uint4 qs = lds128(sb + SM_MISC);
  wg_wait<1>(); fence_regs(k01); fence_regs(k23); fence_regs(q01); fence_regs(q23);
  const float rk[8] = {rsq(k01[0]), rsq(k01[2]), rsq(k01[1]), rsq(k01[3]), rsq(k23[0]), rsq(k23[2]), rsq(k23[1]), rsq(k23[3])};
  scale_heads(ka, rk);
#pragma unroll
  for (int i = 0; i < 6; i++) stsm4(k_dst + (i + (i >= 3)) * 1024, ka[2 * i], ka[2 * i + 1], ka[12 + 2 * i], ka[12 + 2 * i + 1]);
  wg_wait<0>(); fence_regs(vv);
#pragma unroll
  for (int i = 0; i < 6; i++)
    stsm4(k_dst + (WG_V - WG_K) + (i + (i >= 3)) * 1024, pack_bf16(vv[4 * i], vv[4 * i + 1]), pack_bf16(vv[4 * i + 2], vv[4 * i + 3]),
          pack_bf16(vv[24 + 4 * i], vv[24 + 4 * i + 1]), pack_bf16(vv[24 + 4 * i + 2], vv[24 + 4 * i + 3]));
  const float s0 = __uint_as_float(qs.x), s1 = __uint_as_float(qs.y), s2 = __uint_as_float(qs.z), s3 = __uint_as_float(qs.w);
  const float rq[8] = {rsq(q01[0]) * s0, rsq(q01[2]) * s0, rsq(q01[1]) * s1, rsq(q01[3]) * s1,
                       rsq(q23[0]) * s2, rsq(q23[2]) * s2, rsq(q23[1]) * s3, rsq(q23[3]) * s3};
  scale_heads(qa, rq);
  fence_async();
}
__device__ __forceinline__ void issue_out(float (&y)[48], const uint32_t (&of)[24], uint64_t dWo) {
  wg_fence();
#pragma unroll
  for (int s = 0; s < 6; s++) {
    if (s == 0) wgmma_rs_n96_t1<0>(y, of[0], of[1], of[2], of[3], dWo);
    else wgmma_rs_n96_t1<1>(y, of[4 * s], of[4 * s + 1], of[4 * s + 2], of[4 * s + 3], dWo + s * 16);
  }
  wg_commit();
}
__device__ __forceinline__ void ln_head(float (&y)[48], uint32_t (&yb)[24], float (&var)[4], uint64_t dOnes) {
  uint32_t sy[8];
  wg_wait<0>(); fence_regs(y);
  pack_sumsq(y, yb, sy, 0u);
  wg_fence();
  wgmma_rs_n8_t0<0>(var, sy[0], sy[1], sy[2], sy[3], dOnes);
  wgmma_rs_n8_t0<1>(var, sy[4], sy[5], sy[6], sy[7], dOnes);
  wg_commit();
}
__device__ __forceinline__ char* out_ptr(__nv_bfloat16* out, int win, int warp, uint32_t t16) {
  int py = ((win >> 8) & 255) * 8 + 4 + (warp & 1) * 4;  if (py >= IMG) py -= IMG;
  int px = (win & 255) * 8 + 4 + (warp >> 1) * 4;        if (px >= IMG) px -= IMG;
  return reinterpret_cast<char*>(out) + ((uint32_t)(py * IMG + px) * PIXB - warp * 512 + t16 + ((t16 & 0xC0) << 1) + (t16 & 0x100) * 287);
}
__device__ __forceinline__ uint32_t ln_tail(const uint32_t (&yb)[24], float (&var)[4], char* optr) {
  fence_regs(var);
  uint32_t last;
  const uint32_t nn = pack_bf16(rsq(fmaf(var[0], 1.f / 96.f, 1e-5f)), rsq(fmaf(var[2], 1.f / 96.f, 1e-5f)));
#pragma unroll
  for (int j = 0; j < 3; j++) {
    stg128(optr + j * 64, hmul2_b<0>(yb[8 * j], nn), hmul2_b<0>(yb[8 * j + 2], nn), hmul2_b<0>(yb[8 * j + 4], nn), hmul2_b<0>(yb[8 * j + 6], nn));
    last = hmul2_b<1>(yb[8 * j + 7], nn);
    stg128(optr + 2 * ROWB + j * 64, hmul2_b<1>(yb[8 * j + 1], nn), hmul2_b<1>(yb[8 * j + 3], nn), hmul2_b<1>(yb[8 * j + 5], nn), last);
  }
  return last;
}

__device__ __forceinline__ void general_windows(const CUtensorMap* tm_x, const CUtensorMap* tm_xq, const char* mb, __nv_bfloat16* out, uint32_t xph) {
  int tid;
  asm volatile("mov.u32 %0, %%tid.x;" : "=r"(tid));
  const int lane = tid & 31;
  const int warp = __shfl_sync(0xffffffffu, (tid >> 5) & 3, 0), wg = __shfl_sync(0xffffffffu, tid >> 7, 0);
  const uint32_t t16 = (tid & 127) * 16, wgb = sb + SM_WG + wg * WG_SZ, bar_x = mbar + MB_X + 8 * wg;
  const uint32_t k_dst = wgb + WG_K + (lane >> 4) * 7168 + warp * 256 + (lane & 15) * 16;
  const uint32_t slow_heads = lds_uniform(sb + SM_SLOW);
  const uint64_t dX = mk_desc(WG_X, 16, 512, 2) + (wgb >> 4), dK = mk_desc(WG_K, 1024, 128, 0) + (wgb >> 4), dV = mk_desc(WG_V, 128, 1024, 0) + (wgb >> 4);
#pragma unroll 1
  for (uint32_t gl = sb + SM_GEN + wg * NENT * 4;; gl += 4) {
    const int win = lds_uniform(gl);
    if (win < 0) break;
    uint32_t qa[24], of[24], mk[16];
    uint32_t tm;
    {
      const char* mrow = mb + (mask_off(win) + (orig_tok(16 * warp + (lane >> 2)) * 64 + ((lane >> 1) & 1) * 8 + (lane & 1) * 2) * 2);
#pragma unroll
      for (int Gk = 0; Gk < 8; Gk++) {
        mk[2 * Gk] = __ldg(reinterpret_cast<const uint32_t*>(mrow + (Gk & 3) * 32 + (Gk >> 2) * 8));
        mk[2 * Gk + 1] = __ldg(reinterpret_cast<const uint32_t*>(mrow + 2048 + (Gk & 3) * 32 + (Gk >> 2) * 8));
      }
      float qk[96];
      mbar_wait(bar_x, xph); xph ^= 1;
      wg_fence();
      issue_qk(qk, dX, mk_desc(sb + SM_W, 12288, 1024, 1)); wg_commit();
      uint32_t x0 = mk[0], x1 = mk[1], any = 0;
#pragma unroll
      for (int i = 0; i < 16; i += 2) { x0 = hmax2_nan(x0, mk[i]); x1 = hmax2_nan(x1, mk[i + 1]); any |= mk[i] | mk[i + 1]; }
      const bool nan_in = !(bf_lo(x0) == bf_lo(x0) && bf_hi(x0) == bf_hi(x0) && bf_lo(x1) == bf_lo(x1) && bf_hi(x1) == bf_hi(x1));
      const float r0 = quad_max(fmaxf(bf_lo(x0), bf_hi(x0))), r1 = quad_max(fmaxf(bf_lo(x1), bf_hi(x1)));
      tm = bar_wg_or(BAR_KV + wg, nan_in || !(fabsf(r0) <= 8.f && fabsf(r1) <= 8.f) || (slow_heads != 0 && (any & 0x7FFF7FFFu) != 0)) ? 0x1Fu : slow_heads;
      if (tm == 0) {
#pragma unroll
        for (int i = 0; i < 16; i++) mk[i] = pack_bf16(ex2(bf_lo(mk[i]) * LOG2E), ex2(bf_hi(mk[i]) * LOG2E));
      }
      qkv_epilogue(qk, qa, dX, mk_desc(sb + SM_WV, 6144, 512, 2), k_dst);
    }
    bar_sync_n(BAR_AUX + wg, 128);
    if (warp == 0 && elect_one()) {
      const int nxt = lds32(gl + 4);
      if (nxt >= 0) { load_x(tm_x, tm_xq, nxt, wg); prefetch_l2(mb + mask_off(nxt), 8192); }
    }
    __syncwarp();
    auto head = [&](float (&sc)[32], uint32_t (&p)[16], bool tmax) {
      if (tmax) {
        if (tm & 16) {
#pragma unroll
          for (int i = 0; i < 16; i++) {
            sc[2 * i] = fmaf(bf_lo(mk[i]), LOG2E, sc[2 * i]); sc[2 * i + 1] = fmaf(bf_hi(mk[i]), LOG2E, sc[2 * i + 1]);
          }
        }
        softmax_true_max(sc, p);
      } else {
        if (tm == 0) {
#pragma unroll
          for (int i = 0; i < 16; i++) p[i] = hmul2(p[i], mk[i]);
        }
        softmax_fast(sc, p);
      }
    };
#pragma unroll
    for (int i = 0; i < 24; i++) of[i] = 0;
#pragma unroll 1
    for (int hp = 0; hp < 2; hp++) {
      float sA[32], sB[32], oA[16], oB[16]; uint32_t p[16];
      const uint32_t po = hp * 7 * 64;
      wg_fence();
      issue_s<0>(sA, qa, dK + po);
      issue_s<1>(sB, qa, dK + po); wg_commit();
      load_eb(p, sb + SM_EB + t16 + hp * 16384);
      wg_wait<0>(); fence_regs(sA); fence_regs(sB);
#pragma unroll
      for (int i = 0; i < 12; i++) { qa[i] = qa[i + 12]; of[i] = of[i + 12]; }
      head(sA, p, (tm >> (2 * hp)) & 1);
      wg_fence(); issue_pv<0>(oA, p, dV + po); wg_commit();
      uint32_t p2[16];
      load_eb(p2, sb + SM_EB + t16 + hp * 16384 + 8192);
      head(sB, p2, (tm >> (2 * hp + 1)) & 1);
      wg_fence(); issue_pv<1>(oB, p2, dV + po); wg_commit();
      wg_wait<1>(); fence_regs(oA);
      norm_o<0>(oA, of + 12);
      wg_wait<0>(); fence_regs(oB);
      norm_o<1>(oB, of + 18);
    }
    float y[48], var[4]; uint32_t yb[24];
    issue_out(y, of, mk_desc(sb + SM_WO, 128, 1536, 0));
    ln_head(y, yb, var, dV + 3 * 64);
    wg_wait<0>();
    ln_tail(yb, var, out_ptr(out, win, warp, t16));
  }
}

__global__ void __launch_bounds__(384, 1)
swin_kernel(const __grid_constant__ CUtensorMap tm_x, const __grid_constant__ CUtensorMap tm_xq, const __grid_constant__ CUtensorMap tm_wqk,
            const __grid_constant__ CUtensorMap tm_wv,
            const __nv_bfloat16* __restrict__ wo,
            const __nv_bfloat16* __restrict__ logit_scale, const __nv_bfloat16* __restrict__ w1, const __nv_bfloat16* __restrict__ w2,
            const __nv_bfloat16* __restrict__ coords, const int* __restrict__ rel_idx, const __nv_bfloat16* __restrict__ mask,
            __nv_bfloat16* __restrict__ out) {
  extern __shared__ __align__(1024) uint8_t smem[];
  const int tid = threadIdx.x, lane = tid & 31;
  const int warp = __shfl_sync(0xffffffffu, (tid >> 5) & 3, 0), wg = __shfl_sync(0xffffffffu, tid >> 7, 0);
  const uint32_t t16 = (tid & 127) * 16;
  const int G = gridDim.x;
  const uint32_t wgb = sb + SM_WG + wg * WG_SZ;
  const uint32_t bar_x = mbar + MB_X + 8 * wg;
  const char* mb = reinterpret_cast<const char*>(mask);
  TL(0); TG(14);

  uint4 mw[4];
  auto load_mask = [&](uint32_t off) {
    const char* src = mb + (off + t16);
#pragma unroll
    for (int i = 0; i < 4; i++) mw[i] = ldg128_stream(src + i * 2048);
  };
  auto mask_or = [&](uint32_t seed) {
    uint32_t r = seed & 0x80008000u;
#pragma unroll
    for (int i = 0; i < 4; i++) {
      asm("lop3.b32 %0, %0, %1, %2, 0xFE;" : "+r"(r) : "r"(mw[i].x), "r"(mw[i].y));
      asm("lop3.b32 %0, %0, %1, %2, 0xFE;" : "+r"(r) : "r"(mw[i].z), "r"(mw[i].w));
    }
    return r;
  };

  const bool g132 = G == 132;
  const uint2 lsw = __ldg(reinterpret_cast<const uint2*>(logit_scale));
  uint32_t cw = 0;
  int4 rid[4];
  if (wg == 0) {
    if (warp == 0) {
      if (elect_one()) {
#pragma unroll
        for (int i = 0; i < 13; i++) mbar_init(mbar + 8 * i, ((i >= 4 && i < 7) || i >= 9) ? 4 : 1);
        mbar_init(mbar + MB_RDY, 8);
        fence_async();
        mbar_expect(mbar + MB_WQK, 3 * 12288);
        tma3(sb + SM_W, &tm_wqk, mbar + MB_WQK, 0, 0, 0);
        load_x(&tm_x, &tm_xq, slot_window(blockIdx.x, g132), 0);
        mbar_expect(mbar + MB_WV, 3 * 6144);
        tma3(sb + SM_WV, &tm_wv, mbar + MB_WV, 0, 0, 0);
        mbar_expect(mbar + MB_WO, 18432);
        bulk_g2s(sb + SM_WOR, wo, 18432, mbar + MB_WO);
      }
      __syncwarp();
    }
  } else {
    const int i = tid - 128;
    if (i < 12) *reinterpret_cast<uint4*>(smem + SM_PAR + 16 * i) = __ldg(i < 4 ? reinterpret_cast<const uint4*>(w1) + i : reinterpret_cast<const uint4*>(w2) + (i - 4));
    if (i < 225) cw = __ldg(reinterpret_cast<const uint32_t*>(coords) + i);
  }
  if ((uint32_t)__cvta_generic_to_shared(smem) != sb) __trap();
  auto const_tiles = [&]() {
    const int i = tid & 127;
    uint8_t* vt = smem + SM_WG + wg * WG_SZ + WG_V + (i < 64 ? 3 : 10) * 1024 + (i & 63) * 16;
    *reinterpret_cast<uint4*>(vt) = make_uint4(0x3F803F80u, 0x3F803F80u, 0x3F803F80u, 0x3F803F80u);
    *reinterpret_cast<uint4*>(vt - (WG_V - WG_K)) = make_uint4(0u, 0u, 0u, 0u);
  };
  if (wg != 2) const_tiles();
  float tau[4]; uint32_t slow_heads = 0;
  {
    const float ls[4] = {bf_lo(lsw.x), bf_hi(lsw.x), bf_lo(lsw.y), bf_hi(lsw.y)};
#pragma unroll
    for (int h = 0; h < 4; h++) {
      const float c = ls[h] < -100.f ? -100.f : (ls[h] > 4.59375f ? 4.59375f : ls[h]);
      tau[h] = rbf(ex2(c * LOG2E)) * LOG2E;
      if (!(tau[h] <= TAU_FAST_MAX)) slow_heads |= 1u << h;
    }
    slow_heads = __shfl_sync(0xffffffffu, slow_heads, 0);
  }
  if (wg == 0 && warp == 1) {
    const int eg = lane / NENT, ei = lane - eg * NENT, sl = blockIdx.x + eg * G + ei * 3 * G;
    const int w = (sl < NWIN && eg < 3) ? slot_window(sl, g132) : -1;
    const bool fast = w >= 0 && slow_heads == 0 && (ei == 0 || ((w >> 8) != NWX - 1 && (w & 255) != NWX - 1));
    const uint32_t fm = __ballot_sync(0xffffffffu, fast), gm = __ballot_sync(0xffffffffu, w >= 0 && !fast);
    const uint32_t below = ((1u << ei) - 1) << (eg * NENT);
    const int pos = __popc((fast ? fm : gm) & below);
    int ticket = 0;
#pragma unroll
    for (int g = 0; g < 3; g++) ticket += min(__popc((fm >> (g * NENT)) & ((1u << NENT) - 1)), pos + (g < eg));
    if (eg < 3) {
      *reinterpret_cast<int*>(smem + SM_WIN + lane * 4) = -1;
      *reinterpret_cast<int*>(smem + SM_GEN + lane * 4) = -1;
    }
    __syncwarp();
    if (w >= 0) *reinterpret_cast<int*>(smem + (fast ? SM_WIN : SM_GEN) + (eg * NENT + pos) * 4) = w | ticket << 16;
  }
  if (wg == 0 && warp == 3 && lane < 16) {
    const uint32_t v = (((lane >> 3) ^ lane) & 1) ? 0u : 0x3F803F80u;
    *reinterpret_cast<uint4*>(smem + SM_SEL + lane * 16) = make_uint4(v, v, v, v);
  }
  TL(3);
  if (wg == 0) {
    if (tid == 0) {
      *reinterpret_cast<float4*>(smem + SM_MISC) = make_float4(tau[0], tau[1], tau[2], tau[3]);
      *reinterpret_cast<uint32_t*>(smem + SM_SLOW) = slow_heads;
    }
    fence_async();
    bar_arrive_n(BAR_SETUP, 384);
    bar_sync_n(BAR_AUX, 128);
  } else {
    const int i = tid - 128;
#pragma unroll
    for (int c = 0; c < 4; c++) {
      const uint4 r = ldg128_stream(reinterpret_cast<const int4*>(rel_idx) + c * 256 + i);
      rid[c] = make_int4(r.x, r.y, r.z, r.w);
    }
    bar_sync_n(BAR_TAB, 256);
    TL(4);
    if (i < 225) {
      const float c0 = bf_lo(cw), c1 = bf_hi(cw);
      float z[4] = {0.f, 0.f, 0.f, 0.f};
#pragma unroll
      for (int jj = 0; jj < 2; jj++) {
        const uint4 ua4 = lds128(sb + SM_PAR + 16 * jj), ub4 = lds128(sb + SM_PAR + 32 + 16 * jj);
        const uint32_t ua[4] = {ua4.x, ua4.y, ua4.z, ua4.w}, ub[4] = {ub4.x, ub4.y, ub4.z, ub4.w};
#pragma unroll
        for (int j = 0; j < 4; j++) {
          const uint4 wb = lds128(sb + SM_PAR + 64 + 64 * jj + 16 * j);
          const uint32_t hp = pack_bf16(fmaf(c1, bf_lo(ub[j]), c0 * bf_lo(ua[j])), fmaf(c1, bf_hi(ub[j]), c0 * bf_hi(ua[j])));
          float h0 = bf_lo(hp), h1 = bf_hi(hp);
          h0 = h0 > 0.f ? h0 : h0 * 0.f; h1 = h1 > 0.f ? h1 : h1 * 0.f;
          z[0] = fmaf(h0, bf_lo(wb.x), z[0]); z[1] = fmaf(h0, bf_hi(wb.x), z[1]); z[2] = fmaf(h0, bf_lo(wb.y), z[2]); z[3] = fmaf(h0, bf_hi(wb.y), z[3]);
          z[0] = fmaf(h1, bf_lo(wb.z), z[0]); z[1] = fmaf(h1, bf_hi(wb.z), z[1]); z[2] = fmaf(h1, bf_lo(wb.w), z[2]); z[3] = fmaf(h1, bf_hi(wb.w), z[3]);
        }
      }
      float e[4];
#pragma unroll
      for (int q = 0; q < 4; q++) {
        const float sh = ((slow_heads >> q) & 1) ? 0.f : fminf(0.f, 25.f - 1.02f * tau[q]);
        e[q] = ex2(fmaf(16.f * LOG2E, rbf(rcp(1.f + ex2(-LOG2E * rbf(z[q])))), sh));
      }
      *reinterpret_cast<uint2*>(smem + SM_TAB + 8 * i) = make_uint2(pack_bf16(e[0], e[1]), pack_bf16(e[2], e[3]));
    }
    TL(5);
    bar_sync_n(BAR_SETUP, 384);
    if (tid == 128 + 127) {
      const int w = slot_window(blockIdx.x + G, g132);
      load_x(&tm_x, &tm_xq, w, 1);
      prefetch_l2(mb + mask_off(w), 8192);
    }
    __syncwarp();
#pragma unroll
    for (int c = 0; c < 4; c++) asm volatile("" : "+r"(rid[c].x), "+r"(rid[c].y), "+r"(rid[c].z), "+r"(rid[c].w));
    {
      const int y = (i & 15) >> 1, xh = i & 1, j = 2 * xh + (y >> 2);
      const int X = (i >> 4) & 7, Yl = (i >> 7) & 1;
      uint8_t* dst = smem + SM_EB + j * 2048 + ((X >> 2) * 64 + (Yl * 4 + (X & 3)) * 4 + 2 * (y & 1)) * 16 + ((y >> 1) & 1) * 8;
#pragma unroll
      for (int c = 0; c < 4; c++) {
        const int ia0 = xh ? rid[c].z : rid[c].x, ia1 = xh ? rid[c].w : rid[c].y, ib0 = xh ? rid[c].x : rid[c].z, ib1 = xh ? rid[c].y : rid[c].w;
        const uint2 a0 = *reinterpret_cast<const uint2*>(smem + SM_TAB + 8 * ia0), a1 = *reinterpret_cast<const uint2*>(smem + SM_TAB + 8 * ia1);
        const uint2 b0 = *reinterpret_cast<const uint2*>(smem + SM_TAB + 8 * ib0), b1 = *reinterpret_cast<const uint2*>(smem + SM_TAB + 8 * ib1);
        uint8_t* d0 = dst + (c >> 1) * 512 + (((c & 1) ^ (j & 1)) * 4) + xh * 16;
        uint8_t* d1 = dst + (c >> 1) * 512 + (((c & 1) ^ (j & 1)) * 4) + (xh ^ 1) * 16;
        *reinterpret_cast<uint32_t*>(d0)         = __byte_perm(a0.x, a1.x, 0x5410); *reinterpret_cast<uint32_t*>(d1)         = __byte_perm(b0.x, b1.x, 0x5410);
        *reinterpret_cast<uint32_t*>(d0 + 8192)  = __byte_perm(a0.x, a1.x, 0x7632); *reinterpret_cast<uint32_t*>(d1 + 8192)  = __byte_perm(b0.x, b1.x, 0x7632);
        *reinterpret_cast<uint32_t*>(d0 + 16384) = __byte_perm(a0.y, a1.y, 0x5410); *reinterpret_cast<uint32_t*>(d1 + 16384) = __byte_perm(b0.y, b1.y, 0x5410);
        *reinterpret_cast<uint32_t*>(d0 + 24576) = __byte_perm(a0.y, a1.y, 0x7632); *reinterpret_cast<uint32_t*>(d1 + 24576) = __byte_perm(b0.y, b1.y, 0x7632);
      }
    }
    TL(6);
    if (tid == 256) {
      const int w = slot_window(blockIdx.x + 2 * G, g132);
      load_x(&tm_x, &tm_xq, w, 2);
      prefetch_l2(mb + mask_off(w), 8192);
    }
    __syncwarp();
    fence_async();
    if (elect_one()) mbar_arrive(mbar + MB_RDY);
    __syncwarp();
    bar_sync_n(BAR_TAB, 256);
    if (wg == 2) {
      mbar_wait(mbar + MB_WO, 0);
      uint4 v[9];
#pragma unroll
      for (int c = 0; c < 9; c++) v[c] = lds128(sb + SM_WOR + ((c / 3) * 32 + ((tid & 127) >> 2)) * 192 + (c % 3) * 64 + (lane & 3) * 16);
      bar_sync_n(BAR_AUX + 2, 128);
      const_tiles();
#pragma unroll
      for (int r = 0; r < 3; r++) {
        float sum = 0.f;
#pragma unroll
        for (int c = 3 * r; c < 3 * r + 3; c++)
          sum += (bf_lo(v[c].x) + bf_hi(v[c].x)) + (bf_lo(v[c].y) + bf_hi(v[c].y)) + (bf_lo(v[c].z) + bf_hi(v[c].z)) + (bf_lo(v[c].w) + bf_hi(v[c].w));
        sum += __shfl_xor_sync(0xffffffffu, sum, 1);
        sum += __shfl_xor_sync(0xffffffffu, sum, 2);
        const float mu = sum * (1.f / 96.f);
        auto cen = [&](uint32_t u) { return pack_bf16(bf_lo(u) - mu, bf_hi(u) - mu); };
        uint8_t* dst = smem + SM_WO + (r * 4 + warp) * 128 + lane * 4;
#pragma unroll
        for (int j = 0; j < 3; j++) {
          *reinterpret_cast<uint32_t*>(dst + (4 * j + 0) * 1536) = cen(v[3 * r + j].x);
          *reinterpret_cast<uint32_t*>(dst + (4 * j + 1) * 1536) = cen(v[3 * r + j].y);
          *reinterpret_cast<uint32_t*>(dst + (4 * j + 2) * 1536) = cen(v[3 * r + j].z);
          *reinterpret_cast<uint32_t*>(dst + (4 * j + 3) * 1536) = cen(v[3 * r + j].w);
        }
      }
      fence_async();
      __syncwarp();
      if (elect_one()) mbar_arrive(mbar + MB_TURN);
      __syncwarp();
    }
  }
  uint32_t wl = sb + SM_WIN + wg * NENT * 4;
  int win = lds_uniform(wl), nxt = lds_uniform(wl + 4);
  TL(1);
  mbar_wait(mbar + MB_WQK, 0);
  if (win >= 0) {
    float qk[96];
    load_mask(mask_off(win));
    mbar_wait(bar_x, 0);
    TL(2);
    wg_fence();
    issue_qk(qk, mk_desc(WG_X, 16, 512, 2) + (wgb >> 4), mk_desc(sb + SM_W, 12288, 1024, 1)); wg_commit();
    if (warp == 0 && nxt >= 0 && elect_one()) prefetch_l2(mb + mask_off(nxt), 8192);
    __syncwarp();
    uint32_t mword = mask_or(0);
    TL(7);
    mbar_wait(mbar + MB_WV, 0);
    mbar_wait(mbar + MB_RDY, 0);
    TL(8);

    const uint32_t k_dst = wgb + WG_K + (lane >> 4) * 7168 + warp * 256 + (lane & 15) * 16;
    const uint32_t eb_base = sb + SM_EB + t16;
    while (true) {
      const int nxt2 = lds_uniform(wl + 8), tk = win >> 16;
      const bool more = nxt >= 0;
      const uint32_t z0 = wl >> 20, zw = z0 + (wgb >> 4);
      const uint64_t dX = opaque(mk_desc(WG_X, 16, 512, 2) + zw);
      TL(0);
      uint32_t qa[24];
      qkv_epilogue(qk, qa, dX, opaque(mk_desc(sb + SM_WV, 6144, 512, 2) + z0), k_dst);
      TL(5);
      const bool masked = bar_wg_or(BAR_KV + wg, (mword & 0x7FFF7FFFu) != 0u);
      TL(6);
      const uint64_t dK = opaque(mk_desc(WG_K, 1024, 128, 0) + zw), dV = opaque(mk_desc(WG_V, 128, 1024, 0) + zw);
      auto prefetch_next = [&]() {
        if (warp == 0) {
          if (elect_one()) {
            const int w = more ? nxt : (int)lds32(wl + (SM_GEN - SM_WIN) - ((wl - (sb + SM_WIN)) % (NENT * 4)));
            if (w >= 0) load_x(&tm_x, &tm_xq, w, wg);
            const int w2 = more ? nxt2 : w;
            if (w2 >= 0) prefetch_l2(mb + mask_off(w2), 8192);
          }
          __syncwarp();
        }
      };
      auto wait_turn = [&]() { mbar_wait(mbar + MB_TURN + (tk & 3) * 8, (tk >> 2) & 1); };
      auto pass_turn = [&]() { if (elect_one()) mbar_arrive(mbar + MB_TURN + ((tk + 1) & 3) * 8); __syncwarp(); };
      auto next_qk = [&]() { issue_qk(qk, dX, opaque(mk_desc(sb + SM_W, 12288, 1024, 1) + z0)); wg_commit(); };
      auto tiles_ready = [&]() {
        if (elect_one()) mbar_arrive(bar_x + (MB_KV - MB_X));
        __syncwarp();
        const uint32_t xphase = (wl >> 2) & 1;
        mbar_wait(bar_x, xphase ^ 1);
        mbar_wait(bar_x + (MB_KV - MB_X), xphase);
      };
      if (__builtin_expect(!masked, 1)) {
        uint32_t of[24];
        {
          float sA[32], sB[32], oA[16], oB[16], oC[16], oD[16];
          uint32_t pA[16], pB[16], pC[16], pD[16];
          wg_fence();
          issue_s<0>(sA, qa, dK);
          issue_s<1>(sB, qa, dK); wg_commit();
          load_eb(pA, eb_base);
          prefetch_next();
          wait_turn();
          wg_wait<0>(); fence_regs(sA); fence_regs(sB);
          TL(7);
          load_eb(pB, eb_base + 8192);
          softmax_fast(sA, pA);
          wg_fence();
          issue_s<2>(sA, qa, dK); wg_commit();
          issue_pv<0>(oA, pA, dV); wg_commit();
          TL(8);
          softmax_fast(sB, pB);
          load_eb(pC, eb_base + 2 * 8192);
          wg_wait<1>(); fence_regs(sA);
          wg_fence();
          issue_s<3>(sB, qa, dK); wg_commit();
          issue_pv<1>(oB, pB, dV); wg_commit();
          TL(9);
          softmax_fast(sA, pC);
          pass_turn();
          load_eb(pD, eb_base + 3 * 8192);
          wg_wait<1>(); fence_regs(sB); fence_regs(oA);
          wg_fence();
          issue_pv<2>(oC, pC, dV); wg_commit();
          TL(10);
          norm_o<0>(oA, of);
          softmax_fast(sB, pD);
          wg_fence();
          issue_pv<3>(oD, pD, dV); wg_commit();
          if (more) load_mask(mask_off(nxt));
          else { mw[0] = mw[1] = mw[2] = mw[3] = make_uint4(0, 0, 0, 0); }
          wg_wait<1>(); fence_regs(oB); fence_regs(oC);
          norm_o<1>(oB, of + 6);
          norm_o<0>(oC, of + 12);
          wg_wait<0>(); fence_regs(oD);
          norm_o<1>(oD, of + 18);
        }
        TL(11);
        float y[48], var[4]; uint32_t yb[24];
        issue_out(y, of, opaque(mk_desc(sb + SM_WO, 128, 1536, 0) + z0));
        char* const optr = out_ptr(out, win, warp, t16);
        if (!more) { ln_head(y, yb, var, dV + 3 * 64); wg_wait<0>(); ln_tail(yb, var, optr); TL(14); break; }
        tiles_ready();
        ln_head(y, yb, var, dV + 3 * 64);
        TL(12);
        next_qk();
        wg_wait<1>();
        TL(13);
        mword = mask_or(ln_tail(yb, var, optr));
      } else {
        if (t16 == 0) {
          uint32_t gl = sb + SM_GEN + wg * NENT * 4;
          while ((int)lds32(gl) >= 0) gl += 4;
          asm volatile("st.shared.u32 [%0], %1;" :: "r"(gl), "r"(win) : "memory");
        }
        __syncwarp();
        prefetch_next();
        wait_turn(); pass_turn();
        if (!more) break;
        load_mask(mask_off(nxt));
        tiles_ready();
        wg_fence();
        next_qk();
        mword = mask_or(0);
      }
      TL(14);
      wl += 4;
      win = nxt; nxt = nxt2;
    }
    wl += 4;
  } else {
    mbar_wait(mbar + MB_WV, 0);
    mbar_wait(mbar + MB_RDY, 0);
    mbar_wait(mbar + MB_TURN, 0);
  }
  bar_sync_n(BAR_AUX + wg, 128);
  if (lds_uniform(sb + SM_GEN + wg * NENT * 4) >= 0) general_windows(&tm_x, &tm_xq, mb, out, (wl >> 2) & 1);
  TG(15);
}

typedef CUresult (*EncodeFn)(CUtensorMap*, CUtensorMapDataType, cuuint32_t, void*, const cuuint64_t*, const cuuint64_t*,
                             const cuuint32_t*, const cuuint32_t*, CUtensorMapInterleave, CUtensorMapSwizzle,
                             CUtensorMapL2promotion, CUtensorMapFloatOOBfill);

}

extern "C" void kernel_launch(void* const* d_in, const int* in_sizes, int n_in, void* d_out, int out_size) {
  static int sms = 0;
  static EncodeFn encode = nullptr;
  if (sms == 0) {
    int dev = 0;
    cudaGetDevice(&dev);
    cudaDeviceGetAttribute(&sms, cudaDevAttrMultiProcessorCount, dev);
    if (sms < 96) sms = 96;
    cudaFuncSetAttribute(swin_kernel, cudaFuncAttributeMaxDynamicSharedMemorySize, SM_TOTAL);
    cudaDriverEntryPointQueryResult qr;
    void* fn = nullptr;
    cudaGetDriverEntryPoint("cuTensorMapEncodeTiled", &fn, cudaEnableDefault, &qr);
    encode = (EncodeFn)fn;
  }
  CUtensorMap tm_x, tm_xq, tm_wqk, tm_wv;
  {
    cuuint64_t dims[5] = {32, 4, IMG, IMG / 4, 3};
    cuuint64_t strides[4] = {PIXB, ROWB, 4 * PIXB, 64};
    cuuint32_t es[5] = {1, 1, 1, 1, 1};
    cuuint32_t box[5] = {32, 4, 8, 2, 3}, boxq[5] = {32, 4, 4, 1, 1};
    encode(&tm_x, CU_TENSOR_MAP_DATA_TYPE_BFLOAT16, 5, d_in[0], dims, strides, box, es, CU_TENSOR_MAP_INTERLEAVE_NONE,
           CU_TENSOR_MAP_SWIZZLE_64B, CU_TENSOR_MAP_L2_PROMOTION_L2_128B, CU_TENSOR_MAP_FLOAT_OOB_FILL_NONE);
    encode(&tm_xq, CU_TENSOR_MAP_DATA_TYPE_BFLOAT16, 5, d_in[0], dims, strides, boxq, es, CU_TENSOR_MAP_INTERLEAVE_NONE,
           CU_TENSOR_MAP_SWIZZLE_64B, CU_TENSOR_MAP_L2_PROMOTION_L2_128B, CU_TENSOR_MAP_FLOAT_OOB_FILL_NONE);
    cuuint64_t qd[3] = {64, 96, 3}, qs[2] = {576, 128}, vd[3] = {32, 96, 3}, vs[2] = {576, 64};
    cuuint32_t qb[3] = {64, 96, 3}, vb[3] = {32, 96, 3};
    encode(&tm_wqk, CU_TENSOR_MAP_DATA_TYPE_BFLOAT16, 3, d_in[1], qd, qs, qb, es, CU_TENSOR_MAP_INTERLEAVE_NONE,
           CU_TENSOR_MAP_SWIZZLE_128B, CU_TENSOR_MAP_L2_PROMOTION_L2_256B, CU_TENSOR_MAP_FLOAT_OOB_FILL_NONE);
    encode(&tm_wv, CU_TENSOR_MAP_DATA_TYPE_BFLOAT16, 3, (char*)d_in[1] + 384, vd, vs, vb, es, CU_TENSOR_MAP_INTERLEAVE_NONE,
           CU_TENSOR_MAP_SWIZZLE_64B, CU_TENSOR_MAP_L2_PROMOTION_L2_256B, CU_TENSOR_MAP_FLOAT_OOB_FILL_NONE);
  }
  swin_kernel<<<sms, 384, SM_TOTAL>>>(
      tm_x, tm_xq, tm_wqk, tm_wv, (const __nv_bfloat16*)d_in[2], (const __nv_bfloat16*)d_in[3],
      (const __nv_bfloat16*)d_in[4], (const __nv_bfloat16*)d_in[5], (const __nv_bfloat16*)d_in[6], (const int*)d_in[7],
      (const __nv_bfloat16*)d_in[8], (__nv_bfloat16*)d_out);
}
```

```cpp
#include <cuda_runtime.h>
#include <cuda.h>
#include <cuda_bf16.h>
#include <stdint.h>
#include <type_traits>

#define TOKEN 3
namespace {

constexpr int IMG   = 384;
constexpr int NWX   = 48;
constexpr int NWIN  = NWX * NWX;
constexpr int PIXB  = 192;
constexpr int ROWB  = IMG * PIXB;
constexpr float LOG2E = 1.4426950408889634f;
constexpr float TAU_FAST_MAX = 50.f;

constexpr int SM_W    = 0;
constexpr int SM_WV   = 3 * 12288;
constexpr int SM_WO   = SM_W + 9 * 6144;
constexpr int SM_EB   = SM_WO + 12 * 1536;
constexpr int SM_WG   = SM_EB + 32768;
constexpr int WG_X    = 0;
constexpr int WG_K    = 12288;
constexpr int WG_V    = WG_K + 14336;
constexpr int WG_SZ   = WG_V + 14336;
constexpr int SM_TAB  = SM_WG + WG_SZ + WG_V + 4096;
constexpr int SM_WOR  = SM_WG + 2 * WG_SZ + WG_K;
constexpr int SM_SEL  = SM_WG + 3 * WG_SZ;
constexpr int SM_MISC = SM_SEL + 256;
constexpr int SM_BAR  = SM_MISC + 16;
constexpr int SM_SLOW = SM_BAR + 104;
constexpr int SM_PAR  = SM_BAR + 160;
constexpr int NENT    = 10;
constexpr int SM_WIN  = SM_PAR + 192;
constexpr int SM_GEN  = SM_WIN + 3 * NENT * 4;
constexpr int SM_TOTAL = SM_GEN + 3 * NENT * 4;
static_assert((SM_WIN & 7) == 0 && (NENT & 1) == 0, "list parity");

template <int SD> __device__ __forceinline__ void wgmma_ss_n192_t1(float (&d)[96], uint64_t da, uint64_t db) {
  if constexpr (SD) {
    asm volatile("{\n.reg .pred p;\nsetp.ne.b32 p, 1, 0;\n"
      "wgmma.mma_async.sync.aligned.m64n192k16.f32.bf16.bf16 {%0, %1, %2, %3, %4, %5, %6, %7, %8, %9, %10, %11, %12, %13, %14, %15, %16, %17, %18, %19, %20, %21, %22, %23, %24, %25, %26, %27, %28, %29, %30, %31, %32, %33, %34, %35, %36, %37, %38, %39, %40, %41, %42, %43, %44, %45, %46, %47, %48, %49, %50, %51, %52, %53, %54, %55, %56, %57, %58, %59, %60, %61, %62, %63, %64, %65, %66, %67, %68, %69, %70, %71, %72, %73, %74, %75, %76, %77, %78, %79, %80, %81, %82, %83, %84, %85, %86, %87, %88, %89, %90, %91, %92, %93, %94, %95}, %96, %97, p, 1, 1, 0, 1;\n}\n"
      : "+f"(d[0]), "+f"(d[1]), "+f"(d[2]), "+f"(d[3]), "+f"(d[4]), "+f"(d[5]), "+f"(d[6]), "+f"(d[7]), "+f"(d[8]), "+f"(d[9]), "+f"(d[10]), "+f"(d[11]), "+f"(d[12]), "+f"(d[13]), "+f"(d[14]), "+f"(d[15]), "+f"(d[16]), "+f"(d[17]), "+f"(d[18]), "+f"(d[19]), "+f"(d[20]), "+f"(d[21]), "+f"(d[22]), "+f"(d[23]), "+f"(d[24]), "+f"(d[25]), "+f"(d[26]), "+f"(d[27]), "+f"(d[28]), "+f"(d[29]), "+f"(d[30]), "+f"(d[31]), "+f"(d[32]), "+f"(d[33]), "+f"(d[34]), "+f"(d[35]), "+f"(d[36]), "+f"(d[37]), "+f"(d[38]), "+f"(d[39]), "+f"(d[40]), "+f"(d[41]), "+f"(d[42]), "+f"(d[43]), "+f"(d[44]), "+f"(d[45]), "+f"(d[46]), "+f"(d[47]), "+f"(d[48]), "+f"(d[49]), "+f"(d[50]), "+f"(d[51]), "+f"(d[52]), "+f"(d[53]), "+f"(d[54]), "+f"(d[55]), "+f"(d[56]), "+f"(d[57]), "+f"(d[58]), "+f"(d[59]), "+f"(d[60]), "+f"(d[61]), "+f"(d[62]), "+f"(d[63]), "+f"(d[64]), "+f"(d[65]), "+f"(d[66]), "+f"(d[67]), "+f"(d[68]), "+f"(d[69]), "+f"(d[70]), "+f"(d[71]), "+f"(d[72]), "+f"(d[73]), "+f"(d[74]), "+f"(d[75]), "+f"(d[76]), "+f"(d[77]), "+f"(d[78]), "+f"(d[79]), "+f"(d[80]), "+f"(d[81]), "+f"(d[82]), "+f"(d[83]), "+f"(d[84]), "+f"(d[85]), "+f"(d[86]), "+f"(d[87]), "+f"(d[88]), "+f"(d[89]), "+f"(d[90]), "+f"(d[91]), "+f"(d[92]), "+f"(d[93]), "+f"(d[94]), "+f"(d[95])
      : "l"(da), "l"(db));
  } else {
    asm volatile("{\n.reg .pred p;\nsetp.ne.b32 p, 0, 0;\n"
      "wgmma.mma_async.sync.aligned.m64n192k16.f32.bf16.bf16 {%0, %1, %2, %3, %4, %5, %6, %7, %8, %9, %10, %11, %12, %13, %14, %15, %16, %17, %18, %19, %20, %21, %22, %23, %24, %25, %26, %27, %28, %29, %30, %31, %32, %33, %34, %35, %36, %37, %38, %39, %40, %41, %42, %43, %44, %45, %46, %47, %48, %49, %50, %51, %52, %53, %54, %55, %56, %57, %58, %59, %60, %61, %62, %63, %64, %65, %66, %67, %68, %69, %70, %71, %72, %73, %74, %75, %76, %77, %78, %79, %80, %81, %82, %83, %84, %85, %86, %87, %88, %89, %90, %91, %92, %93, %94, %95}, %96, %97, p, 1, 1, 0, 1;\n}\n"
      : "=f"(d[0]), "=f"(d[1]), "=f"(d[2]), "=f"(d[3]), "=f"(d[4]), "=f"(d[5]), "=f"(d[6]), "=f"(d[7]), "=f"(d[8]), "=f"(d[9]), "=f"(d[10]), "=f"(d[11]), "=f"(d[12]), "=f"(d[13]), "=f"(d[14]), "=f"(d[15]), "=f"(d[16]), "=f"(d[17]), "=f"(d[18]), "=f"(d[19]), "=f"(d[20]), "=f"(d[21]), "=f"(d[22]), "=f"(d[23]), "=f"(d[24]), "=f"(d[25]), "=f"(d[26]), "=f"(d[27]), "=f"(d[28]), "=f"(d[29]), "=f"(d[30]), "=f"(d[31]), "=f"(d[32]), "=f"(d[33]), "=f"(d[34]), "=f"(d[35]), "=f"(d[36]), "=f"(d[37]), "=f"(d[38]), "=f"(d[39]), "=f"(d[40]), "=f"(d[41]), "=f"(d[42]), "=f"(d[43]), "=f"(d[44]), "=f"(d[45]), "=f"(d[46]), "=f"(d[47]), "=f"(d[48]), "=f"(d[49]), "=f"(d[50]), "=f"(d[51]), "=f"(d[52]), "=f"(d[53]), "=f"(d[54]), "=f"(d[55]), "=f"(d[56]), "=f"(d[57]), "=f"(d[58]), "=f"(d[59]), "=f"(d[60]), "=f"(d[61]), "=f"(d[62]), "=f"(d[63]), "=f"(d[64]), "=f"(d[65]), "=f"(d[66]), "=f"(d[67]), "=f"(d[68]), "=f"(d[69]), "=f"(d[70]), "=f"(d[71]), "=f"(d[72]), "=f"(d[73]), "=f"(d[74]), "=f"(d[75]), "=f"(d[76]), "=f"(d[77]), "=f"(d[78]), "=f"(d[79]), "=f"(d[80]), "=f"(d[81]), "=f"(d[82]), "=f"(d[83]), "=f"(d[84]), "=f"(d[85]), "=f"(d[86]), "=f"(d[87]), "=f"(d[88]), "=f"(d[89]), "=f"(d[90]), "=f"(d[91]), "=f"(d[92]), "=f"(d[93]), "=f"(d[94]), "=f"(d[95])
      : "l"(da), "l"(db));
  }
}
template <int SD> __device__ __forceinline__ void wgmma_ss_n96_t1(float (&d)[48], uint64_t da, uint64_t db) {
  if constexpr (SD) {
    asm volatile("{\n.reg .pred p;\nsetp.ne.b32 p, 1, 0;\n"
      "wgmma.mma_async.sync.aligned.m64n96k16.f32.bf16.bf16 {%0, %1, %2, %3, %4, %5, %6, %7, %8, %9, %10, %11, %12, %13, %14, %15, %16, %17, %18, %19, %20, %21, %22, %23, %24, %25, %26, %27, %28, %29, %30, %31, %32, %33, %34, %35, %36, %37, %38, %39, %40, %41, %42, %43, %44, %45, %46, %47}, %48, %49, p, 1, 1, 0, 1;\n}\n"
      : "+f"(d[0]), "+f"(d[1]), "+f"(d[2]), "+f"(d[3]), "+f"(d[4]), "+f"(d[5]), "+f"(d[6]), "+f"(d[7]), "+f"(d[8]), "+f"(d[9]), "+f"(d[10]), "+f"(d[11]), "+f"(d[12]), "+f"(d[13]), "+f"(d[14]), "+f"(d[15]), "+f"(d[16]), "+f"(d[17]), "+f"(d[18]), "+f"(d[19]), "+f"(d[20]), "+f"(d[21]), "+f"(d[22]), "+f"(d[23]), "+f"(d[24]), "+f"(d[25]), "+f"(d[26]), "+f"(d[27]), "+f"(d[28]), "+f"(d[29]), "+f"(d[30]), "+f"(d[31]), "+f"(d[32]), "+f"(d[33]), "+f"(d[34]), "+f"(d[35]), "+f"(d[36]), "+f"(d[37]), "+f"(d[38]), "+f"(d[39]), "+f"(d[40]), "+f"(d[41]), "+f"(d[42]), "+f"(d[43]), "+f"(d[44]), "+f"(d[45]), "+f"(d[46]), "+f"(d[47])
      : "l"(da), "l"(db));
  } else {
    asm volatile("{\n.reg .pred p;\nsetp.ne.b32 p, 0, 0;\n"
      "wgmma.mma_async.sync.aligned.m64n96k16.f32.bf16.bf16 {%0, %1, %2, %3, %4, %5, %6, %7, %8, %9, %10, %11, %12, %13, %14, %15, %16, %17, %18, %19, %20, %21, %22, %23, %24, %25, %26, %27, %28, %29, %30, %31, %32, %33, %34, %35, %36, %37, %38, %39, %40, %41, %42, %43, %44, %45, %46, %47}, %48, %49, p, 1, 1, 0, 1;\n}\n"
      : "=f"(d[0]), "=f"(d[1]), "=f"(d[2]), "=f"(d[3]), "=f"(d[4]), "=f"(d[5]), "=f"(d[6]), "=f"(d[7]), "=f"(d[8]), "=f"(d[9]), "=f"(d[10]), "=f"(d[11]), "=f"(d[12]), "=f"(d[13]), "=f"(d[14]), "=f"(d[15]), "=f"(d[16]), "=f"(d[17]), "=f"(d[18]), "=f"(d[19]), "=f"(d[20]), "=f"(d[21]), "=f"(d[22]), "=f"(d[23]), "=f"(d[24]), "=f"(d[25]), "=f"(d[26]), "=f"(d[27]), "=f"(d[28]), "=f"(d[29]), "=f"(d[30]), "=f"(d[31]), "=f"(d[32]), "=f"(d[33]), "=f"(d[34]), "=f"(d[35]), "=f"(d[36]), "=f"(d[37]), "=f"(d[38]), "=f"(d[39]), "=f"(d[40]), "=f"(d[41]), "=f"(d[42]), "=f"(d[43]), "=f"(d[44]), "=f"(d[45]), "=f"(d[46]), "=f"(d[47])
      : "l"(da), "l"(db));
  }
}
template <int SD> __device__ __forceinline__ void wgmma_rs_n96_t1(float (&d)[48], uint32_t a0, uint32_t a1, uint32_t a2, uint32_t a3, uint64_t db) {
  if constexpr (SD) {
    asm volatile("{\n.reg .pred p;\nsetp.ne.b32 p, 1, 0;\n"
      "wgmma.mma_async.sync.aligned.m64n96k16.f32.bf16.bf16 {%0, %1, %2, %3, %4, %5, %6, %7, %8, %9, %10, %11, %12, %13, %14, %15, %16, %17, %18, %19, %20, %21, %22, %23, %24, %25, %26, %27, %28, %29, %30, %31, %32, %33, %34, %35, %36, %37, %38, %39, %40, %41, %42, %43, %44, %45, %46, %47}, {%48, %49, %50, %51}, %52, p, 1, 1, 1;\n}\n"
      : "+f"(d[0]), "+f"(d[1]), "+f"(d[2]), "+f"(d[3]), "+f"(d[4]), "+f"(d[5]), "+f"(d[6]), "+f"(d[7]), "+f"(d[8]), "+f"(d[9]), "+f"(d[10]), "+f"(d[11]), "+f"(d[12]), "+f"(d[13]), "+f"(d[14]), "+f"(d[15]), "+f"(d[16]), "+f"(d[17]), "+f"(d[18]), "+f"(d[19]), "+f"(d[20]), "+f"(d[21]), "+f"(d[22]), "+f"(d[23]), "+f"(d[24]), "+f"(d[25]), "+f"(d[26]), "+f"(d[27]), "+f"(d[28]), "+f"(d[29]), "+f"(d[30]), "+f"(d[31]), "+f"(d[32]), "+f"(d[33]), "+f"(d[34]), "+f"(d[35]), "+f"(d[36]), "+f"(d[37]), "+f"(d[38]), "+f"(d[39]), "+f"(d[40]), "+f"(d[41]), "+f"(d[42]), "+f"(d[43]), "+f"(d[44]), "+f"(d[45]), "+f"(d[46]), "+f"(d[47])
      : "r"(a0), "r"(a1), "r"(a2), "r"(a3), "l"(db));
  } else {
    asm volatile("{\n.reg .pred p;\nsetp.ne.b32 p, 0, 0;\n"
      "wgmma.mma_async.sync.aligned.m64n96k16.f32.bf16.bf16 {%0, %1, %2, %3, %4, %5, %6, %7, %8, %9, %10, %11, %12, %13, %14, %15, %16, %17, %18, %19, %20, %21, %22, %23, %24, %25, %26, %27, %28, %29, %30, %31, %32, %33, %34, %35, %36, %37, %38, %39, %40, %41, %42, %43, %44, %45, %46, %47}, {%48, %49, %50, %51}, %52, p, 1, 1, 1;\n}\n"
      : "=f"(d[0]), "=f"(d[1]), "=f"(d[2]), "=f"(d[3]), "=f"(d[4]), "=f"(d[5]), "=f"(d[6]), "=f"(d[7]), "=f"(d[8]), "=f"(d[9]), "=f"(d[10]), "=f"(d[11]), "=f"(d[12]), "=f"(d[13]), "=f"(d[14]), "=f"(d[15]), "=f"(d[16]), "=f"(d[17]), "=f"(d[18]), "=f"(d[19]), "=f"(d[20]), "=f"(d[21]), "=f"(d[22]), "=f"(d[23]), "=f"(d[24]), "=f"(d[25]), "=f"(d[26]), "=f"(d[27]), "=f"(d[28]), "=f"(d[29]), "=f"(d[30]), "=f"(d[31]), "=f"(d[32]), "=f"(d[33]), "=f"(d[34]), "=f"(d[35]), "=f"(d[36]), "=f"(d[37]), "=f"(d[38]), "=f"(d[39]), "=f"(d[40]), "=f"(d[41]), "=f"(d[42]), "=f"(d[43]), "=f"(d[44]), "=f"(d[45]), "=f"(d[46]), "=f"(d[47])
      : "r"(a0), "r"(a1), "r"(a2), "r"(a3), "l"(db));
  }
}
template <int SD> __device__ __forceinline__ void wgmma_rs_n64_t0(float (&d)[32], uint32_t a0, uint32_t a1, uint32_t a2, uint32_t a3, uint64_t db) {
  if constexpr (SD) {
    asm volatile("{\n.reg .pred p;\nsetp.ne.b32 p, 1, 0;\n"
      "wgmma.mma_async.sync.aligned.m64n64k16.f32.bf16.bf16 {%0, %1, %2, %3, %4, %5, %6, %7, %8, %9, %10, %11, %12, %13, %14, %15, %16, %17, %18, %19, %20, %21, %22, %23, %24, %25, %26, %27, %28, %29, %30, %31}, {%32, %33, %34, %35}, %36, p, 1, 1, 0;\n}\n"
      : "+f"(d[0]), "+f"(d[1]), "+f"(d[2]), "+f"(d[3]), "+f"(d[4]), "+f"(d[5]), "+f"(d[6]), "+f"(d[7]), "+f"(d[8]), "+f"(d[9]), "+f"(d[10]), "+f"(d[11]), "+f"(d[12]), "+f"(d[13]), "+f"(d[14]), "+f"(d[15]), "+f"(d[16]), "+f"(d[17]), "+f"(d[18]), "+f"(d[19]), "+f"(d[20]), "+f"(d[21]), "+f"(d[22]), "+f"(d[23]), "+f"(d[24]), "+f"(d[25]), "+f"(d[26]), "+f"(d[27]), "+f"(d[28]), "+f"(d[29]), "+f"(d[30]), "+f"(d[31])
      : "r"(a0), "r"(a1), "r"(a2), "r"(a3), "l"(db));
  } else {
    asm volatile("{\n.reg .pred p;\nsetp.ne.b32 p, 0, 0;\n"
      "wgmma.mma_async.sync.aligned.m64n64k16.f32.bf16.bf16 {%0, %1, %2, %3, %4, %5, %6, %7, %8, %9, %10, %11, %12, %13, %14, %15, %16, %17, %18, %19, %20, %21, %22, %23, %24, %25, %26, %27, %28, %29, %30, %31}, {%32, %33, %34, %35}, %36, p, 1, 1, 0;\n}\n"
      : "=f"(d[0]), "=f"(d[1]), "=f"(d[2]), "=f"(d[3]), "=f"(d[4]), "=f"(d[5]), "=f"(d[6]), "=f"(d[7]), "=f"(d[8]), "=f"(d[9]), "=f"(d[10]), "=f"(d[11]), "=f"(d[12]), "=f"(d[13]), "=f"(d[14]), "=f"(d[15]), "=f"(d[16]), "=f"(d[17]), "=f"(d[18]), "=f"(d[19]), "=f"(d[20]), "=f"(d[21]), "=f"(d[22]), "=f"(d[23]), "=f"(d[24]), "=f"(d[25]), "=f"(d[26]), "=f"(d[27]), "=f"(d[28]), "=f"(d[29]), "=f"(d[30]), "=f"(d[31])
      : "r"(a0), "r"(a1), "r"(a2), "r"(a3), "l"(db));
  }
}
template <int SD> __device__ __forceinline__ void wgmma_rs_n32_t1(float (&d)[16], uint32_t a0, uint32_t a1, uint32_t a2, uint32_t a3, uint64_t db) {
  if constexpr (SD) {
    asm volatile("{\n.reg .pred p;\nsetp.ne.b32 p, 1, 0;\n"
      "wgmma.mma_async.sync.aligned.m64n32k16.f32.bf16.bf16 {%0, %1, %2, %3, %4, %5, %6, %7, %8, %9, %10, %11, %12, %13, %14, %15}, {%16, %17, %18, %19}, %20, p, 1, 1, 1;\n}\n"
      : "+f"(d[0]), "+f"(d[1]), "+f"(d[2]), "+f"(d[3]), "+f"(d[4]), "+f"(d[5]), "+f"(d[6]), "+f"(d[7]), "+f"(d[8]), "+f"(d[9]), "+f"(d[10]), "+f"(d[11]), "+f"(d[12]), "+f"(d[13]), "+f"(d[14]), "+f"(d[15])
      : "r"(a0), "r"(a1), "r"(a2), "r"(a3), "l"(db));
  } else {
    asm volatile("{\n.reg .pred p;\nsetp.ne.b32 p, 0, 0;\n"
      "wgmma.mma_async.sync.aligned.m64n32k16.f32.bf16.bf16 {%0, %1, %2, %3, %4, %5, %6, %7, %8, %9, %10, %11, %12, %13, %14, %15}, {%16, %17, %18, %19}, %20, p, 1, 1, 1;\n}\n"
      : "=f"(d[0]), "=f"(d[1]), "=f"(d[2]), "=f"(d[3]), "=f"(d[4]), "=f"(d[5]), "=f"(d[6]), "=f"(d[7]), "=f"(d[8]), "=f"(d[9]), "=f"(d[10]), "=f"(d[11]), "=f"(d[12]), "=f"(d[13]), "=f"(d[14]), "=f"(d[15])
      : "r"(a0), "r"(a1), "r"(a2), "r"(a3), "l"(db));
  }
}
template <int SD> __device__ __forceinline__ void wgmma_rs_n8_t0(float (&d)[4], uint32_t a0, uint32_t a1, uint32_t a2, uint32_t a3, uint64_t db) {
  if constexpr (SD) {
    asm volatile("{\n.reg .pred p;\nsetp.ne.b32 p, 1, 0;\n"
      "wgmma.mma_async.sync.aligned.m64n8k16.f32.bf16.bf16 {%0, %1, %2, %3}, {%4, %5, %6, %7}, %8, p, 1, 1, 0;\n}\n"
      : "+f"(d[0]), "+f"(d[1]), "+f"(d[2]), "+f"(d[3])
      : "r"(a0), "r"(a1), "r"(a2), "r"(a3), "l"(db));
  } else {
    asm volatile("{\n.reg .pred p;\nsetp.ne.b32 p, 0, 0;\n"
      "wgmma.mma_async.sync.aligned.m64n8k16.f32.bf16.bf16 {%0, %1, %2, %3}, {%4, %5, %6, %7}, %8, p, 1, 1, 0;\n}\n"
      : "=f"(d[0]), "=f"(d[1]), "=f"(d[2]), "=f"(d[3])
      : "r"(a0), "r"(a1), "r"(a2), "r"(a3), "l"(db));
  }
}

__device__ __forceinline__ void wg_fence()  { asm volatile("wgmma.fence.sync.aligned;" ::: "memory"); }
__device__ __forceinline__ void wg_commit() { asm volatile("wgmma.commit_group.sync.aligned;" ::: "memory"); }
template <int N> __device__ __forceinline__ void wg_wait() { asm volatile("wgmma.wait_group.sync.aligned %0;" :: "n"(N) : "memory"); }
template <int N> __device__ __forceinline__ void fence_regs(float (&d)[N]) {
#pragma unroll
  for (int i = 0; i < N; i++) asm volatile("" : "+f"(d[i]) :: "memory");
}
__device__ __forceinline__ constexpr uint64_t mk_desc(uint32_t addr, uint32_t lbo, uint32_t sbo, uint32_t swz) {
  return (uint64_t)(addr >> 4) | ((uint64_t)(lbo >> 4) << 16) | ((uint64_t)(sbo >> 4) << 32) | ((uint64_t)swz << 62);
}
__device__ __forceinline__ uint32_t pack_bf16(float lo, float hi) {
  uint32_t r; asm("cvt.rn.bf16x2.f32 %0, %1, %2;" : "=r"(r) : "f"(hi), "f"(lo)); return r;
}
__device__ __forceinline__ uint32_t hmul2(uint32_t a, uint32_t b) {
  uint32_t r; asm("mul.rn.bf16x2 %0, %1, %2;" : "=r"(r) : "r"(a), "r"(b)); return r;
}
template <int HI> __device__ __forceinline__ uint32_t hmul2_b(uint32_t a, uint32_t b) {
  uint32_t r;
  if (HI) asm("{\n.reg .b16 l, h;\n.reg .b32 t;\nmov.b32 {l, h}, %2;\nmov.b32 t, {h, h};\nmul.rn.bf16x2 %0, %1, t;\n}\n" : "=r"(r) : "r"(a), "r"(b));
  else    asm("{\n.reg .b16 l, h;\n.reg .b32 t;\nmov.b32 {l, h}, %2;\nmov.b32 t, {l, l};\nmul.rn.bf16x2 %0, %1, t;\n}\n" : "=r"(r) : "r"(a), "r"(b));
  return r;
}
__device__ __forceinline__ uint32_t hfma2(uint32_t a, uint32_t b, uint32_t c) {
  uint32_t r; asm("fma.rn.bf16x2 %0, %1, %2, %3;" : "=r"(r) : "r"(a), "r"(b), "r"(c)); return r;
}
__device__ __forceinline__ float ex2(float x) { float r; asm("ex2.approx.ftz.f32 %0, %1;" : "=f"(r) : "f"(x)); return r; }
__device__ __forceinline__ float rsq(float x) { float r; asm("rsqrt.approx.ftz.f32 %0, %1;" : "=f"(r) : "f"(x)); return r; }
__device__ __forceinline__ float rcp(float x) { float r; asm("rcp.approx.ftz.f32 %0, %1;" : "=f"(r) : "f"(x)); return r; }
__device__ __forceinline__ void stsm4(uint32_t addr, uint32_t r0, uint32_t r1, uint32_t r2, uint32_t r3) {
  asm volatile("stmatrix.sync.aligned.m8n8.x4.shared.b16 [%0], {%1,%2,%3,%4};" :: "r"(addr), "r"(r0), "r"(r1), "r"(r2), "r"(r3) : "memory");
}
__device__ __forceinline__ void fence_async() { asm volatile("fence.proxy.async.shared::cta;" ::: "memory"); }
__device__ __forceinline__ void bar_sync_n(int id, int n) { asm volatile("bar.sync %0, %1;" :: "r"(id), "r"(n) : "memory"); }
__device__ __forceinline__ void bar_arrive_n(int id, int n) { asm volatile("bar.arrive %0, %1;" :: "r"(id), "r"(n) : "memory"); }
__device__ __forceinline__ bool bar_wg_or(int id, bool v) {
  uint32_t r;
  asm volatile("{\n.reg .pred p, q;\nsetp.ne.u32 q, %2, 0;\nbar.red.or.pred p, %1, 128, q;\nselp.u32 %0, 0, 1, p;\n}\n"
               : "=r"(r) : "r"(id), "r"((uint32_t)v) : "memory");
  return __ballot_sync(0xffffffffu, r != 0) == 0;
}
__device__ __forceinline__ void mbar_init(uint32_t bar, uint32_t cnt) { asm volatile("mbarrier.init.shared::cta.b64 [%0], %1;" :: "r"(bar), "r"(cnt) : "memory"); }
__device__ __forceinline__ void mbar_expect(uint32_t bar, uint32_t bytes) {
  asm volatile("mbarrier.arrive.expect_tx.shared::cta.b64 _, [%0], %1;" :: "r"(bar), "r"(bytes) : "memory");
}
__device__ __forceinline__ void mbar_arrive(uint32_t bar) { asm volatile("mbarrier.arrive.shared::cta.b64 _, [%0];" :: "r"(bar) : "memory"); }
__device__ __forceinline__ void mbar_wait(uint32_t bar, uint32_t parity) {
  asm volatile("{\n.reg .pred p;\n.reg .u32 n;\nmov.u32 n, 0;\n"
               "LW_%=:\nmbarrier.try_wait.parity.shared::cta.b64 p, [%0], %1;\n@p bra.uni LD_%=;\n"
               "add.u32 n, n, 1;\nsetp.lt.u32 p, n, 4194304;\n@p bra.uni LW_%=;\ntrap;\nLD_%=:\n}\n"
               :: "r"(bar), "r"(parity) : "memory");
}
__device__ __forceinline__ void tma5(uint32_t dst, const CUtensorMap* m, uint32_t bar, int c0, int c1, int c2, int c3, int c4) {
  asm volatile("cp.async.bulk.tensor.5d.shared::cluster.global.mbarrier::complete_tx::bytes [%0], [%1, {%3, %4, %5, %6, %7}], [%2];"
               :: "r"(dst), "l"(m), "r"(bar), "r"(c0), "r"(c1), "r"(c2), "r"(c3), "r"(c4) : "memory");
}
__device__ __forceinline__ void tma3(uint32_t dst, const CUtensorMap* m, uint32_t bar, int c0, int c1, int c2) {
  asm volatile("cp.async.bulk.tensor.3d.shared::cluster.global.mbarrier::complete_tx::bytes [%0], [%1, {%3, %4, %5}], [%2];"
               :: "r"(dst), "l"(m), "r"(bar), "r"(c0), "r"(c1), "r"(c2) : "memory");
}
__device__ __forceinline__ void bulk_g2s(uint32_t dst, const void* src, uint32_t bytes, uint32_t bar) {
  asm volatile("cp.async.bulk.shared::cluster.global.mbarrier::complete_tx::bytes [%0], [%1], %2, [%3];"
               :: "r"(dst), "l"(src), "r"(bytes), "r"(bar) : "memory");
}
__device__ __forceinline__ uint32_t lds32(uint32_t addr) {
  uint32_t v; asm volatile("ld.shared.u32 %0, [%1];" : "=r"(v) : "r"(addr)); return v;
}
__device__ __forceinline__ uint64_t opaque(uint64_t v) { asm volatile("" : "+l"(v)); return v; }
__device__ __forceinline__ uint4 lds128(uint32_t addr) {
  uint4 v; asm volatile("ld.shared.v4.u32 {%0,%1,%2,%3}, [%4];" : "=r"(v.x), "=r"(v.y), "=r"(v.z), "=r"(v.w) : "r"(addr)); return v;
}
__device__ __forceinline__ uint4 ldg128_stream(const void* p) {
  uint4 v; asm volatile("ld.global.nc.L1::no_allocate.v4.u32 {%0,%1,%2,%3}, [%4];" : "=r"(v.x), "=r"(v.y), "=r"(v.z), "=r"(v.w) : "l"(p)); return v;
}
__device__ __forceinline__ void stg128(void* p, uint32_t a, uint32_t b, uint32_t c, uint32_t d) {
  asm volatile("st.global.v4.u32 [%0], {%1,%2,%3,%4};" :: "l"(p), "r"(a), "r"(b), "r"(c), "r"(d) : "memory");
}
__device__ __forceinline__ void prefetch_l2(const void* p, uint32_t bytes) {
  asm volatile("cp.async.bulk.prefetch.L2.global [%0], %1;" :: "l"(p), "r"(bytes) : "memory");
}
__device__ __forceinline__ bool elect_one() {
  uint32_t r; asm volatile("{\n.reg .pred p;\nelect.sync _|p, 0xffffffff;\nselp.u32 %0, 1, 0, p;\n}\n" : "=r"(r)); return r != 0;
}
__device__ __forceinline__ float bf_lo(uint32_t u) { return __uint_as_float(u << 16); }
__device__ __forceinline__ float bf_hi(uint32_t u) { return __uint_as_float(u & 0xFFFF0000u); }
__device__ __forceinline__ float rbf(float x) { return bf_lo(pack_bf16(x, 0.f)); }
__device__ __forceinline__ int orig_tok(int r) { return ((r & 31) >> 2) * 8 + (r >> 5) * 4 + (r & 3); }

__device__ __forceinline__ int slot_window(int s, bool g132) {
  const int A0 = g132 ? 396 + 264 + 60 : 47 * 47, A1 = A0 + 72, B0 = g132 ? 3 * 396 + 264 + 60 : A1, B1 = B0 + 23;
  const int i = s - (s >= B1 ? 95 : s >= A1 ? 72 : 0);
  const int k = s >= B0 ? s - B0 + 72 : s - A0;
  const bool border = (s >= A0 && s < A1) || (s >= B0 && s < B1);
  const int iy = (i * 2789) >> 17;
  return border ? (k < 48 ? (47 << 8 | k) : ((k - 48) << 8 | 47)) : (iy << 8 | (i - iy * 47));
}

#define EB_WORD(e, j, a) ((((a) ^ ((j) & 1)) == 0) ? (e).x : (((a) ^ ((j) & 1)) == 1) ? (e).y : (((a) ^ ((j) & 1)) == 2) ? (e).z : (e).w)

__device__ __forceinline__ void load_eb(uint32_t (&e)[16], uint32_t eb_addr) {
#pragma unroll
  for (int j = 0; j < 4; j++) {
    const uint4 v = lds128(eb_addr + j * 2048);
#pragma unroll
    for (int a = 0; a < 4; a++) e[4 * j + a] = EB_WORD(v, j, a);
  }
}
__device__ __forceinline__ void softmax_fast(const float (&s)[32], uint32_t (&p)[16]) {
#pragma unroll
  for (int i = 0; i < 16; i++) p[i] = hmul2(pack_bf16(ex2(s[2 * i]), ex2(s[2 * i + 1])), p[i]);
}
__device__ __forceinline__ uint32_t hmax2(uint32_t a, uint32_t b) {
  uint32_t r; asm("max.bf16x2 %0, %1, %2;" : "=r"(r) : "r"(a), "r"(b)); return r;
}
__device__ __forceinline__ uint32_t hmax2_nan(uint32_t a, uint32_t b) {
  uint32_t r; asm("max.NaN.bf16x2 %0, %1, %2;" : "=r"(r) : "r"(a), "r"(b)); return r;
}
__device__ __forceinline__ float quad_max(float m) {
  m = fmaxf(m, __shfl_xor_sync(0xffffffffu, m, 1));
  return fmaxf(m, __shfl_xor_sync(0xffffffffu, m, 2));
}
__device__ __forceinline__ void softmax_true_max(const float (&s)[32], uint32_t (&p)[16]) {
  float m0 = s[0], m1 = s[2];
#pragma unroll
  for (int g = 0; g < 8; g++) {
    m0 = fmaxf(m0, fmaxf(s[4 * g + 0], s[4 * g + 1]));
    m1 = fmaxf(m1, fmaxf(s[4 * g + 2], s[4 * g + 3]));
  }
  m0 = quad_max(m0); m1 = quad_max(m1);
  uint32_t n0 = 0, n1 = 0;
#pragma unroll
  for (int g = 0; g < 8; g++) {
    p[2 * g + 0] = hmul2(pack_bf16(ex2(s[4 * g + 0] - m0), ex2(s[4 * g + 1] - m0)), p[2 * g + 0]);
    p[2 * g + 1] = hmul2(pack_bf16(ex2(s[4 * g + 2] - m1), ex2(s[4 * g + 3] - m1)), p[2 * g + 1]);
    n0 = hmax2(n0, p[2 * g]); n1 = hmax2(n1, p[2 * g + 1]);
  }
  const uint32_t r = pack_bf16(rcp(quad_max(fmaxf(bf_lo(n0), bf_hi(n0)))), rcp(quad_max(fmaxf(bf_lo(n1), bf_hi(n1)))));
#pragma unroll
  for (int g = 0; g < 8; g++) { p[2 * g] = hmul2_b<0>(p[2 * g], r); p[2 * g + 1] = hmul2_b<1>(p[2 * g + 1], r); }
}
template <int H> __device__ __forceinline__ void issue_s(float (&s)[32], const uint32_t (&q)[24], uint64_t dK) {
  constexpr int Q0 = (H == 0 ? 0 : H == 1 ? 4 : H == 2 ? 12 : 16), P0 = (H == 0 ? 0 : H == 1 ? 3 : H == 2 ? 7 : 10);
  wgmma_rs_n64_t0<0>(s, q[Q0], q[Q0 + 1], q[Q0 + 2], q[Q0 + 3], dK + P0 * 64);
  wgmma_rs_n64_t0<1>(s, q[Q0 + 4], q[Q0 + 5], q[Q0 + 6], q[Q0 + 7], dK + P0 * 64 + 128);
}
template <int H> __device__ __forceinline__ void issue_pv(float (&o)[16], const uint32_t (&p)[16], uint64_t dV) {
  constexpr int P0 = (H == 0 ? 0 : H == 1 ? 3 : H == 2 ? 7 : 10);
  wgmma_rs_n32_t1<0>(o, p[0], p[1], p[2], p[3], dV + P0 * 64);
  wgmma_rs_n32_t1<1>(o, p[4], p[5], p[6], p[7], dV + P0 * 64 + 16);
  wgmma_rs_n32_t1<1>(o, p[8], p[9], p[10], p[11], dV + P0 * 64 + 32);
  wgmma_rs_n32_t1<1>(o, p[12], p[13], p[14], p[15], dV + P0 * 64 + 48);
}
__device__ __forceinline__ void issue_proj(float (&d)[48], uint64_t dX, uint64_t dW) {
#pragma unroll
  for (int s = 0; s < 6; s++) {
    const uint64_t a = dX + (s >> 1) * 256 + (s & 1) * 2, b = dW + s * 64;
    if (s == 0) wgmma_ss_n96_t1<0>(d, a, b); else wgmma_ss_n96_t1<1>(d, a, b);
  }
}
__device__ __forceinline__ void issue_qk(float (&d)[96], uint64_t dX, uint64_t dW) {
#pragma unroll
  for (int s = 0; s < 6; s++) {
    const uint64_t a = dX + (s >> 1) * 256 + (s & 1) * 2, b = dW + s * 128;
    if (s == 0) wgmma_ss_n192_t1<0>(d, a, b); else wgmma_ss_n192_t1<1>(d, a, b);
  }
}
__device__ __forceinline__ void pack_sumsq(const float* a, uint32_t (&f)[24], uint32_t (&sq)[8], uint32_t init) {
#pragma unroll
  for (int i = 0; i < 24; i++) f[i] = pack_bf16(a[2 * i], a[2 * i + 1]);
#pragma unroll
  for (int h = 0; h < 4; h++)
#pragma unroll
    for (int r = 0; r < 2; r++) {
      uint32_t u = f[6 * h + r], v = f[6 * h + 2 + r], w = f[6 * h + 4 + r];
      sq[2 * h + r] = hfma2(w, w, hfma2(v, v, hfma2(u, u, init)));
    }
}
__device__ __forceinline__ void scale_heads(uint32_t (&f)[24], const float (&r)[8]) {
#pragma unroll
  for (int h = 0; h < 4; h++) {
    const uint32_t p = pack_bf16(r[2 * h], r[2 * h + 1]);
#pragma unroll
    for (int c = 0; c < 3; c++) {
      f[6 * h + 2 * c] = hmul2_b<0>(f[6 * h + 2 * c], p);
      f[6 * h + 2 * c + 1] = hmul2_b<1>(f[6 * h + 2 * c + 1], p);
    }
  }
}
template <int ODD> __device__ __forceinline__ void norm_o(const float (&o)[16], uint32_t* of) {
  constexpr int SO = ODD ? 0 : 12, VO = ODD ? 4 : 0;
  const uint32_t p = pack_bf16(rcp(o[SO]), rcp(o[SO + 2]));
#pragma unroll
  for (int g = 0; g < 3; g++) {
    of[2 * g + 0] = hmul2_b<0>(pack_bf16(o[VO + 4 * g + 0], o[VO + 4 * g + 1]), p);
    of[2 * g + 1] = hmul2_b<1>(pack_bf16(o[VO + 4 * g + 2], o[VO + 4 * g + 3]), p);
  }
}

#define TL(i)
#define TG(i)

constexpr int BAR_KV = 1;
constexpr int BAR_AUX = 4;
constexpr int BAR_TAB = 7, BAR_SETUP = 8;
constexpr int NO_TICKET = 0xFF;
#define BORDER_EXTRA 1
constexpr int MB_WQK = 0, MB_X = 8, MB_KV = 32, MB_WV = 56, MB_WO = 64, MB_TURN = 72, MB_RDY = 128;
constexpr uint32_t sb = 1024, mbar = sb + SM_BAR;
constexpr uint32_t EPS8 = 0x2A0D2A0Du;

__device__ __forceinline__ void load_x_interior(const CUtensorMap* tm_x, int w, int g) {
  mbar_expect(mbar + MB_X + 8 * g, 12288);
  tma5(sb + SM_WG + g * WG_SZ + WG_X, tm_x, mbar + MB_X + 8 * g, 0, 0, ((w >> 8) & 255) * 8 + 4, (w & 255) * 2 + 1, 0);
}
__device__ __forceinline__ void load_x(const CUtensorMap* tm_x, const CUtensorMap* tm_xq, int w, int g) {
  const uint32_t dst = sb + SM_WG + g * WG_SZ + WG_X, bar = mbar + MB_X + 8 * g;
  const int wy = (w >> 8) & 255, wx = w & 255;
  mbar_expect(bar, 12288);
  if (wy != NWX - 1 && wx != NWX - 1) {
    tma5(dst, tm_x, bar, 0, 0, wy * 8 + 4, wx * 2 + 1, 0);
  } else {
#pragma unroll 1
    for (int i = 0; i < 12; i++) {
      const int q = i & 3, c = i >> 2;
      int y = wy * 8 + 4 + (q & 1) * 4; if (y >= IMG) y -= IMG;
      int xq = wx * 2 + 1 + (q >> 1);   if (xq >= IMG / 4) xq -= IMG / 4;
      tma5(dst + i * 1024, tm_xq, bar, 0, 0, y, xq, c);
    }
  }
}
__device__ __forceinline__ uint32_t mask_off(int w) { return (uint32_t)(((w >> 8) & 255) * NWX + (w & 255)) * 8192u; }
__device__ __forceinline__ int lds_uniform(uint32_t addr) { return __shfl_sync(0xffffffffu, lds32(addr), 0); }

__device__ __forceinline__ void qkv_epilogue(float (&qk)[96], uint32_t (&qa)[24], uint64_t dX, uint64_t dWv, uint32_t k_dst) {
  uint32_t ka[24], sk[8], sq[8];
  float k01[4], k23[4], q01[4], q23[4], vv[48];
  constexpr uint64_t dSel = mk_desc(sb + SM_SEL, 128, 256, 0);
  wg_wait<0>(); fence_regs(qk);
  pack_sumsq(qk + 48, ka, sk, EPS8);
  pack_sumsq(qk, qa, sq, EPS8);
  wg_fence();
  wgmma_rs_n8_t0<0>(k01, sk[0], sk[1], sk[2], sk[3], dSel);
  wgmma_rs_n8_t0<0>(k23, sk[4], sk[5], sk[6], sk[7], dSel);
  wgmma_rs_n8_t0<0>(q01, sq[0], sq[1], sq[2], sq[3], dSel);
  wgmma_rs_n8_t0<0>(q23, sq[4], sq[5], sq[6], sq[7], dSel);
  wg_commit();
  issue_proj(vv, dX, dWv); wg_commit();
  const uint4 qs = lds128(sb + SM_MISC);
  wg_wait<1>(); fence_regs(k01); fence_regs(k23); fence_regs(q01); fence_regs(q23);
  const float rk[8] = {rsq(k01[0]), rsq(k01[2]), rsq(k01[1]), rsq(k01[3]), rsq(k23[0]), rsq(k23[2]), rsq(k23[1]), rsq(k23[3])};
  scale_heads(ka, rk);
#pragma unroll
  for (int i = 0; i < 6; i++) stsm4(k_dst + (i + (i >= 3)) * 1024, ka[2 * i], ka[2 * i + 1], ka[12 + 2 * i], ka[12 + 2 * i + 1]);
  wg_wait<0>(); fence_regs(vv);
#pragma unroll
  for (int i = 0; i < 6; i++)
    stsm4(k_dst + (WG_V - WG_K) + (i + (i >= 3)) * 1024, pack_bf16(vv[4 * i], vv[4 * i + 1]), pack_bf16(vv[4 * i + 2], vv[4 * i + 3]),
          pack_bf16(vv[24 + 4 * i], vv[24 + 4 * i + 1]), pack_bf16(vv[24 + 4 * i + 2], vv[24 + 4 * i + 3]));
  const float s0 = __uint_as_float(qs.x), s1 = __uint_as_float(qs.y), s2 = __uint_as_float(qs.z), s3 = __uint_as_float(qs.w);
  const float rq[8] = {rsq(q01[0]) * s0, rsq(q01[2]) * s0, rsq(q01[1]) * s1, rsq(q01[3]) * s1,
                       rsq(q23[0]) * s2, rsq(q23[2]) * s2, rsq(q23[1]) * s3, rsq(q23[3]) * s3};
  scale_heads(qa, rq);
  fence_async();
}
__device__ __forceinline__ void issue_out(float (&y)[48], const uint32_t (&of)[24], uint64_t dWo) {
  wg_fence();
#pragma unroll
  for (int s = 0; s < 6; s++) {
    if (s == 0) wgmma_rs_n96_t1<0>(y, of[0], of[1], of[2], of[3], dWo);
    else wgmma_rs_n96_t1<1>(y, of[4 * s], of[4 * s + 1], of[4 * s + 2], of[4 * s + 3], dWo + s * 16);
  }
  wg_commit();
}
__device__ __forceinline__ void ln_head(float (&y)[48], uint32_t (&yb)[24], float (&var)[4], uint64_t dOnes) {
  uint32_t sy[8];
  wg_wait<0>(); fence_regs(y);
  pack_sumsq(y, yb, sy, 0u);
  wg_fence();
  wgmma_rs_n8_t0<0>(var, sy[0], sy[1], sy[2], sy[3], dOnes);
  wgmma_rs_n8_t0<1>(var, sy[4], sy[5], sy[6], sy[7], dOnes);
  wg_commit();
}
__device__ __forceinline__ char* out_ptr(__nv_bfloat16* out, int win, int warp, uint32_t t16) {
  int py = ((win >> 8) & 255) * 8 + 4 + (warp & 1) * 4;  if (py >= IMG) py -= IMG;
  int px = (win & 255) * 8 + 4 + (warp >> 1) * 4;        if (px >= IMG) px -= IMG;
  return reinterpret_cast<char*>(out) + ((uint32_t)(py * IMG + px) * PIXB - warp * 512 + t16 + ((t16 & 0xC0) << 1) + (t16 & 0x100) * 287);
}
__device__ __forceinline__ uint32_t ln_tail(const uint32_t (&yb)[24], float (&var)[4], char* optr) {
  fence_regs(var);
  uint32_t last;
  const uint32_t nn = pack_bf16(rsq(fmaf(var[0], 1.f / 96.f, 1e-5f)), rsq(fmaf(var[2], 1.f / 96.f, 1e-5f)));
#pragma unroll
  for (int j = 0; j < 3; j++) {
    stg128(optr + j * 64, hmul2_b<0>(yb[8 * j], nn), hmul2_b<0>(yb[8 * j + 2], nn), hmul2_b<0>(yb[8 * j + 4], nn), hmul2_b<0>(yb[8 * j + 6], nn));
    last = hmul2_b<1>(yb[8 * j + 7], nn);
    stg128(optr + 2 * ROWB + j * 64, hmul2_b<1>(yb[8 * j + 1], nn), hmul2_b<1>(yb[8 * j + 3], nn), hmul2_b<1>(yb[8 * j + 5], nn), last);
  }
  return last;
}

__device__ __forceinline__ void load_mask_frag(uint32_t (&mk)[16], const char* tile, int warp, int lane) {
  const char* mrow = tile + (orig_tok(16 * warp + (lane >> 2)) * 64 + ((lane >> 1) & 1) * 8 + (lane & 1) * 2) * 2;
#pragma unroll
  for (int Gk = 0; Gk < 8; Gk++) {
    mk[2 * Gk] = __ldg(reinterpret_cast<const uint32_t*>(mrow + (Gk & 3) * 32 + (Gk >> 2) * 8));
    mk[2 * Gk + 1] = __ldg(reinterpret_cast<const uint32_t*>(mrow + 2048 + (Gk & 3) * 32 + (Gk >> 2) * 8));
  }
}
__device__ __forceinline__ bool mask_unsafe(const uint32_t (&mk)[16]) {
  uint32_t x0 = mk[0], x1 = mk[1];
#pragma unroll
  for (int i = 2; i < 16; i += 2) { x0 = hmax2_nan(x0, mk[i]); x1 = hmax2_nan(x1, mk[i + 1]); }
  const bool nan_in = !(bf_lo(x0) == bf_lo(x0) && bf_hi(x0) == bf_hi(x0) && bf_lo(x1) == bf_lo(x1) && bf_hi(x1) == bf_hi(x1));
  const float r0 = quad_max(fmaxf(bf_lo(x0), bf_hi(x0))), r1 = quad_max(fmaxf(bf_lo(x1), bf_hi(x1)));
  return nan_in || !(fabsf(r0) <= 8.f && fabsf(r1) <= 8.f);
}

__device__ __forceinline__ void general_windows(const CUtensorMap* tm_x, const CUtensorMap* tm_xq, const char* mb, __nv_bfloat16* out, uint32_t xph) {
  int tid;
  asm volatile("mov.u32 %0, %%tid.x;" : "=r"(tid));
  const int lane = tid & 31;
  const int warp = __shfl_sync(0xffffffffu, (tid >> 5) & 3, 0), wg = __shfl_sync(0xffffffffu, tid >> 7, 0);
  const uint32_t t16 = (tid & 127) * 16, wgb = sb + SM_WG + wg * WG_SZ, bar_x = mbar + MB_X + 8 * wg;
  const uint32_t k_dst = wgb + WG_K + (lane >> 4) * 7168 + warp * 256 + (lane & 15) * 16;
  const uint32_t slow_heads = lds_uniform(sb + SM_SLOW);
  const uint64_t dX = mk_desc(WG_X, 16, 512, 2) + (wgb >> 4), dK = mk_desc(WG_K, 1024, 128, 0) + (wgb >> 4), dV = mk_desc(WG_V, 128, 1024, 0) + (wgb >> 4);
#pragma unroll 1
  for (uint32_t gl = sb + SM_GEN + wg * NENT * 4;; gl += 4) {
    const int win = lds_uniform(gl);
    if (win < 0) break;
    uint32_t qa[24], of[24], mk[16];
    uint32_t tm;
    {
      load_mask_frag(mk, mb + mask_off(win), warp, lane);
      float qk[96];
      mbar_wait(bar_x, xph); xph ^= 1;
      wg_fence();
      issue_qk(qk, dX, mk_desc(sb + SM_W, 12288, 1024, 1)); wg_commit();
      uint32_t any = 0;
#pragma unroll
      for (int i = 0; i < 16; i += 2) any |= mk[i] | mk[i + 1];
      tm = bar_wg_or(BAR_KV + wg, (any & 0x7FFF7FFFu) != 0) ? 0x1Fu : slow_heads;
      qkv_epilogue(qk, qa, dX, mk_desc(sb + SM_WV, 6144, 512, 2), k_dst);
    }
    bar_sync_n(BAR_AUX + wg, 128);
    if (warp == 0 && elect_one()) {
      const int nxt = lds32(gl + 4);
      if (nxt >= 0) { load_x(tm_x, tm_xq, nxt, wg); prefetch_l2(mb + mask_off(nxt), 8192); }
    }
    __syncwarp();
    auto head = [&](float (&sc)[32], uint32_t (&p)[16], bool tmax) {
      if (tmax) {
        if (tm & 16) {
#pragma unroll
          for (int i = 0; i < 16; i++) {
            sc[2 * i] = fmaf(bf_lo(mk[i]), LOG2E, sc[2 * i]); sc[2 * i + 1] = fmaf(bf_hi(mk[i]), LOG2E, sc[2 * i + 1]);
          }
        }
        softmax_true_max(sc, p);
      } else {
        softmax_fast(sc, p);
      }
    };
#pragma unroll
    for (int i = 0; i < 24; i++) of[i] = 0;
#pragma unroll 1
    for (int hp = 0; hp < 2; hp++) {
      float sA[32], sB[32], oA[16], oB[16]; uint32_t p[16];
      const uint32_t po = hp * 7 * 64;
      wg_fence();
      issue_s<0>(sA, qa, dK + po);
      issue_s<1>(sB, qa, dK + po); wg_commit();
      load_eb(p, sb + SM_EB + t16 + hp * 16384);
      wg_wait<0>(); fence_regs(sA); fence_regs(sB);
#pragma unroll
      for (int i = 0; i < 12; i++) { qa[i] = qa[i + 12]; of[i] = of[i + 12]; }
      head(sA, p, (tm >> (2 * hp)) & 1);
      wg_fence(); issue_pv<0>(oA, p, dV + po); wg_commit();
      uint32_t p2[16];
      load_eb(p2, sb + SM_EB + t16 + hp * 16384 + 8192);
      head(sB, p2, (tm >> (2 * hp + 1)) & 1);
      wg_fence(); issue_pv<1>(oB, p2, dV + po); wg_commit();
      wg_wait<1>(); fence_regs(oA);
      norm_o<0>(oA, of + 12);
      wg_wait<0>(); fence_regs(oB);
      norm_o<1>(oB, of + 18);
    }
    float y[48], var[4]; uint32_t yb[24];
    issue_out(y, of, mk_desc(sb + SM_WO, 128, 1536, 0));
    ln_head(y, yb, var, dV + 3 * 64);
    wg_wait<0>();
    ln_tail(yb, var, out_ptr(out, win, warp, t16));
  }
}

__global__ void __launch_bounds__(384, 1)
swin_kernel(const __grid_constant__ CUtensorMap tm_x, const __grid_constant__ CUtensorMap tm_xq, const __grid_constant__ CUtensorMap tm_wqk,
            const __grid_constant__ CUtensorMap tm_wv,
            const __nv_bfloat16* __restrict__ wo,
            const __nv_bfloat16* __restrict__ logit_scale, const __nv_bfloat16* __restrict__ w1, const __nv_bfloat16* __restrict__ w2,
            const __nv_bfloat16* __restrict__ coords, const int* __restrict__ rel_idx, const __nv_bfloat16* __restrict__ mask,
            __nv_bfloat16* __restrict__ out) {
  extern __shared__ __align__(1024) uint8_t smem[];
  const int tid = threadIdx.x, lane = tid & 31;
  const int warp = __shfl_sync(0xffffffffu, (tid >> 5) & 3, 0), wg = __shfl_sync(0xffffffffu, tid >> 7, 0);
  const uint32_t t16 = (tid & 127) * 16;
  const int G = gridDim.x;
  const uint32_t wgb = sb + SM_WG + wg * WG_SZ;
  const uint32_t bar_x = mbar + MB_X + 8 * wg;
  const char* mb = reinterpret_cast<const char*>(mask);
  TL(0); TG(14);

  uint4 mw[4];
  auto load_mask = [&](uint32_t off) {
    const char* src = mb + (off + t16);
#pragma unroll
    for (int i = 0; i < 4; i++) mw[i] = ldg128_stream(src + i * 2048);
  };
  auto mask_or = [&](uint32_t seed) {
    uint32_t r = seed & 0x80008000u;
#pragma unroll
    for (int i = 0; i < 4; i++) {
      asm("lop3.b32 %0, %0, %1, %2, 0xFE;" : "+r"(r) : "r"(mw[i].x), "r"(mw[i].y));
      asm("lop3.b32 %0, %0, %1, %2, 0xFE;" : "+r"(r) : "r"(mw[i].z), "r"(mw[i].w));
    }
    return r;
  };

  const bool g132 = G == 132;
  const uint2 lsw = __ldg(reinterpret_cast<const uint2*>(logit_scale));
  uint32_t cw = 0;
  int4 rid[4];
  if (wg == 0) {
    if (warp == 0) {
      if (elect_one()) {
#pragma unroll
        for (int i = 0; i < 13; i++) mbar_init(mbar + 8 * i, ((i >= 4 && i < 7) || i >= 9) ? 4 : 1);
        mbar_init(mbar + MB_RDY, 8);
        fence_async();
        mbar_expect(mbar + MB_WQK, 3 * 12288);
        tma3(sb + SM_W, &tm_wqk, mbar + MB_WQK, 0, 0, 0);
        load_x_interior(&tm_x, slot_window(blockIdx.x, g132), 0);
        mbar_expect(mbar + MB_WV, 3 * 6144);
        tma3(sb + SM_WV, &tm_wv, mbar + MB_WV, 0, 0, 0);
        mbar_expect(mbar + MB_WO, 18432);
        bulk_g2s(sb + SM_WOR, wo, 18432, mbar + MB_WO);
      }
      __syncwarp();
    }
  } else {
    const int i = tid - 128;
    if (i < 12) *reinterpret_cast<uint4*>(smem + SM_PAR + 16 * i) = __ldg(i < 4 ? reinterpret_cast<const uint4*>(w1) + i : reinterpret_cast<const uint4*>(w2) + (i - 4));
    if (i < 225) cw = __ldg(reinterpret_cast<const uint32_t*>(coords) + i);
  }
  if ((uint32_t)__cvta_generic_to_shared(smem) != sb) __trap();
  auto const_tiles = [&]() {
    const int i = tid & 127;
    uint8_t* vt = smem + SM_WG + wg * WG_SZ + WG_V + (i < 64 ? 3 : 10) * 1024 + (i & 63) * 16;
    *reinterpret_cast<uint4*>(vt) = make_uint4(0x3F803F80u, 0x3F803F80u, 0x3F803F80u, 0x3F803F80u);
    *reinterpret_cast<uint4*>(vt - (WG_V - WG_K)) = make_uint4(0u, 0u, 0u, 0u);
  };
  if (wg != 2) const_tiles();
  float tau[4]; uint32_t slow_heads = 0;
  {
    const float ls[4] = {bf_lo(lsw.x), bf_hi(lsw.x), bf_lo(lsw.y), bf_hi(lsw.y)};
#pragma unroll
    for (int h = 0; h < 4; h++) {
      const float c = ls[h] < -100.f ? -100.f : (ls[h] > 4.59375f ? 4.59375f : ls[h]);
      tau[h] = rbf(ex2(c * LOG2E)) * LOG2E;
      if (!(tau[h] <= TAU_FAST_MAX)) slow_heads |= 1u << h;
    }
    slow_heads = __shfl_sync(0xffffffffu, slow_heads, 0);
  }
  if (wg == 0 && warp == 1) {
    const int eg = lane / NENT, ei = lane - eg * NENT, sl = blockIdx.x + eg * G + ei * 3 * G;
    const int w = (sl < NWIN && eg < 3) ? slot_window(sl, g132) : -1;
    const bool queues = w >= 0 && (w >> 8) != NWX - 1 && (w & 255) != NWX - 1;
    const uint32_t qmask = __ballot_sync(0xffffffffu, queues);
    const int key = (eg + 3 * ei + BORDER_EXTRA * __popc((~qmask >> (eg * NENT)) & ((1u << ei) - 1))) * 4 + eg;
    int ticket = 0;
#pragma unroll 1
    for (int l = 0; l < 3 * NENT; l++) { const int k = __shfl_sync(0xffffffffu, key, l); ticket += ((qmask >> l) & 1) && k < key; }
    const int ent = w | (queues ? ticket : NO_TICKET) << 16;
    if (eg < 3) {
      *reinterpret_cast<int*>(smem + SM_WIN + lane * 4) = slow_heads ? -1 : ent;
      *reinterpret_cast<int*>(smem + SM_GEN + lane * 4) = slow_heads ? ent : -1;
    }
  }
  if (wg == 0 && warp == 3 && lane < 16) {
    const uint32_t v = (((lane >> 3) ^ lane) & 1) ? 0u : 0x3F803F80u;
    *reinterpret_cast<uint4*>(smem + SM_SEL + lane * 16) = make_uint4(v, v, v, v);
  }
  TL(3);
  if (wg == 0) {
    if (tid == 0) {
      *reinterpret_cast<float4*>(smem + SM_MISC) = make_float4(tau[0], tau[1], tau[2], tau[3]);
      *reinterpret_cast<uint32_t*>(smem + SM_SLOW) = slow_heads;
    }
    fence_async();
    bar_arrive_n(BAR_SETUP, 384);
    bar_sync_n(BAR_AUX, 128);
  } else {
    const int i = tid - 128;
#pragma unroll
    for (int c = 0; c < 4; c++) {
      const uint4 r = ldg128_stream(reinterpret_cast<const int4*>(rel_idx) + c * 256 + i);
      rid[c] = make_int4(r.x, r.y, r.z, r.w);
    }
    bar_sync_n(BAR_TAB, 256);
    TL(4);
    if (i < 225) {
      const float c0 = bf_lo(cw), c1 = bf_hi(cw);
      float z[4] = {0.f, 0.f, 0.f, 0.f};
#pragma unroll
      for (int jj = 0; jj < 2; jj++) {
        const uint4 ua4 = lds128(sb + SM_PAR + 16 * jj), ub4 = lds128(sb + SM_PAR + 32 + 16 * jj);
        const uint32_t ua[4] = {ua4.x, ua4.y, ua4.z, ua4.w}, ub[4] = {ub4.x, ub4.y, ub4.z, ub4.w};
#pragma unroll
        for (int j = 0; j < 4; j++) {
          const uint4 wb = lds128(sb + SM_PAR + 64 + 64 * jj + 16 * j);
          const uint32_t hp = pack_bf16(fmaf(c1, bf_lo(ub[j]), c0 * bf_lo(ua[j])), fmaf(c1, bf_hi(ub[j]), c0 * bf_hi(ua[j])));
          float h0 = bf_lo(hp), h1 = bf_hi(hp);
          h0 = h0 > 0.f ? h0 : h0 * 0.f; h1 = h1 > 0.f ? h1 : h1 * 0.f;
          z[0] = fmaf(h0, bf_lo(wb.x), z[0]); z[1] = fmaf(h0, bf_hi(wb.x), z[1]); z[2] = fmaf(h0, bf_lo(wb.y), z[2]); z[3] = fmaf(h0, bf_hi(wb.y), z[3]);
          z[0] = fmaf(h1, bf_lo(wb.z), z[0]); z[1] = fmaf(h1, bf_hi(wb.z), z[1]); z[2] = fmaf(h1, bf_lo(wb.w), z[2]); z[3] = fmaf(h1, bf_hi(wb.w), z[3]);
        }
      }
      float e[4];
#pragma unroll
      for (int q = 0; q < 4; q++) {
        const float sh = ((slow_heads >> q) & 1) ? 0.f : fminf(0.f, 25.f - 1.02f * tau[q]);
        e[q] = ex2(fmaf(16.f * LOG2E, rbf(rcp(1.f + ex2(-LOG2E * rbf(z[q])))), sh));
      }
      *reinterpret_cast<uint2*>(smem + SM_TAB + 8 * i) = make_uint2(pack_bf16(e[0], e[1]), pack_bf16(e[2], e[3]));
    }
    TL(5);
    bar_sync_n(BAR_SETUP, 384);
    if (tid == 128 + 127) {
      const int w = slot_window(blockIdx.x + G, g132);
      load_x_interior(&tm_x, w, 1);
      prefetch_l2(mb + mask_off(w), 8192);
    }
    __syncwarp();
#pragma unroll
    for (int c = 0; c < 4; c++) asm volatile("" : "+r"(rid[c].x), "+r"(rid[c].y), "+r"(rid[c].z), "+r"(rid[c].w));
    {
      const int y = (i & 15) >> 1, xh = i & 1, j = 2 * xh + (y >> 2);
      const int X = (i >> 4) & 7, Yl = (i >> 7) & 1;
      uint8_t* dst = smem + SM_EB + j * 2048 + ((X >> 2) * 64 + (Yl * 4 + (X & 3)) * 4 + 2 * (y & 1)) * 16 + ((y >> 1) & 1) * 8;
#pragma unroll
      for (int c = 0; c < 4; c++) {
        const int ia0 = xh ? rid[c].z : rid[c].x, ia1 = xh ? rid[c].w : rid[c].y, ib0 = xh ? rid[c].x : rid[c].z, ib1 = xh ? rid[c].y : rid[c].w;
        const uint2 a0 = *reinterpret_cast<const uint2*>(smem + SM_TAB + 8 * ia0), a1 = *reinterpret_cast<const uint2*>(smem + SM_TAB + 8 * ia1);
        const uint2 b0 = *reinterpret_cast<const uint2*>(smem + SM_TAB + 8 * ib0), b1 = *reinterpret_cast<const uint2*>(smem + SM_TAB + 8 * ib1);
        uint8_t* d0 = dst + (c >> 1) * 512 + (((c & 1) ^ (j & 1)) * 4) + xh * 16;
        uint8_t* d1 = dst + (c >> 1) * 512 + (((c & 1) ^ (j & 1)) * 4) + (xh ^ 1) * 16;
        *reinterpret_cast<uint32_t*>(d0)         = __byte_perm(a0.x, a1.x, 0x5410); *reinterpret_cast<uint32_t*>(d1)         = __byte_perm(b0.x, b1.x, 0x5410);
        *reinterpret_cast<uint32_t*>(d0 + 8192)  = __byte_perm(a0.x, a1.x, 0x7632); *reinterpret_cast<uint32_t*>(d1 + 8192)  = __byte_perm(b0.x, b1.x, 0x7632);
        *reinterpret_cast<uint32_t*>(d0 + 16384) = __byte_perm(a0.y, a1.y, 0x5410); *reinterpret_cast<uint32_t*>(d1 + 16384) = __byte_perm(b0.y, b1.y, 0x5410);
        *reinterpret_cast<uint32_t*>(d0 + 24576) = __byte_perm(a0.y, a1.y, 0x7632); *reinterpret_cast<uint32_t*>(d1 + 24576) = __byte_perm(b0.y, b1.y, 0x7632);
      }
    }
    TL(6);
    if (tid == 256) {
      const int w = slot_window(blockIdx.x + 2 * G, g132);
      load_x_interior(&tm_x, w, 2);
      prefetch_l2(mb + mask_off(w), 8192);
    }
    __syncwarp();
    fence_async();
    if (elect_one()) mbar_arrive(mbar + MB_RDY);
    __syncwarp();
    bar_sync_n(BAR_TAB, 256);
    if (wg == 2) {
      mbar_wait(mbar + MB_WO, 0);
#pragma unroll 1
      for (int r = 0; r < 3; r++) {
        uint4 v[3];
#pragma unroll
        for (int c = 0; c < 3; c++) v[c] = lds128(sb + SM_WOR + (r * 32 + ((tid & 127) >> 2)) * 192 + c * 64 + (lane & 3) * 16);
        float sum = 0.f;
#pragma unroll
        for (int c = 0; c < 3; c++)
          sum += (bf_lo(v[c].x) + bf_hi(v[c].x)) + (bf_lo(v[c].y) + bf_hi(v[c].y)) + (bf_lo(v[c].z) + bf_hi(v[c].z)) + (bf_lo(v[c].w) + bf_hi(v[c].w));
        sum += __shfl_xor_sync(0xffffffffu, sum, 1);
        sum += __shfl_xor_sync(0xffffffffu, sum, 2);
        const float mu = sum * (1.f / 96.f);
        auto cen = [&](uint32_t u) { return pack_bf16(bf_lo(u) - mu, bf_hi(u) - mu); };
        uint8_t* dst = smem + SM_WO + (r * 4 + warp) * 128 + lane * 4;
#pragma unroll
        for (int j = 0; j < 3; j++) {
          *reinterpret_cast<uint32_t*>(dst + (4 * j + 0) * 1536) = cen(v[j].x);
          *reinterpret_cast<uint32_t*>(dst + (4 * j + 1) * 1536) = cen(v[j].y);
          *reinterpret_cast<uint32_t*>(dst + (4 * j + 2) * 1536) = cen(v[j].z);
          *reinterpret_cast<uint32_t*>(dst + (4 * j + 3) * 1536) = cen(v[j].w);
        }
      }
      bar_sync_n(BAR_AUX + 2, 128);
      const_tiles();
      fence_async();
      __syncwarp();
      if (elect_one()) mbar_arrive(mbar + MB_TURN);
      __syncwarp();
    }
  }
  uint32_t wl = sb + SM_WIN + wg * NENT * 4;
  int win = lds_uniform(wl), nxt = lds_uniform(wl + 4);
  TL(1);
  mbar_wait(mbar + MB_WQK, 0);
  if (win >= 0) {
    float qk[96];
    load_mask(mask_off(win));
    mbar_wait(bar_x, 0);
    TL(2);
    wg_fence();
    issue_qk(qk, mk_desc(WG_X, 16, 512, 2) + (wgb >> 4), mk_desc(sb + SM_W, 12288, 1024, 1)); wg_commit();
    if (warp == 0 && nxt >= 0 && elect_one()) prefetch_l2(mb + mask_off(nxt), 8192);
    __syncwarp();
    uint32_t mword = mask_or(0);
    TL(7);
    mbar_wait(mbar + MB_WV, 0);
    mbar_wait(mbar + MB_RDY, 0);
    TL(8);

    const uint32_t k_dst = wgb + WG_K + (lane >> 4) * 7168 + warp * 256 + (lane & 15) * 16;
    const uint32_t eb_base = sb + SM_EB + t16;
    auto first_general = [&]() {
      if (warp == 0 && elect_one()) {
        const int w = lds32(sb + SM_GEN + wg * NENT * 4);
        if (w >= 0) { load_x(&tm_x, &tm_xq, w, wg); prefetch_l2(mb + mask_off(w), 8192); }
      }
      __syncwarp();
    };
    while (true) {
      const int nxt2 = lds_uniform(wl + 8), tk = win >> 16;
      const bool more = nxt >= 0;
      const uint32_t z0 = wl >> 20, zw = z0 + (wgb >> 4);
      const uint64_t dX = opaque(mk_desc(WG_X, 16, 512, 2) + zw);
      TL(0);
      if (tk == NO_TICKET && t16 == 0) prefetch_l2(mb + mask_off(win), 8192);
      uint32_t qa[24];
      qkv_epilogue(qk, qa, dX, opaque(mk_desc(sb + SM_WV, 6144, 512, 2) + z0), k_dst);
      TL(5);
      const bool masked = bar_wg_or(BAR_KV + wg, (mword & 0x7FFF7FFFu) != 0u);
      TL(6);
      const uint64_t dK = opaque(mk_desc(WG_K, 1024, 128, 0) + zw), dV = opaque(mk_desc(WG_V, 128, 1024, 0) + zw);
      auto prefetch_next = [&]() {
        if (warp == 0 && more) {
          if (elect_one()) {
            load_x(&tm_x, &tm_xq, nxt, wg);
            if (nxt2 >= 0) prefetch_l2(mb + mask_off(nxt2), 8192);
          }
          __syncwarp();
        }
      };
      auto wait_turn = [&]() { if (tk != NO_TICKET) mbar_wait(mbar + MB_TURN + (tk & 3) * 8, (tk >> 2) & 1); };
      auto pass_turn = [&]() { if (tk != NO_TICKET && elect_one()) mbar_arrive(mbar + MB_TURN + ((tk + 1) & 3) * 8); __syncwarp(); };
      auto next_qk = [&]() { issue_qk(qk, dX, opaque(mk_desc(sb + SM_W, 12288, 1024, 1) + z0)); wg_commit(); };
      auto tiles_ready = [&]() {
        if (elect_one()) mbar_arrive(bar_x + (MB_KV - MB_X));
        __syncwarp();
        const uint32_t xphase = (wl >> 2) & 1;
        mbar_wait(bar_x, xphase ^ 1);
        mbar_wait(bar_x + (MB_KV - MB_X), xphase);
      };
      uint32_t of[24];
      auto attention = [&](auto em) {
          constexpr bool EM = decltype(em)::value;
          auto table = [&](uint32_t (&p)[16], int h) {
            load_eb(p, eb_base + h * 8192);
            if (EM) {
#pragma unroll
              for (int j = 0; j < 4; j++) {
                const uint4 m = lds128(wgb + WG_X + t16 + j * 2048);
                p[4 * j] = hmul2(p[4 * j], m.x); p[4 * j + 1] = hmul2(p[4 * j + 1], m.y);
                p[4 * j + 2] = hmul2(p[4 * j + 2], m.z); p[4 * j + 3] = hmul2(p[4 * j + 3], m.w);
              }
            }
          };
          float sA[32], sB[32], oA[16], oB[16], oC[16], oD[16];
          uint32_t pA[16], pB[16], pC[16], pD[16];
          wg_fence();
          issue_s<0>(sA, qa, dK);
          issue_s<1>(sB, qa, dK); wg_commit();
          table(pA, 0);
          if (!EM) { prefetch_next(); wait_turn(); }
          wg_wait<0>(); fence_regs(sA); fence_regs(sB);
          TL(7);
          table(pB, 1);
          softmax_fast(sA, pA);
          wg_fence();
          issue_s<2>(sA, qa, dK); wg_commit();
          issue_pv<0>(oA, pA, dV); wg_commit();
          TL(8);
          softmax_fast(sB, pB);
          table(pC, 2);
          wg_wait<1>(); fence_regs(sA);
          wg_fence();
          issue_s<3>(sB, qa, dK); wg_commit();
          issue_pv<1>(oB, pB, dV); wg_commit();
          TL(9);
          softmax_fast(sA, pC);
          if (!EM) pass_turn();
          table(pD, 3);
          if (EM) { fence_async(); bar_sync_n(BAR_AUX + wg, 128); prefetch_next(); }
          wg_wait<1>(); fence_regs(sB); fence_regs(oA);
          wg_fence();
          issue_pv<2>(oC, pC, dV); wg_commit();
          TL(10);
          norm_o<0>(oA, of);
          softmax_fast(sB, pD);
          wg_fence();
          issue_pv<3>(oD, pD, dV); wg_commit();
          if (more) load_mask(mask_off(nxt));
          else { mw[0] = mw[1] = mw[2] = mw[3] = make_uint4(0, 0, 0, 0); }
          wg_wait<1>(); fence_regs(oB); fence_regs(oC);
          norm_o<1>(oB, of + 6);
          norm_o<0>(oC, of + 12);
          wg_wait<0>(); fence_regs(oD);
          norm_o<1>(oD, of + 18);
        };
      bool handled = true;
      if (__builtin_expect(!masked, 1)) {
        attention(std::false_type{});
      } else {
        uint32_t mk[16];
        load_mask_frag(mk, mb + mask_off(win), warp, lane);
        wait_turn(); pass_turn();
        handled = !bar_wg_or(BAR_AUX + wg, mask_unsafe(mk));
        if (handled) {
#pragma unroll
          for (int i = 0; i < 16; i++) mk[i] = pack_bf16(ex2(bf_lo(mk[i]) * LOG2E), ex2(bf_hi(mk[i]) * LOG2E));
#pragma unroll
          for (int j = 0; j < 4; j++)
            asm volatile("st.shared.v4.u32 [%0], {%1,%2,%3,%4};" :: "r"(wgb + WG_X + t16 + j * 2048), "r"(mk[4 * j]), "r"(mk[4 * j + 1]), "r"(mk[4 * j + 2]), "r"(mk[4 * j + 3]) : "memory");
          attention(std::true_type{});
        }
      }
      if (__builtin_expect(handled, 1)) {
        TL(11);
        float y[48], var[4]; uint32_t yb[24];
        issue_out(y, of, opaque(mk_desc(sb + SM_WO, 128, 1536, 0) + z0));
        char* const optr = out_ptr(out, win, warp, t16);
        if (!more) { ln_head(y, yb, var, dV + 3 * 64); wg_wait<0>(); ln_tail(yb, var, optr); TL(14); break; }
        tiles_ready();
        ln_head(y, yb, var, dV + 3 * 64);
        TL(12);
        next_qk();
        wg_wait<1>();
        TL(13);
        mword = mask_or(ln_tail(yb, var, optr));
      } else {
        if (t16 == 0) {
          uint32_t gl = sb + SM_GEN + wg * NENT * 4;
          while ((int)lds32(gl) >= 0) gl += 4;
          asm volatile("st.shared.u32 [%0], %1;" :: "r"(gl), "r"(win) : "memory");
        }
        __syncwarp();
        prefetch_next();
        if (!more) break;
        load_mask(mask_off(nxt));
        tiles_ready();
        wg_fence();
        next_qk();
        mword = mask_or(0);
      }
      TL(14);
      wl += 4;
      win = nxt; nxt = nxt2;
    }
    wl += 4;
    first_general();
  } else {
    mbar_wait(mbar + MB_WV, 0);
    mbar_wait(mbar + MB_RDY, 0);
    mbar_wait(mbar + MB_TURN, 0);
  }
  bar_sync_n(BAR_AUX + wg, 128);
  if (lds_uniform(sb + SM_GEN + wg * NENT * 4) >= 0) general_windows(&tm_x, &tm_xq, mb, out, (wl >> 2) & 1);
  TG(15);
}

typedef CUresult (*EncodeFn)(CUtensorMap*, CUtensorMapDataType, cuuint32_t, void*, const cuuint64_t*, const cuuint64_t*,
                             const cuuint32_t*, const cuuint32_t*, CUtensorMapInterleave, CUtensorMapSwizzle,
                             CUtensorMapL2promotion, CUtensorMapFloatOOBfill);

}

extern "C" void kernel_launch(void* const* d_in, const int* in_sizes, int n_in, void* d_out, int out_size) {
  static int sms = 0;
  static EncodeFn encode = nullptr;
  if (sms == 0) {
    int dev = 0;
    cudaGetDevice(&dev);
    cudaDeviceGetAttribute(&sms, cudaDevAttrMultiProcessorCount, dev);
    if (sms < 96) sms = 96;
    cudaFuncSetAttribute(swin_kernel, cudaFuncAttributeMaxDynamicSharedMemorySize, SM_TOTAL);
    cudaDriverEntryPointQueryResult qr;
    void* fn = nullptr;
    cudaGetDriverEntryPoint("cuTensorMapEncodeTiled", &fn, cudaEnableDefault, &qr);
    encode = (EncodeFn)fn;
  }
  CUtensorMap tm_x, tm_xq, tm_wqk, tm_wv;
  {
    cuuint64_t dims[5] = {32, 4, IMG, IMG / 4, 3};
    cuuint64_t strides[4] = {PIXB, ROWB, 4 * PIXB, 64};
    cuuint32_t es[5] = {1, 1, 1, 1, 1};
    cuuint32_t box[5] = {32, 4, 8, 2, 3}, boxq[5] = {32, 4, 4, 1, 1};
    encode(&tm_x, CU_TENSOR_MAP_DATA_TYPE_BFLOAT16, 5, d_in[0], dims, strides, box, es, CU_TENSOR_MAP_INTERLEAVE_NONE,
           CU_TENSOR_MAP_SWIZZLE_64B, CU_TENSOR_MAP_L2_PROMOTION_L2_128B, CU_TENSOR_MAP_FLOAT_OOB_FILL_NONE);
    encode(&tm_xq, CU_TENSOR_MAP_DATA_TYPE_BFLOAT16, 5, d_in[0], dims, strides, boxq, es, CU_TENSOR_MAP_INTERLEAVE_NONE,
           CU_TENSOR_MAP_SWIZZLE_64B, CU_TENSOR_MAP_L2_PROMOTION_L2_128B, CU_TENSOR_MAP_FLOAT_OOB_FILL_NONE);
    cuuint64_t qd[3] = {64, 96, 3}, qs[2] = {576, 128}, vd[3] = {32, 96, 3}, vs[2] = {576, 64};
    cuuint32_t qb[3] = {64, 96, 3}, vb[3] = {32, 96, 3};
    encode(&tm_wqk, CU_TENSOR_MAP_DATA_TYPE_BFLOAT16, 3, d_in[1], qd, qs, qb, es, CU_TENSOR_MAP_INTERLEAVE_NONE,
           CU_TENSOR_MAP_SWIZZLE_128B, CU_TENSOR_MAP_L2_PROMOTION_L2_256B, CU_TENSOR_MAP_FLOAT_OOB_FILL_NONE);
    encode(&tm_wv, CU_TENSOR_MAP_DATA_TYPE_BFLOAT16, 3, (char*)d_in[1] + 384, vd, vs, vb, es, CU_TENSOR_MAP_INTERLEAVE_NONE,
           CU_TENSOR_MAP_SWIZZLE_64B, CU_TENSOR_MAP_L2_PROMOTION_L2_256B, CU_TENSOR_MAP_FLOAT_OOB_FILL_NONE);
  }
  swin_kernel<<<sms, 384, SM_TOTAL>>>(
      tm_x, tm_xq, tm_wqk, tm_wv, (const __nv_bfloat16*)d_in[2], (const __nv_bfloat16*)d_in[3],
      (const __nv_bfloat16*)d_in[4], (const __nv_bfloat16*)d_in[5], (const __nv_bfloat16*)d_in[6], (const int*)d_in[7],
      (const __nv_bfloat16*)d_in[8], (__nv_bfloat16*)d_out);
}
```

```cpp
#include <cuda_runtime.h>
#include <cuda.h>
#include <cuda_bf16.h>
#include <stdint.h>
#include <type_traits>

#define TOKEN 3
namespace {

constexpr int IMG   = 384;
constexpr int NWX   = 48;
constexpr int NWIN  = NWX * NWX;
constexpr int PIXB  = 192;
constexpr int ROWB  = IMG * PIXB;
constexpr float LOG2E = 1.4426950408889634f;
constexpr float TAU_FAST_MAX = 50.f;

constexpr int SM_W    = 0;
constexpr int SM_WV   = 3 * 12288;
constexpr int SM_WO   = SM_W + 9 * 6144;
constexpr int SM_EB   = SM_WO + 12 * 1536;
constexpr int SM_WG   = SM_EB + 32768;
constexpr int WG_X    = 0;
constexpr int WG_K    = 12288;
constexpr int WG_V    = WG_K + 14336;
constexpr int WG_SZ   = WG_V + 14336;
constexpr int SM_TAB  = SM_WG + WG_SZ + WG_V + 4096;
constexpr int SM_WOR  = SM_WG + 2 * WG_SZ + WG_K;
constexpr int SM_SEL  = SM_WG + 3 * WG_SZ;
constexpr int SM_MISC = SM_SEL + 256;
constexpr int SM_BAR  = SM_MISC + 16;
constexpr int SM_SLOW = SM_BAR + 104;
constexpr int SM_PAR  = SM_BAR + 160;
constexpr int NENT    = 10;
constexpr int SM_WIN  = SM_PAR + 192;
constexpr int SM_WEM  = SM_WIN + 3 * NENT * 4;
constexpr int SM_GEN  = SM_WEM + 3 * NENT * 4;
constexpr int SM_TOTAL = SM_GEN + 3 * NENT * 4;
static_assert((SM_WIN & 7) == 0 && (NENT & 1) == 0, "list parity");

template <int SD> __device__ __forceinline__ void wgmma_ss_n192_t1(float (&d)[96], uint64_t da, uint64_t db) {
  if constexpr (SD) {
    asm volatile("{\n.reg .pred p;\nsetp.ne.b32 p, 1, 0;\n"
      "wgmma.mma_async.sync.aligned.m64n192k16.f32.bf16.bf16 {%0, %1, %2, %3, %4, %5, %6, %7, %8, %9, %10, %11, %12, %13, %14, %15, %16, %17, %18, %19, %20, %21, %22, %23, %24, %25, %26, %27, %28, %29, %30, %31, %32, %33, %34, %35, %36, %37, %38, %39, %40, %41, %42, %43, %44, %45, %46, %47, %48, %49, %50, %51, %52, %53, %54, %55, %56, %57, %58, %59, %60, %61, %62, %63, %64, %65, %66, %67, %68, %69, %70, %71, %72, %73, %74, %75, %76, %77, %78, %79, %80, %81, %82, %83, %84, %85, %86, %87, %88, %89, %90, %91, %92, %93, %94, %95}, %96, %97, p, 1, 1, 0, 1;\n}\n"
      : "+f"(d[0]), "+f"(d[1]), "+f"(d[2]), "+f"(d[3]), "+f"(d[4]), "+f"(d[5]), "+f"(d[6]), "+f"(d[7]), "+f"(d[8]), "+f"(d[9]), "+f"(d[10]), "+f"(d[11]), "+f"(d[12]), "+f"(d[13]), "+f"(d[14]), "+f"(d[15]), "+f"(d[16]), "+f"(d[17]), "+f"(d[18]), "+f"(d[19]), "+f"(d[20]), "+f"(d[21]), "+f"(d[22]), "+f"(d[23]), "+f"(d[24]), "+f"(d[25]), "+f"(d[26]), "+f"(d[27]), "+f"(d[28]), "+f"(d[29]), "+f"(d[30]), "+f"(d[31]), "+f"(d[32]), "+f"(d[33]), "+f"(d[34]), "+f"(d[35]), "+f"(d[36]), "+f"(d[37]), "+f"(d[38]), "+f"(d[39]), "+f"(d[40]), "+f"(d[41]), "+f"(d[42]), "+f"(d[43]), "+f"(d[44]), "+f"(d[45]), "+f"(d[46]), "+f"(d[47]), "+f"(d[48]), "+f"(d[49]), "+f"(d[50]), "+f"(d[51]), "+f"(d[52]), "+f"(d[53]), "+f"(d[54]), "+f"(d[55]), "+f"(d[56]), "+f"(d[57]), "+f"(d[58]), "+f"(d[59]), "+f"(d[60]), "+f"(d[61]), "+f"(d[62]), "+f"(d[63]), "+f"(d[64]), "+f"(d[65]), "+f"(d[66]), "+f"(d[67]), "+f"(d[68]), "+f"(d[69]), "+f"(d[70]), "+f"(d[71]), "+f"(d[72]), "+f"(d[73]), "+f"(d[74]), "+f"(d[75]), "+f"(d[76]), "+f"(d[77]), "+f"(d[78]), "+f"(d[79]), "+f"(d[80]), "+f"(d[81]), "+f"(d[82]), "+f"(d[83]), "+f"(d[84]), "+f"(d[85]), "+f"(d[86]), "+f"(d[87]), "+f"(d[88]), "+f"(d[89]), "+f"(d[90]), "+f"(d[91]), "+f"(d[92]), "+f"(d[93]), "+f"(d[94]), "+f"(d[95])
      : "l"(da), "l"(db));
  } else {
    asm volatile("{\n.reg .pred p;\nsetp.ne.b32 p, 0, 0;\n"
      "wgmma.mma_async.sync.aligned.m64n192k16.f32.bf16.bf16 {%0, %1, %2, %3, %4, %5, %6, %7, %8, %9, %10, %11, %12, %13, %14, %15, %16, %17, %18, %19, %20, %21, %22, %23, %24, %25, %26, %27, %28, %29, %30, %31, %32, %33, %34, %35, %36, %37, %38, %39, %40, %41, %42, %43, %44, %45, %46, %47, %48, %49, %50, %51, %52, %53, %54, %55, %56, %57, %58, %59, %60, %61, %62, %63, %64, %65, %66, %67, %68, %69, %70, %71, %72, %73, %74, %75, %76, %77, %78, %79, %80, %81, %82, %83, %84, %85, %86, %87, %88, %89, %90, %91, %92, %93, %94, %95}, %96, %97, p, 1, 1, 0, 1;\n}\n"
      : "=f"(d[0]), "=f"(d[1]), "=f"(d[2]), "=f"(d[3]), "=f"(d[4]), "=f"(d[5]), "=f"(d[6]), "=f"(d[7]), "=f"(d[8]), "=f"(d[9]), "=f"(d[10]), "=f"(d[11]), "=f"(d[12]), "=f"(d[13]), "=f"(d[14]), "=f"(d[15]), "=f"(d[16]), "=f"(d[17]), "=f"(d[18]), "=f"(d[19]), "=f"(d[20]), "=f"(d[21]), "=f"(d[22]), "=f"(d[23]), "=f"(d[24]), "=f"(d[25]), "=f"(d[26]), "=f"(d[27]), "=f"(d[28]), "=f"(d[29]), "=f"(d[30]), "=f"(d[31]), "=f"(d[32]), "=f"(d[33]), "=f"(d[34]), "=f"(d[35]), "=f"(d[36]), "=f"(d[37]), "=f"(d[38]), "=f"(d[39]), "=f"(d[40]), "=f"(d[41]), "=f"(d[42]), "=f"(d[43]), "=f"(d[44]), "=f"(d[45]), "=f"(d[46]), "=f"(d[47]), "=f"(d[48]), "=f"(d[49]), "=f"(d[50]), "=f"(d[51]), "=f"(d[52]), "=f"(d[53]), "=f"(d[54]), "=f"(d[55]), "=f"(d[56]), "=f"(d[57]), "=f"(d[58]), "=f"(d[59]), "=f"(d[60]), "=f"(d[61]), "=f"(d[62]), "=f"(d[63]), "=f"(d[64]), "=f"(d[65]), "=f"(d[66]), "=f"(d[67]), "=f"(d[68]), "=f"(d[69]), "=f"(d[70]), "=f"(d[71]), "=f"(d[72]), "=f"(d[73]), "=f"(d[74]), "=f"(d[75]), "=f"(d[76]), "=f"(d[77]), "=f"(d[78]), "=f"(d[79]), "=f"(d[80]), "=f"(d[81]), "=f"(d[82]), "=f"(d[83]), "=f"(d[84]), "=f"(d[85]), "=f"(d[86]), "=f"(d[87]), "=f"(d[88]), "=f"(d[89]), "=f"(d[90]), "=f"(d[91]), "=f"(d[92]), "=f"(d[93]), "=f"(d[94]), "=f"(d[95])
      : "l"(da), "l"(db));
  }
}
template <int SD> __device__ __forceinline__ void wgmma_ss_n96_t1(float (&d)[48], uint64_t da, uint64_t db) {
  if constexpr (SD) {
    asm volatile("{\n.reg .pred p;\nsetp.ne.b32 p, 1, 0;\n"
      "wgmma.mma_async.sync.aligned.m64n96k16.f32.bf16.bf16 {%0, %1, %2, %3, %4, %5, %6, %7, %8, %9, %10, %11, %12, %13, %14, %15, %16, %17, %18, %19, %20, %21, %22, %23, %24, %25, %26, %27, %28, %29, %30, %31, %32, %33, %34, %35, %36, %37, %38, %39, %40, %41, %42, %43, %44, %45, %46, %47}, %48, %49, p, 1, 1, 0, 1;\n}\n"
      : "+f"(d[0]), "+f"(d[1]), "+f"(d[2]), "+f"(d[3]), "+f"(d[4]), "+f"(d[5]), "+f"(d[6]), "+f"(d[7]), "+f"(d[8]), "+f"(d[9]), "+f"(d[10]), "+f"(d[11]), "+f"(d[12]), "+f"(d[13]), "+f"(d[14]), "+f"(d[15]), "+f"(d[16]), "+f"(d[17]), "+f"(d[18]), "+f"(d[19]), "+f"(d[20]), "+f"(d[21]), "+f"(d[22]), "+f"(d[23]), "+f"(d[24]), "+f"(d[25]), "+f"(d[26]), "+f"(d[27]), "+f"(d[28]), "+f"(d[29]), "+f"(d[30]), "+f"(d[31]), "+f"(d[32]), "+f"(d[33]), "+f"(d[34]), "+f"(d[35]), "+f"(d[36]), "+f"(d[37]), "+f"(d[38]), "+f"(d[39]), "+f"(d[40]), "+f"(d[41]), "+f"(d[42]), "+f"(d[43]), "+f"(d[44]), "+f"(d[45]), "+f"(d[46]), "+f"(d[47])
      : "l"(da), "l"(db));
  } else {
    asm volatile("{\n.reg .pred p;\nsetp.ne.b32 p, 0, 0;\n"
      "wgmma.mma_async.sync.aligned.m64n96k16.f32.bf16.bf16 {%0, %1, %2, %3, %4, %5, %6, %7, %8, %9, %10, %11, %12, %13, %14, %15, %16, %17, %18, %19, %20, %21, %22, %23, %24, %25, %26, %27, %28, %29, %30, %31, %32, %33, %34, %35, %36, %37, %38, %39, %40, %41, %42, %43, %44, %45, %46, %47}, %48, %49, p, 1, 1, 0, 1;\n}\n"
      : "=f"(d[0]), "=f"(d[1]), "=f"(d[2]), "=f"(d[3]), "=f"(d[4]), "=f"(d[5]), "=f"(d[6]), "=f"(d[7]), "=f"(d[8]), "=f"(d[9]), "=f"(d[10]), "=f"(d[11]), "=f"(d[12]), "=f"(d[13]), "=f"(d[14]), "=f"(d[15]), "=f"(d[16]), "=f"(d[17]), "=f"(d[18]), "=f"(d[19]), "=f"(d[20]), "=f"(d[21]), "=f"(d[22]), "=f"(d[23]), "=f"(d[24]), "=f"(d[25]), "=f"(d[26]), "=f"(d[27]), "=f"(d[28]), "=f"(d[29]), "=f"(d[30]), "=f"(d[31]), "=f"(d[32]), "=f"(d[33]), "=f"(d[34]), "=f"(d[35]), "=f"(d[36]), "=f"(d[37]), "=f"(d[38]), "=f"(d[39]), "=f"(d[40]), "=f"(d[41]), "=f"(d[42]), "=f"(d[43]), "=f"(d[44]), "=f"(d[45]), "=f"(d[46]), "=f"(d[47])
      : "l"(da), "l"(db));
  }
}
template <int SD> __device__ __forceinline__ void wgmma_rs_n96_t1(float (&d)[48], uint32_t a0, uint32_t a1, uint32_t a2, uint32_t a3, uint64_t db) {
  if constexpr (SD) {
    asm volatile("{\n.reg .pred p;\nsetp.ne.b32 p, 1, 0;\n"
      "wgmma.mma_async.sync.aligned.m64n96k16.f32.bf16.bf16 {%0, %1, %2, %3, %4, %5, %6, %7, %8, %9, %10, %11, %12, %13, %14, %15, %16, %17, %18, %19, %20, %21, %22, %23, %24, %25, %26, %27, %28, %29, %30, %31, %32, %33, %34, %35, %36, %37, %38, %39, %40, %41, %42, %43, %44, %45, %46, %47}, {%48, %49, %50, %51}, %52, p, 1, 1, 1;\n}\n"
      : "+f"(d[0]), "+f"(d[1]), "+f"(d[2]), "+f"(d[3]), "+f"(d[4]), "+f"(d[5]), "+f"(d[6]), "+f"(d[7]), "+f"(d[8]), "+f"(d[9]), "+f"(d[10]), "+f"(d[11]), "+f"(d[12]), "+f"(d[13]), "+f"(d[14]), "+f"(d[15]), "+f"(d[16]), "+f"(d[17]), "+f"(d[18]), "+f"(d[19]), "+f"(d[20]), "+f"(d[21]), "+f"(d[22]), "+f"(d[23]), "+f"(d[24]), "+f"(d[25]), "+f"(d[26]), "+f"(d[27]), "+f"(d[28]), "+f"(d[29]), "+f"(d[30]), "+f"(d[31]), "+f"(d[32]), "+f"(d[33]), "+f"(d[34]), "+f"(d[35]), "+f"(d[36]), "+f"(d[37]), "+f"(d[38]), "+f"(d[39]), "+f"(d[40]), "+f"(d[41]), "+f"(d[42]), "+f"(d[43]), "+f"(d[44]), "+f"(d[45]), "+f"(d[46]), "+f"(d[47])
      : "r"(a0), "r"(a1), "r"(a2), "r"(a3), "l"(db));
  } else {
    asm volatile("{\n.reg .pred p;\nsetp.ne.b32 p, 0, 0;\n"
      "wgmma.mma_async.sync.aligned.m64n96k16.f32.bf16.bf16 {%0, %1, %2, %3, %4, %5, %6, %7, %8, %9, %10, %11, %12, %13, %14, %15, %16, %17, %18, %19, %20, %21, %22, %23, %24, %25, %26, %27, %28, %29, %30, %31, %32, %33, %34, %35, %36, %37, %38, %39, %40, %41, %42, %43, %44, %45, %46, %47}, {%48, %49, %50, %51}, %52, p, 1, 1, 1;\n}\n"
      : "=f"(d[0]), "=f"(d[1]), "=f"(d[2]), "=f"(d[3]), "=f"(d[4]), "=f"(d[5]), "=f"(d[6]), "=f"(d[7]), "=f"(d[8]), "=f"(d[9]), "=f"(d[10]), "=f"(d[11]), "=f"(d[12]), "=f"(d[13]), "=f"(d[14]), "=f"(d[15]), "=f"(d[16]), "=f"(d[17]), "=f"(d[18]), "=f"(d[19]), "=f"(d[20]), "=f"(d[21]), "=f"(d[22]), "=f"(d[23]), "=f"(d[24]), "=f"(d[25]), "=f"(d[26]), "=f"(d[27]), "=f"(d[28]), "=f"(d[29]), "=f"(d[30]), "=f"(d[31]), "=f"(d[32]), "=f"(d[33]), "=f"(d[34]), "=f"(d[35]), "=f"(d[36]), "=f"(d[37]), "=f"(d[38]), "=f"(d[39]), "=f"(d[40]), "=f"(d[41]), "=f"(d[42]), "=f"(d[43]), "=f"(d[44]), "=f"(d[45]), "=f"(d[46]), "=f"(d[47])
      : "r"(a0), "r"(a1), "r"(a2), "r"(a3), "l"(db));
  }
}
template <int SD> __device__ __forceinline__ void wgmma_rs_n64_t0(float (&d)[32], uint32_t a0, uint32_t a1, uint32_t a2, uint32_t a3, uint64_t db) {
  if constexpr (SD) {
    asm volatile("{\n.reg .pred p;\nsetp.ne.b32 p, 1, 0;\n"
      "wgmma.mma_async.sync.aligned.m64n64k16.f32.bf16.bf16 {%0, %1, %2, %3, %4, %5, %6, %7, %8, %9, %10, %11, %12, %13, %14, %15, %16, %17, %18, %19, %20, %21, %22, %23, %24, %25, %26, %27, %28, %29, %30, %31}, {%32, %33, %34, %35}, %36, p, 1, 1, 0;\n}\n"
      : "+f"(d[0]), "+f"(d[1]), "+f"(d[2]), "+f"(d[3]), "+f"(d[4]), "+f"(d[5]), "+f"(d[6]), "+f"(d[7]), "+f"(d[8]), "+f"(d[9]), "+f"(d[10]), "+f"(d[11]), "+f"(d[12]), "+f"(d[13]), "+f"(d[14]), "+f"(d[15]), "+f"(d[16]), "+f"(d[17]), "+f"(d[18]), "+f"(d[19]), "+f"(d[20]), "+f"(d[21]), "+f"(d[22]), "+f"(d[23]), "+f"(d[24]), "+f"(d[25]), "+f"(d[26]), "+f"(d[27]), "+f"(d[28]), "+f"(d[29]), "+f"(d[30]), "+f"(d[31])
      : "r"(a0), "r"(a1), "r"(a2), "r"(a3), "l"(db));
  } else {
    asm volatile("{\n.reg .pred p;\nsetp.ne.b32 p, 0, 0;\n"
      "wgmma.mma_async.sync.aligned.m64n64k16.f32.bf16.bf16 {%0, %1, %2, %3, %4, %5, %6, %7, %8, %9, %10, %11, %12, %13, %14, %15, %16, %17, %18, %19, %20, %21, %22, %23, %24, %25, %26, %27, %28, %29, %30, %31}, {%32, %33, %34, %35}, %36, p, 1, 1, 0;\n}\n"
      : "=f"(d[0]), "=f"(d[1]), "=f"(d[2]), "=f"(d[3]), "=f"(d[4]), "=f"(d[5]), "=f"(d[6]), "=f"(d[7]), "=f"(d[8]), "=f"(d[9]), "=f"(d[10]), "=f"(d[11]), "=f"(d[12]), "=f"(d[13]), "=f"(d[14]), "=f"(d[15]), "=f"(d[16]), "=f"(d[17]), "=f"(d[18]), "=f"(d[19]), "=f"(d[20]), "=f"(d[21]), "=f"(d[22]), "=f"(d[23]), "=f"(d[24]), "=f"(d[25]), "=f"(d[26]), "=f"(d[27]), "=f"(d[28]), "=f"(d[29]), "=f"(d[30]), "=f"(d[31])
      : "r"(a0), "r"(a1), "r"(a2), "r"(a3), "l"(db));
  }
}
template <int SD> __device__ __forceinline__ void wgmma_rs_n32_t1(float (&d)[16], uint32_t a0, uint32_t a1, uint32_t a2, uint32_t a3, uint64_t db) {
  if constexpr (SD) {
    asm volatile("{\n.reg .pred p;\nsetp.ne.b32 p, 1, 0;\n"
      "wgmma.mma_async.sync.aligned.m64n32k16.f32.bf16.bf16 {%0, %1, %2, %3, %4, %5, %6, %7, %8, %9, %10, %11, %12, %13, %14, %15}, {%16, %17, %18, %19}, %20, p, 1, 1, 1;\n}\n"
      : "+f"(d[0]), "+f"(d[1]), "+f"(d[2]), "+f"(d[3]), "+f"(d[4]), "+f"(d[5]), "+f"(d[6]), "+f"(d[7]), "+f"(d[8]), "+f"(d[9]), "+f"(d[10]), "+f"(d[11]), "+f"(d[12]), "+f"(d[13]), "+f"(d[14]), "+f"(d[15])
      : "r"(a0), "r"(a1), "r"(a2), "r"(a3), "l"(db));
  } else {
    asm volatile("{\n.reg .pred p;\nsetp.ne.b32 p, 0, 0;\n"
      "wgmma.mma_async.sync.aligned.m64n32k16.f32.bf16.bf16 {%0, %1, %2, %3, %4, %5, %6, %7, %8, %9, %10, %11, %12, %13, %14, %15}, {%16, %17, %18, %19}, %20, p, 1, 1, 1;\n}\n"
      : "=f"(d[0]), "=f"(d[1]), "=f"(d[2]), "=f"(d[3]), "=f"(d[4]), "=f"(d[5]), "=f"(d[6]), "=f"(d[7]), "=f"(d[8]), "=f"(d[9]), "=f"(d[10]), "=f"(d[11]), "=f"(d[12]), "=f"(d[13]), "=f"(d[14]), "=f"(d[15])
      : "r"(a0), "r"(a1), "r"(a2), "r"(a3), "l"(db));
  }
}
template <int SD> __device__ __forceinline__ void wgmma_rs_n8_t0(float (&d)[4], uint32_t a0, uint32_t a1, uint32_t a2, uint32_t a3, uint64_t db) {
  if constexpr (SD) {
    asm volatile("{\n.reg .pred p;\nsetp.ne.b32 p, 1, 0;\n"
      "wgmma.mma_async.sync.aligned.m64n8k16.f32.bf16.bf16 {%0, %1, %2, %3}, {%4, %5, %6, %7}, %8, p, 1, 1, 0;\n}\n"
      : "+f"(d[0]), "+f"(d[1]), "+f"(d[2]), "+f"(d[3])
      : "r"(a0), "r"(a1), "r"(a2), "r"(a3), "l"(db));
  } else {
    asm volatile("{\n.reg .pred p;\nsetp.ne.b32 p, 0, 0;\n"
      "wgmma.mma_async.sync.aligned.m64n8k16.f32.bf16.bf16 {%0, %1, %2, %3}, {%4, %5, %6, %7}, %8, p, 1, 1, 0;\n}\n"
      : "=f"(d[0]), "=f"(d[1]), "=f"(d[2]), "=f"(d[3])
      : "r"(a0), "r"(a1), "r"(a2), "r"(a3), "l"(db));
  }
}

__device__ __forceinline__ void wg_fence()  { asm volatile("wgmma.fence.sync.aligned;" ::: "memory"); }
__device__ __forceinline__ void wg_commit() { asm volatile("wgmma.commit_group.sync.aligned;" ::: "memory"); }
template <int N> __device__ __forceinline__ void wg_wait() { asm volatile("wgmma.wait_group.sync.aligned %0;" :: "n"(N) : "memory"); }
template <int N> __device__ __forceinline__ void fence_regs(float (&d)[N]) {
#pragma unroll
  for (int i = 0; i < N; i++) asm volatile("" : "+f"(d[i]) :: "memory");
}
__device__ __forceinline__ constexpr uint64_t mk_desc(uint32_t addr, uint32_t lbo, uint32_t sbo, uint32_t swz) {
  return (uint64_t)(addr >> 4) | ((uint64_t)(lbo >> 4) << 16) | ((uint64_t)(sbo >> 4) << 32) | ((uint64_t)swz << 62);
}
__device__ __forceinline__ uint32_t pack_bf16(float lo, float hi) {
  uint32_t r; asm("cvt.rn.bf16x2.f32 %0, %1, %2;" : "=r"(r) : "f"(hi), "f"(lo)); return r;
}
__device__ __forceinline__ uint32_t hmul2(uint32_t a, uint32_t b) {
  uint32_t r; asm("mul.rn.bf16x2 %0, %1, %2;" : "=r"(r) : "r"(a), "r"(b)); return r;
}
template <int HI> __device__ __forceinline__ uint32_t hmul2_b(uint32_t a, uint32_t b) {
  uint32_t r;
  if (HI) asm("{\n.reg .b16 l, h;\n.reg .b32 t;\nmov.b32 {l, h}, %2;\nmov.b32 t, {h, h};\nmul.rn.bf16x2 %0, %1, t;\n}\n" : "=r"(r) : "r"(a), "r"(b));
  else    asm("{\n.reg .b16 l, h;\n.reg .b32 t;\nmov.b32 {l, h}, %2;\nmov.b32 t, {l, l};\nmul.rn.bf16x2 %0, %1, t;\n}\n" : "=r"(r) : "r"(a), "r"(b));
  return r;
}
__device__ __forceinline__ uint32_t hfma2(uint32_t a, uint32_t b, uint32_t c) {
  uint32_t r; asm("fma.rn.bf16x2 %0, %1, %2, %3;" : "=r"(r) : "r"(a), "r"(b), "r"(c)); return r;
}
__device__ __forceinline__ float ex2(float x) { float r; asm("ex2.approx.ftz.f32 %0, %1;" : "=f"(r) : "f"(x)); return r; }
__device__ __forceinline__ float rsq(float x) { float r; asm("rsqrt.approx.ftz.f32 %0, %1;" : "=f"(r) : "f"(x)); return r; }
__device__ __forceinline__ float rcp(float x) { float r; asm("rcp.approx.ftz.f32 %0, %1;" : "=f"(r) : "f"(x)); return r; }
__device__ __forceinline__ void stsm4(uint32_t addr, uint32_t r0, uint32_t r1, uint32_t r2, uint32_t r3) {
  asm volatile("stmatrix.sync.aligned.m8n8.x4.shared.b16 [%0], {%1,%2,%3,%4};" :: "r"(addr), "r"(r0), "r"(r1), "r"(r2), "r"(r3) : "memory");
}
__device__ __forceinline__ void fence_async() { asm volatile("fence.proxy.async.shared::cta;" ::: "memory"); }
__device__ __forceinline__ void bar_sync_n(int id, int n) { asm volatile("bar.sync %0, %1;" :: "r"(id), "r"(n) : "memory"); }
__device__ __forceinline__ void bar_arrive_n(int id, int n) { asm volatile("bar.arrive %0, %1;" :: "r"(id), "r"(n) : "memory"); }
__device__ __forceinline__ bool bar_wg_or(int id, bool v) {
  uint32_t r;
  asm volatile("{\n.reg .pred p, q;\nsetp.ne.u32 q, %2, 0;\nbar.red.or.pred p, %1, 128, q;\nselp.u32 %0, 0, 1, p;\n}\n"
               : "=r"(r) : "r"(id), "r"((uint32_t)v) : "memory");
  return __ballot_sync(0xffffffffu, r != 0) == 0;
}
__device__ __forceinline__ void mbar_init(uint32_t bar, uint32_t cnt) { asm volatile("mbarrier.init.shared::cta.b64 [%0], %1;" :: "r"(bar), "r"(cnt) : "memory"); }
__device__ __forceinline__ void mbar_expect(uint32_t bar, uint32_t bytes) {
  asm volatile("mbarrier.arrive.expect_tx.shared::cta.b64 _, [%0], %1;" :: "r"(bar), "r"(bytes) : "memory");
}
__device__ __forceinline__ void mbar_arrive(uint32_t bar) { asm volatile("mbarrier.arrive.shared::cta.b64 _, [%0];" :: "r"(bar) : "memory"); }
__device__ __forceinline__ void mbar_wait(uint32_t bar, uint32_t parity) {
  asm volatile("{\n.reg .pred p;\n.reg .u32 n;\nmov.u32 n, 0;\n"
               "LW_%=:\nmbarrier.try_wait.parity.shared::cta.b64 p, [%0], %1;\n@p bra.uni LD_%=;\n"
               "add.u32 n, n, 1;\nsetp.lt.u32 p, n, 4194304;\n@p bra.uni LW_%=;\ntrap;\nLD_%=:\n}\n"
               :: "r"(bar), "r"(parity) : "memory");
}
__device__ __forceinline__ void tma5(uint32_t dst, const CUtensorMap* m, uint32_t bar, int c0, int c1, int c2, int c3, int c4) {
  asm volatile("cp.async.bulk.tensor.5d.shared::cluster.global.mbarrier::complete_tx::bytes [%0], [%1, {%3, %4, %5, %6, %7}], [%2];"
               :: "r"(dst), "l"(m), "r"(bar), "r"(c0), "r"(c1), "r"(c2), "r"(c3), "r"(c4) : "memory");
}
__device__ __forceinline__ void tma3(uint32_t dst, const CUtensorMap* m, uint32_t bar, int c0, int c1, int c2) {
  asm volatile("cp.async.bulk.tensor.3d.shared::cluster.global.mbarrier::complete_tx::bytes [%0], [%1, {%3, %4, %5}], [%2];"
               :: "r"(dst), "l"(m), "r"(bar), "r"(c0), "r"(c1), "r"(c2) : "memory");
}
__device__ __forceinline__ void bulk_g2s(uint32_t dst, const void* src, uint32_t bytes, uint32_t bar) {
  asm volatile("cp.async.bulk.shared::cluster.global.mbarrier::complete_tx::bytes [%0], [%1], %2, [%3];"
               :: "r"(dst), "l"(src), "r"(bytes), "r"(bar) : "memory");
}
__device__ __forceinline__ uint32_t lds32(uint32_t addr) {
  uint32_t v; asm volatile("ld.shared.u32 %0, [%1];" : "=r"(v) : "r"(addr)); return v;
}
__device__ __forceinline__ uint64_t opaque(uint64_t v) { asm volatile("" : "+l"(v)); return v; }
__device__ __forceinline__ uint4 lds128(uint32_t addr) {
  uint4 v; asm volatile("ld.shared.v4.u32 {%0,%1,%2,%3}, [%4];" : "=r"(v.x), "=r"(v.y), "=r"(v.z), "=r"(v.w) : "r"(addr)); return v;
}
__device__ __forceinline__ uint4 ldg128_stream(const void* p) {
  uint4 v; asm volatile("ld.global.nc.L1::no_allocate.v4.u32 {%0,%1,%2,%3}, [%4];" : "=r"(v.x), "=r"(v.y), "=r"(v.z), "=r"(v.w) : "l"(p)); return v;
}
__device__ __forceinline__ void stg128(void* p, uint32_t a, uint32_t b, uint32_t c, uint32_t d) {
  asm volatile("st.global.v4.u32 [%0], {%1,%2,%3,%4};" :: "l"(p), "r"(a), "r"(b), "r"(c), "r"(d) : "memory");
}
__device__ __forceinline__ void prefetch_l2(const void* p, uint32_t bytes) {
  asm volatile("cp.async.bulk.prefetch.L2.global [%0], %1;" :: "l"(p), "r"(bytes) : "memory");
}
__device__ __forceinline__ bool elect_one() {
  uint32_t r; asm volatile("{\n.reg .pred p;\nelect.sync _|p, 0xffffffff;\nselp.u32 %0, 1, 0, p;\n}\n" : "=r"(r)); return r != 0;
}
__device__ __forceinline__ float bf_lo(uint32_t u) { return __uint_as_float(u << 16); }
__device__ __forceinline__ float bf_hi(uint32_t u) { return __uint_as_float(u & 0xFFFF0000u); }
__device__ __forceinline__ float rbf(float x) { return bf_lo(pack_bf16(x, 0.f)); }
__device__ __forceinline__ int orig_tok(int r) { return ((r & 31) >> 2) * 8 + (r >> 5) * 4 + (r & 3); }

__device__ __forceinline__ int slot_window(int s, bool g132) {
  const int A0 = g132 ? 396 + 264 + 60 : 47 * 47, A1 = A0 + 72, B0 = g132 ? 3 * 396 + 264 + 60 : A1, B1 = B0 + 23;
  const int i = s - (s >= B1 ? 95 : s >= A1 ? 72 : 0);
  const int k = s >= B0 ? s - B0 + 72 : s - A0;
  const bool border = (s >= A0 && s < A1) || (s >= B0 && s < B1);
  const int iy = (i * 2789) >> 17;
  return border ? (k < 48 ? (47 << 8 | k) : ((k - 48) << 8 | 47)) : (iy << 8 | (i - iy * 47));
}

#define EB_WORD(e, j, a) ((((a) ^ ((j) & 1)) == 0) ? (e).x : (((a) ^ ((j) & 1)) == 1) ? (e).y : (((a) ^ ((j) & 1)) == 2) ? (e).z : (e).w)

__device__ __forceinline__ void load_eb(uint32_t (&e)[16], uint32_t eb_addr) {
#pragma unroll
  for (int j = 0; j < 4; j++) {
    const uint4 v = lds128(eb_addr + j * 2048);
#pragma unroll
    for (int a = 0; a < 4; a++) e[4 * j + a] = EB_WORD(v, j, a);
  }
}
__device__ __forceinline__ void softmax_fast(const float (&s)[32], uint32_t (&p)[16]) {
#pragma unroll
  for (int i = 0; i < 16; i++) p[i] = hmul2(pack_bf16(ex2(s[2 * i]), ex2(s[2 * i + 1])), p[i]);
}
__device__ __forceinline__ uint32_t hmax2(uint32_t a, uint32_t b) {
  uint32_t r; asm("max.bf16x2 %0, %1, %2;" : "=r"(r) : "r"(a), "r"(b)); return r;
}
__device__ __forceinline__ uint32_t hmax2_nan(uint32_t a, uint32_t b) {
  uint32_t r; asm("max.NaN.bf16x2 %0, %1, %2;" : "=r"(r) : "r"(a), "r"(b)); return r;
}
__device__ __forceinline__ float quad_max(float m) {
  m = fmaxf(m, __shfl_xor_sync(0xffffffffu, m, 1));
  return fmaxf(m, __shfl_xor_sync(0xffffffffu, m, 2));
}
__device__ __forceinline__ void softmax_true_max(const float (&s)[32], uint32_t (&p)[16]) {
  float m0 = s[0], m1 = s[2];
#pragma unroll
  for (int g = 0; g < 8; g++) {
    m0 = fmaxf(m0, fmaxf(s[4 * g + 0], s[4 * g + 1]));
    m1 = fmaxf(m1, fmaxf(s[4 * g + 2], s[4 * g + 3]));
  }
  m0 = quad_max(m0); m1 = quad_max(m1);
  uint32_t n0 = 0, n1 = 0;
#pragma unroll
  for (int g = 0; g < 8; g++) {
    p[2 * g + 0] = hmul2(pack_bf16(ex2(s[4 * g + 0] - m0), ex2(s[4 * g + 1] - m0)), p[2 * g + 0]);
    p[2 * g + 1] = hmul2(pack_bf16(ex2(s[4 * g + 2] - m1), ex2(s[4 * g + 3] - m1)), p[2 * g + 1]);
    n0 = hmax2(n0, p[2 * g]); n1 = hmax2(n1, p[2 * g + 1]);
  }
  const uint32_t r = pack_bf16(rcp(quad_max(fmaxf(bf_lo(n0), bf_hi(n0)))), rcp(quad_max(fmaxf(bf_lo(n1), bf_hi(n1)))));
#pragma unroll
  for (int g = 0; g < 8; g++) { p[2 * g] = hmul2_b<0>(p[2 * g], r); p[2 * g + 1] = hmul2_b<1>(p[2 * g + 1], r); }
}
template <int H> __device__ __forceinline__ void issue_s(float (&s)[32], const uint32_t (&q)[24], uint64_t dK) {
  constexpr int Q0 = (H == 0 ? 0 : H == 1 ? 4 : H == 2 ? 12 : 16), P0 = (H == 0 ? 0 : H == 1 ? 3 : H == 2 ? 7 : 10);
  wgmma_rs_n64_t0<0>(s, q[Q0], q[Q0 + 1], q[Q0 + 2], q[Q0 + 3], dK + P0 * 64);
  wgmma_rs_n64_t0<1>(s, q[Q0 + 4], q[Q0 + 5], q[Q0 + 6], q[Q0 + 7], dK + P0 * 64 + 128);
}
template <int H> __device__ __forceinline__ void issue_pv(float (&o)[16], const uint32_t (&p)[16], uint64_t dV) {
  constexpr int P0 = (H == 0 ? 0 : H == 1 ? 3 : H == 2 ? 7 : 10);
  wgmma_rs_n32_t1<0>(o, p[0], p[1], p[2], p[3], dV + P0 * 64);
  wgmma_rs_n32_t1<1>(o, p[4], p[5], p[6], p[7], dV + P0 * 64 + 16);
  wgmma_rs_n32_t1<1>(o, p[8], p[9], p[10], p[11], dV + P0 * 64 + 32);
  wgmma_rs_n32_t1<1>(o, p[12], p[13], p[14], p[15], dV + P0 * 64 + 48);
}
__device__ __forceinline__ void issue_proj(float (&d)[48], uint64_t dX, uint64_t dW) {
#pragma unroll
  for (int s = 0; s < 6; s++) {
    const uint64_t a = dX + (s >> 1) * 256 + (s & 1) * 2, b = dW + s * 64;
    if (s == 0) wgmma_ss_n96_t1<0>(d, a, b); else wgmma_ss_n96_t1<1>(d, a, b);
  }
}
__device__ __forceinline__ void issue_qk(float (&d)[96], uint64_t dX, uint64_t dW) {
#pragma unroll
  for (int s = 0; s < 6; s++) {
    const uint64_t a = dX + (s >> 1) * 256 + (s & 1) * 2, b = dW + s * 128;
    if (s == 0) wgmma_ss_n192_t1<0>(d, a, b); else wgmma_ss_n192_t1<1>(d, a, b);
  }
}
__device__ __forceinline__ void pack_sumsq(const float* a, uint32_t (&f)[24], uint32_t (&sq)[8], uint32_t init) {
#pragma unroll
  for (int i = 0; i < 24; i++) f[i] = pack_bf16(a[2 * i], a[2 * i + 1]);
#pragma unroll
  for (int h = 0; h < 4; h++)
#pragma unroll
    for (int r = 0; r < 2; r++) {
      uint32_t u = f[6 * h + r], v = f[6 * h + 2 + r], w = f[6 * h + 4 + r];
      sq[2 * h + r] = hfma2(w, w, hfma2(v, v, hfma2(u, u, init)));
    }
}
__device__ __forceinline__ void scale_heads(uint32_t (&f)[24], const float (&r)[8]) {
#pragma unroll
  for (int h = 0; h < 4; h++) {
    const uint32_t p = pack_bf16(r[2 * h], r[2 * h + 1]);
#pragma unroll
    for (int c = 0; c < 3; c++) {
      f[6 * h + 2 * c] = hmul2_b<0>(f[6 * h + 2 * c], p);
      f[6 * h + 2 * c + 1] = hmul2_b<1>(f[6 * h + 2 * c + 1], p);
    }
  }
}
template <int ODD> __device__ __forceinline__ void norm_o(const float (&o)[16], uint32_t* of) {
  constexpr int SO = ODD ? 0 : 12, VO = ODD ? 4 : 0;
  const uint32_t p = pack_bf16(rcp(o[SO]), rcp(o[SO + 2]));
#pragma unroll
  for (int g = 0; g < 3; g++) {
    of[2 * g + 0] = hmul2_b<0>(pack_bf16(o[VO + 4 * g + 0], o[VO + 4 * g + 1]), p);
    of[2 * g + 1] = hmul2_b<1>(pack_bf16(o[VO + 4 * g + 2], o[VO + 4 * g + 3]), p);
  }
}

#define TL(i)
#define TG(i)

constexpr int BAR_KV = 1;
constexpr int BAR_AUX = 4;
constexpr int BAR_TAB = 7, BAR_SETUP = 8;
constexpr int MB_WQK = 0, MB_X = 8, MB_KV = 32, MB_WV = 56, MB_WO = 64, MB_TURN = 72, MB_RDY = 128, MB_WOC = 136;
constexpr uint32_t sb = 1024, mbar = sb + SM_BAR;
constexpr uint32_t EPS8 = 0x2A0D2A0Du;

__device__ __forceinline__ void load_x_interior(const CUtensorMap* tm_x, int w, int g) {
  mbar_expect(mbar + MB_X + 8 * g, 12288);
  tma5(sb + SM_WG + g * WG_SZ + WG_X, tm_x, mbar + MB_X + 8 * g, 0, 0, ((w >> 8) & 255) * 8 + 4, (w & 255) * 2 + 1, 0);
}
__device__ __forceinline__ void load_x(const CUtensorMap* tm_x, const CUtensorMap* tm_xq, int w, int g) {
  const uint32_t dst = sb + SM_WG + g * WG_SZ + WG_X, bar = mbar + MB_X + 8 * g;
  const int wy = (w >> 8) & 255, wx = w & 255;
  mbar_expect(bar, 12288);
  if (wy != NWX - 1 && wx != NWX - 1) {
    tma5(dst, tm_x, bar, 0, 0, wy * 8 + 4, wx * 2 + 1, 0);
  } else {
#pragma unroll 1
    for (int i = 0; i < 12; i++) {
      const int q = i & 3, c = i >> 2;
      int y = wy * 8 + 4 + (q & 1) * 4; if (y >= IMG) y -= IMG;
      int xq = wx * 2 + 1 + (q >> 1);   if (xq >= IMG / 4) xq -= IMG / 4;
      tma5(dst + i * 1024, tm_xq, bar, 0, 0, y, xq, c);
    }
  }
}
__device__ __forceinline__ uint32_t mask_off(int w) { return (uint32_t)(((w >> 8) & 255) * NWX + (w & 255)) * 8192u; }
__device__ __forceinline__ int lds_uniform(uint32_t addr) { return __shfl_sync(0xffffffffu, lds32(addr), 0); }

__device__ __forceinline__ void qkv_epilogue(float (&qk)[96], uint32_t (&qa)[24], uint64_t dX, uint64_t dWv, uint32_t k_dst) {
  uint32_t ka[24], sk[8], sq[8];
  float k01[4], k23[4], q01[4], q23[4], vv[48];
  constexpr uint64_t dSel = mk_desc(sb + SM_SEL, 128, 256, 0);
  wg_wait<0>(); fence_regs(qk);
  pack_sumsq(qk + 48, ka, sk, EPS8);
  pack_sumsq(qk, qa, sq, EPS8);
  wg_fence();
  wgmma_rs_n8_t0<0>(k01, sk[0], sk[1], sk[2], sk[3], dSel);
  wgmma_rs_n8_t0<0>(k23, sk[4], sk[5], sk[6], sk[7], dSel);
  wgmma_rs_n8_t0<0>(q01, sq[0], sq[1], sq[2], sq[3], dSel);
  wgmma_rs_n8_t0<0>(q23, sq[4], sq[5], sq[6], sq[7], dSel);
  wg_commit();
  issue_proj(vv, dX, dWv); wg_commit();
  const uint4 qs = lds128(sb + SM_MISC);
  wg_wait<1>(); fence_regs(k01); fence_regs(k23); fence_regs(q01); fence_regs(q23);
  const float rk[8] = {rsq(k01[0]), rsq(k01[2]), rsq(k01[1]), rsq(k01[3]), rsq(k23[0]), rsq(k23[2]), rsq(k23[1]), rsq(k23[3])};
  scale_heads(ka, rk);
#pragma unroll
  for (int i = 0; i < 6; i++) stsm4(k_dst + (i + (i >= 3)) * 1024, ka[2 * i], ka[2 * i + 1], ka[12 + 2 * i], ka[12 + 2 * i + 1]);
  wg_wait<0>(); fence_regs(vv);
#pragma unroll
  for (int i = 0; i < 6; i++)
    stsm4(k_dst + (WG_V - WG_K) + (i + (i >= 3)) * 1024, pack_bf16(vv[4 * i], vv[4 * i + 1]), pack_bf16(vv[4 * i + 2], vv[4 * i + 3]),
          pack_bf16(vv[24 + 4 * i], vv[24 + 4 * i + 1]), pack_bf16(vv[24 + 4 * i + 2], vv[24 + 4 * i + 3]));
  const float s0 = __uint_as_float(qs.x), s1 = __uint_as_float(qs.y), s2 = __uint_as_float(qs.z), s3 = __uint_as_float(qs.w);
  const float rq[8] = {rsq(q01[0]) * s0, rsq(q01[2]) * s0, rsq(q01[1]) * s1, rsq(q01[3]) * s1,
                       rsq(q23[0]) * s2, rsq(q23[2]) * s2, rsq(q23[1]) * s3, rsq(q23[3]) * s3};
  scale_heads(qa, rq);
  fence_async();
}
__device__ __forceinline__ void issue_out(float (&y)[48], const uint32_t (&of)[24], uint64_t dWo) {
  wg_fence();
#pragma unroll
  for (int s = 0; s < 6; s++) {
    if (s == 0) wgmma_rs_n96_t1<0>(y, of[0], of[1], of[2], of[3], dWo);
    else wgmma_rs_n96_t1<1>(y, of[4 * s], of[4 * s + 1], of[4 * s + 2], of[4 * s + 3], dWo + s * 16);
  }
  wg_commit();
}
__device__ __forceinline__ void ln_head(float (&y)[48], uint32_t (&yb)[24], float (&var)[4], uint64_t dOnes) {
  uint32_t sy[8];
  wg_wait<0>(); fence_regs(y);
  pack_sumsq(y, yb, sy, 0u);
  wg_fence();
  wgmma_rs_n8_t0<0>(var, sy[0], sy[1], sy[2], sy[3], dOnes);
  wgmma_rs_n8_t0<1>(var, sy[4], sy[5], sy[6], sy[7], dOnes);
  wg_commit();
}
__device__ __forceinline__ char* out_ptr(__nv_bfloat16* out, int win, int warp, uint32_t t16) {
  int py = ((win >> 8) & 255) * 8 + 4 + (warp & 1) * 4;  if (py >= IMG) py -= IMG;
  int px = (win & 255) * 8 + 4 + (warp >> 1) * 4;        if (px >= IMG) px -= IMG;
  return reinterpret_cast<char*>(out) + ((uint32_t)(py * IMG + px) * PIXB - warp * 512 + t16 + ((t16 & 0xC0) << 1) + (t16 & 0x100) * 287);
}
__device__ __forceinline__ uint32_t ln_tail(const uint32_t (&yb)[24], float (&var)[4], char* optr) {
  fence_regs(var);
  uint32_t last;
  const uint32_t nn = pack_bf16(rsq(fmaf(var[0], 1.f / 96.f, 1e-5f)), rsq(fmaf(var[2], 1.f / 96.f, 1e-5f)));
#pragma unroll
  for (int j = 0; j < 3; j++) {
    stg128(optr + j * 64, hmul2_b<0>(yb[8 * j], nn), hmul2_b<0>(yb[8 * j + 2], nn), hmul2_b<0>(yb[8 * j + 4], nn), hmul2_b<0>(yb[8 * j + 6], nn));
    last = hmul2_b<1>(yb[8 * j + 7], nn);
    stg128(optr + 2 * ROWB + j * 64, hmul2_b<1>(yb[8 * j + 1], nn), hmul2_b<1>(yb[8 * j + 3], nn), hmul2_b<1>(yb[8 * j + 5], nn), last);
  }
  return last;
}

__device__ __forceinline__ void load_mask_frag(uint32_t (&mk)[16], const char* tile, int warp, int lane) {
  const char* mrow = tile + (orig_tok(16 * warp + (lane >> 2)) * 64 + ((lane >> 1) & 1) * 8 + (lane & 1) * 2) * 2;
#pragma unroll
  for (int Gk = 0; Gk < 8; Gk++) {
    mk[2 * Gk] = __ldg(reinterpret_cast<const uint32_t*>(mrow + (Gk & 3) * 32 + (Gk >> 2) * 8));
    mk[2 * Gk + 1] = __ldg(reinterpret_cast<const uint32_t*>(mrow + 2048 + (Gk & 3) * 32 + (Gk >> 2) * 8));
  }
}
__device__ __forceinline__ bool mask_unsafe(const uint32_t (&mk)[16]) {
  uint32_t x0 = mk[0], x1 = mk[1];
#pragma unroll
  for (int i = 2; i < 16; i += 2) { x0 = hmax2_nan(x0, mk[i]); x1 = hmax2_nan(x1, mk[i + 1]); }
  const bool nan_in = !(bf_lo(x0) == bf_lo(x0) && bf_hi(x0) == bf_hi(x0) && bf_lo(x1) == bf_lo(x1) && bf_hi(x1) == bf_hi(x1));
  const float r0 = quad_max(fmaxf(bf_lo(x0), bf_hi(x0))), r1 = quad_max(fmaxf(bf_lo(x1), bf_hi(x1)));
  return nan_in || !(fabsf(r0) <= 8.f && fabsf(r1) <= 8.f);
}

__device__ __forceinline__ void general_windows(const CUtensorMap* tm_x, const CUtensorMap* tm_xq, const char* mb, __nv_bfloat16* out, uint32_t xph) {
  int tid;
  asm volatile("mov.u32 %0, %%tid.x;" : "=r"(tid));
  const int lane = tid & 31;
  const int warp = __shfl_sync(0xffffffffu, (tid >> 5) & 3, 0), wg = __shfl_sync(0xffffffffu, tid >> 7, 0);
  const uint32_t t16 = (tid & 127) * 16, wgb = sb + SM_WG + wg * WG_SZ, bar_x = mbar + MB_X + 8 * wg;
  const uint32_t k_dst = wgb + WG_K + (lane >> 4) * 7168 + warp * 256 + (lane & 15) * 16;
  const uint32_t slow_heads = lds_uniform(sb + SM_SLOW);
  const uint64_t dX = mk_desc(WG_X, 16, 512, 2) + (wgb >> 4), dK = mk_desc(WG_K, 1024, 128, 0) + (wgb >> 4), dV = mk_desc(WG_V, 128, 1024, 0) + (wgb >> 4);
#pragma unroll 1
  for (uint32_t gl = sb + SM_GEN + wg * NENT * 4;; gl += 4) {
    const int win = lds_uniform(gl);
    if (win < 0) break;
    uint32_t qa[24], of[24], mk[16];
    uint32_t tm;
    {
      load_mask_frag(mk, mb + mask_off(win), warp, lane);
      float qk[96];
      mbar_wait(bar_x, xph); xph ^= 1;
      wg_fence();
      issue_qk(qk, dX, mk_desc(sb + SM_W, 12288, 1024, 1)); wg_commit();
      uint32_t any = 0;
#pragma unroll
      for (int i = 0; i < 16; i += 2) any |= mk[i] | mk[i + 1];
      tm = bar_wg_or(BAR_KV + wg, (any & 0x7FFF7FFFu) != 0) ? 0x1Fu : slow_heads;
      qkv_epilogue(qk, qa, dX, mk_desc(sb + SM_WV, 6144, 512, 2), k_dst);
    }
    bar_sync_n(BAR_AUX + wg, 128);
    if (warp == 0 && elect_one()) {
      const int nxt = lds32(gl + 4);
      if (nxt >= 0) { load_x(tm_x, tm_xq, nxt, wg); prefetch_l2(mb + mask_off(nxt), 8192); }
    }
    __syncwarp();
    auto head = [&](float (&sc)[32], uint32_t (&p)[16], bool tmax) {
      if (tmax) {
        if (tm & 16) {
#pragma unroll
          for (int i = 0; i < 16; i++) {
            sc[2 * i] = fmaf(bf_lo(mk[i]), LOG2E, sc[2 * i]); sc[2 * i + 1] = fmaf(bf_hi(mk[i]), LOG2E, sc[2 * i + 1]);
          }
        }
        softmax_true_max(sc, p);
      } else {
        softmax_fast(sc, p);
      }
    };
#pragma unroll
    for (int i = 0; i < 24; i++) of[i] = 0;
#pragma unroll 1
    for (int hp = 0; hp < 2; hp++) {
      float sA[32], sB[32], oA[16], oB[16]; uint32_t p[16];
      const uint32_t po = hp * 7 * 64;
      wg_fence();
      issue_s<0>(sA, qa, dK + po);
      issue_s<1>(sB, qa, dK + po); wg_commit();
      load_eb(p, sb + SM_EB + t16 + hp * 16384);
      wg_wait<0>(); fence_regs(sA); fence_regs(sB);
#pragma unroll
      for (int i = 0; i < 12; i++) { qa[i] = qa[i + 12]; of[i] = of[i + 12]; }
      head(sA, p, (tm >> (2 * hp)) & 1);
      wg_fence(); issue_pv<0>(oA, p, dV + po); wg_commit();
      uint32_t p2[16];
      load_eb(p2, sb + SM_EB + t16 + hp * 16384 + 8192);
      head(sB, p2, (tm >> (2 * hp + 1)) & 1);
      wg_fence(); issue_pv<1>(oB, p2, dV + po); wg_commit();
      wg_wait<1>(); fence_regs(oA);
      norm_o<0>(oA, of + 12);
      wg_wait<0>(); fence_regs(oB);
      norm_o<1>(oB, of + 18);
    }
    float y[48], var[4]; uint32_t yb[24];
    issue_out(y, of, mk_desc(sb + SM_WO, 128, 1536, 0));
    ln_head(y, yb, var, dV + 3 * 64);
    wg_wait<0>();
    ln_tail(yb, var, out_ptr(out, win, warp, t16));
  }
}

__global__ void __launch_bounds__(384, 1)
swin_kernel(const __grid_constant__ CUtensorMap tm_x, const __grid_constant__ CUtensorMap tm_xq, const __grid_constant__ CUtensorMap tm_wqk,
            const __grid_constant__ CUtensorMap tm_wv,
            const __nv_bfloat16* __restrict__ wo,
            const __nv_bfloat16* __restrict__ logit_scale, const __nv_bfloat16* __restrict__ w1, const __nv_bfloat16* __restrict__ w2,
            const __nv_bfloat16* __restrict__ coords, const int* __restrict__ rel_idx, const __nv_bfloat16* __restrict__ mask,
            __nv_bfloat16* __restrict__ out) {
  extern __shared__ __align__(1024) uint8_t smem[];
  const int tid = threadIdx.x, lane = tid & 31;
  const int warp = __shfl_sync(0xffffffffu, (tid >> 5) & 3, 0), wg = __shfl_sync(0xffffffffu, tid >> 7, 0);
  const uint32_t t16 = (tid & 127) * 16;
  const int G = gridDim.x;
  const uint32_t wgb = sb + SM_WG + wg * WG_SZ;
  const uint32_t bar_x = mbar + MB_X + 8 * wg;
  const char* mb = reinterpret_cast<const char*>(mask);
  TL(0); TG(14);

  const bool g132 = G == 132;
  const uint2 lsw = __ldg(reinterpret_cast<const uint2*>(logit_scale));
  uint32_t cw = 0;
  int4 rid[4];
  if (wg == 0) {
    if (warp == 0) {
      if (elect_one()) {
#pragma unroll
        for (int i = 0; i < 13; i++) mbar_init(mbar + 8 * i, ((i >= 4 && i < 7) || i >= 9) ? 4 : 1);
        mbar_init(mbar + MB_RDY, 8); mbar_init(mbar + MB_WOC, 4);
        fence_async();
        mbar_expect(mbar + MB_WQK, 3 * 12288);
        tma3(sb + SM_W, &tm_wqk, mbar + MB_WQK, 0, 0, 0);
        load_x_interior(&tm_x, slot_window(blockIdx.x, g132), 0);
        mbar_expect(mbar + MB_WV, 3 * 6144);
        tma3(sb + SM_WV, &tm_wv, mbar + MB_WV, 0, 0, 0);
        mbar_expect(mbar + MB_WO, 18432);
        bulk_g2s(sb + SM_WOR, wo, 18432, mbar + MB_WO);
      }
      __syncwarp();
    }
  } else {
    const int i = tid - 128;
    if (i < 12) *reinterpret_cast<uint4*>(smem + SM_PAR + 16 * i) = __ldg(i < 4 ? reinterpret_cast<const uint4*>(w1) + i : reinterpret_cast<const uint4*>(w2) + (i - 4));
    if (i < 225) cw = __ldg(reinterpret_cast<const uint32_t*>(coords) + i);
  }
  if ((uint32_t)__cvta_generic_to_shared(smem) != sb) __trap();
  auto const_tiles = [&]() {
    const int i = tid & 127;
    uint8_t* vt = smem + SM_WG + wg * WG_SZ + WG_V + (i < 64 ? 3 : 10) * 1024 + (i & 63) * 16;
    *reinterpret_cast<uint4*>(vt) = make_uint4(0x3F803F80u, 0x3F803F80u, 0x3F803F80u, 0x3F803F80u);
    *reinterpret_cast<uint4*>(vt - (WG_V - WG_K)) = make_uint4(0u, 0u, 0u, 0u);
  };
  if (wg != 2) const_tiles();
  float tau[4]; uint32_t slow_heads = 0;
  {
    const float ls[4] = {bf_lo(lsw.x), bf_hi(lsw.x), bf_lo(lsw.y), bf_hi(lsw.y)};
#pragma unroll
    for (int h = 0; h < 4; h++) {
      const float c = ls[h] < -100.f ? -100.f : (ls[h] > 4.59375f ? 4.59375f : ls[h]);
      tau[h] = rbf(ex2(c * LOG2E)) * LOG2E;
      if (!(tau[h] <= TAU_FAST_MAX)) slow_heads |= 1u << h;
    }
    slow_heads = __shfl_sync(0xffffffffu, slow_heads, 0);
  }
  if (wg == 0 && warp == 1) {
    const int eg = lane / NENT, ei = lane - eg * NENT, sl = blockIdx.x + eg * G + ei * 3 * G;
    const int w = (sl < NWIN && eg < 3) ? slot_window(sl, g132) : -1;
    const bool fast = w >= 0 && slow_heads == 0 && (w >> 8) != NWX - 1 && (w & 255) != NWX - 1;
    const uint32_t fm = __ballot_sync(0xffffffffu, fast), gm = __ballot_sync(0xffffffffu, w >= 0 && !fast);
    const uint32_t below = ((1u << ei) - 1) << (eg * NENT);
    const int pos = __popc((fast ? fm : gm) & below);
    int ticket = 0;
#pragma unroll
    for (int g = 0; g < 3; g++) ticket += min(__popc((fm >> (g * NENT)) & ((1u << NENT) - 1)), pos + (g < eg));
    if (eg < 3) {
      *reinterpret_cast<int*>(smem + SM_WIN + lane * 4) = -1;
      *reinterpret_cast<int*>(smem + SM_WEM + lane * 4) = -1;
      *reinterpret_cast<int*>(smem + SM_GEN + lane * 4) = -1;
    }
    __syncwarp();
    if (w >= 0) *reinterpret_cast<int*>(smem + (fast ? SM_WIN : slow_heads ? SM_GEN : SM_WEM) + (eg * NENT + pos) * 4) = w | ticket << 16;
  }
  if (wg == 0 && warp == 3 && lane < 16) {
    const uint32_t v = (((lane >> 3) ^ lane) & 1) ? 0u : 0x3F803F80u;
    *reinterpret_cast<uint4*>(smem + SM_SEL + lane * 16) = make_uint4(v, v, v, v);
  }
  TL(3);
  if (wg == 0) {
    if (tid == 0) {
      *reinterpret_cast<float4*>(smem + SM_MISC) = make_float4(tau[0], tau[1], tau[2], tau[3]);
      *reinterpret_cast<uint32_t*>(smem + SM_SLOW) = slow_heads;
    }
    fence_async();
    bar_arrive_n(BAR_SETUP, 384);
    bar_sync_n(BAR_AUX, 128);
  } else {
    const int i = tid - 128;
#pragma unroll
    for (int c = 0; c < 4; c++) {
      const uint4 r = ldg128_stream(reinterpret_cast<const int4*>(rel_idx) + c * 256 + i);
      rid[c] = make_int4(r.x, r.y, r.z, r.w);
    }
    bar_sync_n(BAR_TAB, 256);
    TL(4);
    if (i < 225) {
      const float c0 = bf_lo(cw), c1 = bf_hi(cw);
      float z[4] = {0.f, 0.f, 0.f, 0.f};
#pragma unroll
      for (int jj = 0; jj < 2; jj++) {
        const uint4 ua4 = lds128(sb + SM_PAR + 16 * jj), ub4 = lds128(sb + SM_PAR + 32 + 16 * jj);
        const uint32_t ua[4] = {ua4.x, ua4.y, ua4.z, ua4.w}, ub[4] = {ub4.x, ub4.y, ub4.z, ub4.w};
#pragma unroll
        for (int j = 0; j < 4; j++) {
          const uint4 wb = lds128(sb + SM_PAR + 64 + 64 * jj + 16 * j);
          const uint32_t hp = pack_bf16(fmaf(c1, bf_lo(ub[j]), c0 * bf_lo(ua[j])), fmaf(c1, bf_hi(ub[j]), c0 * bf_hi(ua[j])));
          float h0 = bf_lo(hp), h1 = bf_hi(hp);
          h0 = h0 > 0.f ? h0 : h0 * 0.f; h1 = h1 > 0.f ? h1 : h1 * 0.f;
          z[0] = fmaf(h0, bf_lo(wb.x), z[0]); z[1] = fmaf(h0, bf_hi(wb.x), z[1]); z[2] = fmaf(h0, bf_lo(wb.y), z[2]); z[3] = fmaf(h0, bf_hi(wb.y), z[3]);
          z[0] = fmaf(h1, bf_lo(wb.z), z[0]); z[1] = fmaf(h1, bf_hi(wb.z), z[1]); z[2] = fmaf(h1, bf_lo(wb.w), z[2]); z[3] = fmaf(h1, bf_hi(wb.w), z[3]);
        }
      }
      float e[4];
#pragma unroll
      for (int q = 0; q < 4; q++) {
        const float sh = ((slow_heads >> q) & 1) ? 0.f : fminf(0.f, 25.f - 1.02f * tau[q]);
        e[q] = ex2(fmaf(16.f * LOG2E, rbf(rcp(1.f + ex2(-LOG2E * rbf(z[q])))), sh));
      }
      *reinterpret_cast<uint2*>(smem + SM_TAB + 8 * i) = make_uint2(pack_bf16(e[0], e[1]), pack_bf16(e[2], e[3]));
    }
    TL(5);
    bar_sync_n(BAR_SETUP, 384);
    if (tid == 128 + 127) {
      const int w = slot_window(blockIdx.x + G, g132);
      load_x_interior(&tm_x, w, 1);
      prefetch_l2(mb + mask_off(w), 8192);
    }
    __syncwarp();
#pragma unroll
    for (int c = 0; c < 4; c++) asm volatile("" : "+r"(rid[c].x), "+r"(rid[c].y), "+r"(rid[c].z), "+r"(rid[c].w));
    {
      const int y = (i & 15) >> 1, xh = i & 1, j = 2 * xh + (y >> 2);
      const int X = (i >> 4) & 7, Yl = (i >> 7) & 1;
      uint8_t* dst = smem + SM_EB + j * 2048 + ((X >> 2) * 64 + (Yl * 4 + (X & 3)) * 4 + 2 * (y & 1)) * 16 + ((y >> 1) & 1) * 8;
#pragma unroll
      for (int c = 0; c < 4; c++) {
        const int ia0 = xh ? rid[c].z : rid[c].x, ia1 = xh ? rid[c].w : rid[c].y, ib0 = xh ? rid[c].x : rid[c].z, ib1 = xh ? rid[c].y : rid[c].w;
        const uint2 a0 = *reinterpret_cast<const uint2*>(smem + SM_TAB + 8 * ia0), a1 = *reinterpret_cast<const uint2*>(smem + SM_TAB + 8 * ia1);
        const uint2 b0 = *reinterpret_cast<const uint2*>(smem + SM_TAB + 8 * ib0), b1 = *reinterpret_cast<const uint2*>(smem + SM_TAB + 8 * ib1);
        uint8_t* d0 = dst + (c >> 1) * 512 + (((c & 1) ^ (j & 1)) * 4) + xh * 16;
        uint8_t* d1 = dst + (c >> 1) * 512 + (((c & 1) ^ (j & 1)) * 4) + (xh ^ 1) * 16;
        *reinterpret_cast<uint32_t*>(d0)         = __byte_perm(a0.x, a1.x, 0x5410); *reinterpret_cast<uint32_t*>(d1)         = __byte_perm(b0.x, b1.x, 0x5410);
        *reinterpret_cast<uint32_t*>(d0 + 8192)  = __byte_perm(a0.x, a1.x, 0x7632); *reinterpret_cast<uint32_t*>(d1 + 8192)  = __byte_perm(b0.x, b1.x, 0x7632);
        *reinterpret_cast<uint32_t*>(d0 + 16384) = __byte_perm(a0.y, a1.y, 0x5410); *reinterpret_cast<uint32_t*>(d1 + 16384) = __byte_perm(b0.y, b1.y, 0x5410);
        *reinterpret_cast<uint32_t*>(d0 + 24576) = __byte_perm(a0.y, a1.y, 0x7632); *reinterpret_cast<uint32_t*>(d1 + 24576) = __byte_perm(b0.y, b1.y, 0x7632);
      }
    }
    TL(6);
    if (tid == 256) {
      const int w = slot_window(blockIdx.x + 2 * G, g132);
      load_x_interior(&tm_x, w, 2);
      prefetch_l2(mb + mask_off(w), 8192);
    }
    __syncwarp();
    fence_async();
    if (elect_one()) mbar_arrive(mbar + MB_RDY);
    __syncwarp();
    bar_sync_n(BAR_TAB, 256);
    if (wg == 2) {
      mbar_wait(mbar + MB_WO, 0);
#pragma unroll 1
      for (int r = 0; r < 3; r++) {
        uint4 v[3];
#pragma unroll
        for (int c = 0; c < 3; c++) v[c] = lds128(sb + SM_WOR + (r * 32 + ((tid & 127) >> 2)) * 192 + c * 64 + (lane & 3) * 16);
        float sum = 0.f;
#pragma unroll
        for (int c = 0; c < 3; c++)
          sum += (bf_lo(v[c].x) + bf_hi(v[c].x)) + (bf_lo(v[c].y) + bf_hi(v[c].y)) + (bf_lo(v[c].z) + bf_hi(v[c].z)) + (bf_lo(v[c].w) + bf_hi(v[c].w));
        sum += __shfl_xor_sync(0xffffffffu, sum, 1);
        sum += __shfl_xor_sync(0xffffffffu, sum, 2);
        const float mu = sum * (1.f / 96.f);
        auto cen = [&](uint32_t u) { return pack_bf16(bf_lo(u) - mu, bf_hi(u) - mu); };
        uint8_t* dst = smem + SM_WO + (r * 4 + warp) * 128 + lane * 4;
#pragma unroll
        for (int j = 0; j < 3; j++) {
          *reinterpret_cast<uint32_t*>(dst + (4 * j + 0) * 1536) = cen(v[j].x);
          *reinterpret_cast<uint32_t*>(dst + (4 * j + 1) * 1536) = cen(v[j].y);
          *reinterpret_cast<uint32_t*>(dst + (4 * j + 2) * 1536) = cen(v[j].z);
          *reinterpret_cast<uint32_t*>(dst + (4 * j + 3) * 1536) = cen(v[j].w);
        }
      }
      bar_sync_n(BAR_AUX + 2, 128);
      const_tiles();
      fence_async();
      __syncwarp();
      if (elect_one()) { mbar_arrive(mbar + MB_TURN); mbar_arrive(mbar + MB_WOC); }
      __syncwarp();
    }
  }
  TL(1);
  mbar_wait(mbar + MB_WQK, 0);
  uint32_t xpar = 0, kvpar = 0;
  auto first_x = [&](uint32_t list) {
    if (warp == 0 && elect_one()) {
      int w = lds32(list);
      if (w < 0) w = lds32(sb + SM_GEN + wg * NENT * 4);
      if (w >= 0) { load_x(&tm_x, &tm_xq, w, wg); prefetch_l2(mb + mask_off(w), 8192); }
    }
    __syncwarp();
  };
  auto push = [&](uint32_t list, int w) {
    if (t16 == 0) {
      while ((int)lds32(list) >= 0) list += 4;
      asm volatile("st.shared.u32 [%0], %1;" :: "r"(list), "r"(w) : "memory");
    }
    __syncwarp();
  };

  auto run = [&](auto em) {
    constexpr bool EM = decltype(em)::value;
    uint32_t wl = sb + (EM ? SM_WEM : SM_WIN) + wg * NENT * 4;
    int win = lds_uniform(wl), nxt = lds_uniform(wl + 4);
    if (win < 0) return;
    uint32_t tt;
    asm volatile("mov.u32 %0, %%tid.x;" : "=r"(tt));
    const uint32_t t16 = (tt & 127) * 16;
    const uint32_t k_dst = wgb + WG_K + (tt & 16) * 448 + warp * 256 + (tt & 15) * 16;
    const uint32_t eb_base = sb + SM_EB + t16;
    const uint32_t next_list = sb + (EM ? SM_GEN : SM_WEM) + wg * NENT * 4;
    const uint32_t xb = xpar, kb = kvpar;
    uint4 mw[4];
    auto load_mask = [&](uint32_t off) {
      const char* src = mb + (off + t16);
#pragma unroll
      for (int i = 0; i < 4; i++) mw[i] = ldg128_stream(src + i * 2048);
    };
    auto mask_or = [&](uint32_t seed) {
      uint32_t r = seed & 0x80008000u;
#pragma unroll
      for (int i = 0; i < 4; i++) {
        asm("lop3.b32 %0, %0, %1, %2, 0xFE;" : "+r"(r) : "r"(mw[i].x), "r"(mw[i].y));
        asm("lop3.b32 %0, %0, %1, %2, 0xFE;" : "+r"(r) : "r"(mw[i].z), "r"(mw[i].w));
      }
      return r;
    };
    float qk[96];
    uint32_t mword = 0;
    if (!EM) load_mask(mask_off(win));
    mbar_wait(bar_x, xb);
    TL(2);
    wg_fence();
    issue_qk(qk, mk_desc(WG_X, 16, 512, 2) + (wgb >> 4), mk_desc(sb + SM_W, 12288, 1024, 1)); wg_commit();
    if (!EM) {
      if (warp == 0 && nxt >= 0 && elect_one()) prefetch_l2(mb + mask_off(nxt), 8192);
      __syncwarp();
      mword = mask_or(0);
      TL(7);
      mbar_wait(mbar + MB_WV, 0);
      mbar_wait(mbar + MB_RDY, 0);
      TL(8);
    }
    while (true) {
      const int nxt2 = lds_uniform(wl + 8), tk = win >> 16;
      const bool more = nxt >= 0;
      const uint32_t z0 = wl >> 20, zw = z0 + (wgb >> 4);
      const uint64_t dX = opaque(mk_desc(WG_X, 16, 512, 2) + zw);
      TL(0);
      uint32_t qa[24];
      qkv_epilogue(qk, qa, dX, opaque(mk_desc(sb + SM_WV, 6144, 512, 2) + z0), k_dst);
      TL(5);
      uint32_t mk[16];
      if (EM) load_mask_frag(mk, mb + mask_off(win), warp, tt & 31);
      const bool defer = bar_wg_or(BAR_KV + wg, EM ? mask_unsafe(mk) : (mword & 0x7FFF7FFFu) != 0u);
      TL(6);
      const uint64_t dK = opaque(mk_desc(WG_K, 1024, 128, 0) + zw), dV = opaque(mk_desc(WG_V, 128, 1024, 0) + zw);
      auto prefetch_next = [&]() {
        if (warp == 0 && more) {
          if (elect_one()) {
            if (EM) load_x(&tm_x, &tm_xq, nxt, wg); else load_x_interior(&tm_x, nxt, wg);
            if (EM) prefetch_l2(mb + mask_off(nxt), 8192); else if (nxt2 >= 0) prefetch_l2(mb + mask_off(nxt2), 8192);
          }
          __syncwarp();
        }
      };
      auto wait_turn = [&]() { if (!EM) mbar_wait(mbar + MB_TURN + (tk & 3) * 8, (tk >> 2) & 1); };
      auto pass_turn = [&]() { if (!EM) { if (elect_one()) mbar_arrive(mbar + MB_TURN + ((tk + 1) & 3) * 8); __syncwarp(); } };
      auto next_qk = [&]() { issue_qk(qk, dX, opaque(mk_desc(sb + SM_W, 12288, 1024, 1) + z0)); wg_commit(); };
      auto tiles_ready = [&]() {
        if (elect_one()) mbar_arrive(bar_x + (MB_KV - MB_X));
        __syncwarp();
        const uint32_t par = (wl >> 2) & 1;
        mbar_wait(bar_x, par ^ 1 ^ xb);
        mbar_wait(bar_x + (MB_KV - MB_X), par ^ kb);
      };
      if (__builtin_expect(defer, 0)) {
        push(next_list, win);
        wait_turn(); pass_turn();
        if (!more) { first_x(next_list); break; }
        prefetch_next();
        if (!EM) load_mask(mask_off(nxt));
        tiles_ready();
        wg_fence();
        next_qk();
        if (!EM) mword = mask_or(0);
        wl += 4;
        win = nxt; nxt = nxt2;
        continue;
      }
      uint32_t of[24];
      {
        auto table = [&](uint32_t (&p)[16], int h) {
          load_eb(p, eb_base + h * 8192);
          if (EM) {
#pragma unroll
            for (int j = 0; j < 4; j++) {
              const uint4 m = lds128(wgb + WG_X + t16 + j * 2048);
              p[4 * j] = hmul2(p[4 * j], m.x); p[4 * j + 1] = hmul2(p[4 * j + 1], m.y);
              p[4 * j + 2] = hmul2(p[4 * j + 2], m.z); p[4 * j + 3] = hmul2(p[4 * j + 3], m.w);
            }
          }
        };
        float sA[32], sB[32], oA[16], oB[16], oC[16], oD[16];
        uint32_t pA[16], pB[16], pC[16], pD[16];
        wg_fence();
        issue_s<0>(sA, qa, dK);
        issue_s<1>(sB, qa, dK); wg_commit();
        if (EM) {
#pragma unroll
          for (int i = 0; i < 16; i++) mk[i] = pack_bf16(ex2(bf_lo(mk[i]) * LOG2E), ex2(bf_hi(mk[i]) * LOG2E));
#pragma unroll
          for (int j = 0; j < 4; j++)
            asm volatile("st.shared.v4.u32 [%0], {%1,%2,%3,%4};" :: "r"(wgb + WG_X + t16 + j * 2048), "r"(mk[4 * j]), "r"(mk[4 * j + 1]), "r"(mk[4 * j + 2]), "r"(mk[4 * j + 3]) : "memory");
        }
        table(pA, 0);
        if (!EM) prefetch_next();
        wait_turn();
        wg_wait<0>(); fence_regs(sA); fence_regs(sB);
        TL(7);
        table(pB, 1);
        softmax_fast(sA, pA);
        wg_fence();
        issue_s<2>(sA, qa, dK); wg_commit();
        issue_pv<0>(oA, pA, dV); wg_commit();
        TL(8);
        softmax_fast(sB, pB);
        table(pC, 2);
        wg_wait<1>(); fence_regs(sA);
        wg_fence();
        issue_s<3>(sB, qa, dK); wg_commit();
        issue_pv<1>(oB, pB, dV); wg_commit();
        TL(9);
        softmax_fast(sA, pC);
        pass_turn();
        table(pD, 3);
        if (EM) { fence_async(); bar_sync_n(BAR_AUX + wg, 128); prefetch_next(); }
        wg_wait<1>(); fence_regs(sB); fence_regs(oA);
        wg_fence();
        issue_pv<2>(oC, pC, dV); wg_commit();
        TL(10);
        norm_o<0>(oA, of);
        softmax_fast(sB, pD);
        wg_fence();
        issue_pv<3>(oD, pD, dV); wg_commit();
        if (!EM) {
          if (more) load_mask(mask_off(nxt));
          else { mw[0] = mw[1] = mw[2] = mw[3] = make_uint4(0, 0, 0, 0); }
        }
        wg_wait<1>(); fence_regs(oB); fence_regs(oC);
        norm_o<1>(oB, of + 6);
        norm_o<0>(oC, of + 12);
        wg_wait<0>(); fence_regs(oD);
        norm_o<1>(oD, of + 18);
      }
      TL(11);
      float y[48], var[4]; uint32_t yb[24];
      issue_out(y, of, opaque(mk_desc(sb + SM_WO, 128, 1536, 0) + z0));
      char* const optr = out_ptr(out, win, warp, t16);
      if (!more) { first_x(next_list); ln_head(y, yb, var, dV + 3 * 64); wg_wait<0>(); ln_tail(yb, var, optr); TL(14); break; }
      tiles_ready();
      ln_head(y, yb, var, dV + 3 * 64);
      TL(12);
      next_qk();
      wg_wait<1>();
      TL(13);
      const uint32_t last = ln_tail(yb, var, optr);
      if (!EM) mword = mask_or(last);
      TL(14);
      wl += 4;
      win = nxt; nxt = nxt2;
    }
    xpar = xb ^ ((wl >> 2) & 1) ^ 1;
    kvpar = kb ^ ((wl >> 2) & 1);
    bar_sync_n(BAR_AUX + wg, 128);
  };
  run(std::false_type{});
  run(std::true_type{});
  if (lds_uniform(sb + SM_GEN + wg * NENT * 4) >= 0) {
    mbar_wait(mbar + MB_WV, 0);
    mbar_wait(mbar + MB_RDY, 0);
    mbar_wait(mbar + MB_WOC, 0);
    general_windows(&tm_x, &tm_xq, mb, out, xpar);
  }
  TG(15);
}

typedef CUresult (*EncodeFn)(CUtensorMap*, CUtensorMapDataType, cuuint32_t, void*, const cuuint64_t*, const cuuint64_t*,
                             const cuuint32_t*, const cuuint32_t*, CUtensorMapInterleave, CUtensorMapSwizzle,
                             CUtensorMapL2promotion, CUtensorMapFloatOOBfill);

}

extern "C" void kernel_launch(void* const* d_in, const int* in_sizes, int n_in, void* d_out, int out_size) {
  static int sms = 0;
  static EncodeFn encode = nullptr;
  if (sms == 0) {
    int dev = 0;
    cudaGetDevice(&dev);
    cudaDeviceGetAttribute(&sms, cudaDevAttrMultiProcessorCount, dev);
    if (sms < 96) sms = 96;
    cudaFuncSetAttribute(swin_kernel, cudaFuncAttributeMaxDynamicSharedMemorySize, SM_TOTAL);
    cudaDriverEntryPointQueryResult qr;
    void* fn = nullptr;
    cudaGetDriverEntryPoint("cuTensorMapEncodeTiled", &fn, cudaEnableDefault, &qr);
    encode = (EncodeFn)fn;
  }
  CUtensorMap tm_x, tm_xq, tm_wqk, tm_wv;
  {
    cuuint64_t dims[5] = {32, 4, IMG, IMG / 4, 3};
    cuuint64_t strides[4] = {PIXB, ROWB, 4 * PIXB, 64};
    cuuint32_t es[5] = {1, 1, 1, 1, 1};
    cuuint32_t box[5] = {32, 4, 8, 2, 3}, boxq[5] = {32, 4, 4, 1, 1};
    encode(&tm_x, CU_TENSOR_MAP_DATA_TYPE_BFLOAT16, 5, d_in[0], dims, strides, box, es, CU_TENSOR_MAP_INTERLEAVE_NONE,
           CU_TENSOR_MAP_SWIZZLE_64B, CU_TENSOR_MAP_L2_PROMOTION_L2_128B, CU_TENSOR_MAP_FLOAT_OOB_FILL_NONE);
    encode(&tm_xq, CU_TENSOR_MAP_DATA_TYPE_BFLOAT16, 5, d_in[0], dims, strides, boxq, es, CU_TENSOR_MAP_INTERLEAVE_NONE,
           CU_TENSOR_MAP_SWIZZLE_64B, CU_TENSOR_MAP_L2_PROMOTION_L2_128B, CU_TENSOR_MAP_FLOAT_OOB_FILL_NONE);
    cuuint64_t qd[3] = {64, 96, 3}, qs[2] = {576, 128}, vd[3] = {32, 96, 3}, vs[2] = {576, 64};
    cuuint32_t qb[3] = {64, 96, 3}, vb[3] = {32, 96, 3};
    encode(&tm_wqk, CU_TENSOR_MAP_DATA_TYPE_BFLOAT16, 3, d_in[1], qd, qs, qb, es, CU_TENSOR_MAP_INTERLEAVE_NONE,
           CU_TENSOR_MAP_SWIZZLE_128B, CU_TENSOR_MAP_L2_PROMOTION_L2_256B, CU_TENSOR_MAP_FLOAT_OOB_FILL_NONE);
    encode(&tm_wv, CU_TENSOR_MAP_DATA_TYPE_BFLOAT16, 3, (char*)d_in[1] + 384, vd, vs, vb, es, CU_TENSOR_MAP_INTERLEAVE_NONE,
           CU_TENSOR_MAP_SWIZZLE_64B, CU_TENSOR_MAP_L2_PROMOTION_L2_256B, CU_TENSOR_MAP_FLOAT_OOB_FILL_NONE);
  }
  swin_kernel<<<sms, 384, SM_TOTAL>>>(
      tm_x, tm_xq, tm_wqk, tm_wv, (const __nv_bfloat16*)d_in[2], (const __nv_bfloat16*)d_in[3],
      (const __nv_bfloat16*)d_in[4], (const __nv_bfloat16*)d_in[5], (const __nv_bfloat16*)d_in[6], (const int*)d_in[7],
      (const __nv_bfloat16*)d_in[8], (__nv_bfloat16*)d_out);
}
```

```cpp
#include <cuda_runtime.h>
#include <cuda.h>
#include <cuda_bf16.h>
#include <stdint.h>
#include <type_traits>

#define TOKEN 3
namespace {

constexpr int IMG   = 384;
constexpr int NWX   = 48;
constexpr int NWIN  = NWX * NWX;
constexpr int PIXB  = 192;
constexpr int ROWB  = IMG * PIXB;
constexpr float LOG2E = 1.4426950408889634f;
constexpr float TAU_FAST_MAX = 50.f;

constexpr int SM_W    = 0;
constexpr int SM_WV   = 3 * 12288;
constexpr int SM_WO   = SM_W + 9 * 6144;
constexpr int SM_EB   = SM_WO + 12 * 1536;
constexpr int SM_WG   = SM_EB + 32768;
constexpr int WG_X    = 0;
constexpr int WG_K    = 12288;
constexpr int WG_V    = WG_K + 14336;
constexpr int WG_SZ   = WG_V + 14336;
constexpr int SM_TAB  = SM_WG + WG_SZ + WG_V + 4096;
constexpr int SM_WOR  = SM_WG + 2 * WG_SZ + WG_K;
constexpr int SM_SEL  = SM_WG + 3 * WG_SZ;
constexpr int SM_MISC = SM_SEL + 256;
constexpr int SM_BAR  = SM_MISC + 16;
constexpr int SM_SLOW = SM_BAR + 104;
constexpr int SM_PAR  = SM_BAR + 160;
constexpr int NENT    = 10;
constexpr int SM_WIN  = SM_PAR + 192;
constexpr int SM_GEN  = SM_WIN + 3 * NENT * 4;
constexpr int SM_TOTAL = SM_GEN + 3 * NENT * 4;
static_assert((SM_WIN & 7) == 0 && (NENT & 1) == 0, "list parity");

template <int SD> __device__ __forceinline__ void wgmma_ss_n192_t1(float (&d)[96], uint64_t da, uint64_t db) {
  if constexpr (SD) {
    asm volatile("{\n.reg .pred p;\nsetp.ne.b32 p, 1, 0;\n"
      "wgmma.mma_async.sync.aligned.m64n192k16.f32.bf16.bf16 {%0, %1, %2, %3, %4, %5, %6, %7, %8, %9, %10, %11, %12, %13, %14, %15, %16, %17, %18, %19, %20, %21, %22, %23, %24, %25, %26, %27, %28, %29, %30, %31, %32, %33, %34, %35, %36, %37, %38, %39, %40, %41, %42, %43, %44, %45, %46, %47, %48, %49, %50, %51, %52, %53, %54, %55, %56, %57, %58, %59, %60, %61, %62, %63, %64, %65, %66, %67, %68, %69, %70, %71, %72, %73, %74, %75, %76, %77, %78, %79, %80, %81, %82, %83, %84, %85, %86, %87, %88, %89, %90, %91, %92, %93, %94, %95}, %96, %97, p, 1, 1, 0, 1;\n}\n"
      : "+f"(d[0]), "+f"(d[1]), "+f"(d[2]), "+f"(d[3]), "+f"(d[4]), "+f"(d[5]), "+f"(d[6]), "+f"(d[7]), "+f"(d[8]), "+f"(d[9]), "+f"(d[10]), "+f"(d[11]), "+f"(d[12]), "+f"(d[13]), "+f"(d[14]), "+f"(d[15]), "+f"(d[16]), "+f"(d[17]), "+f"(d[18]), "+f"(d[19]), "+f"(d[20]), "+f"(d[21]), "+f"(d[22]), "+f"(d[23]), "+f"(d[24]), "+f"(d[25]), "+f"(d[26]), "+f"(d[27]), "+f"(d[28]), "+f"(d[29]), "+f"(d[30]), "+f"(d[31]), "+f"(d[32]), "+f"(d[33]), "+f"(d[34]), "+f"(d[35]), "+f"(d[36]), "+f"(d[37]), "+f"(d[38]), "+f"(d[39]), "+f"(d[40]), "+f"(d[41]), "+f"(d[42]), "+f"(d[43]), "+f"(d[44]), "+f"(d[45]), "+f"(d[46]), "+f"(d[47]), "+f"(d[48]), "+f"(d[49]), "+f"(d[50]), "+f"(d[51]), "+f"(d[52]), "+f"(d[53]), "+f"(d[54]), "+f"(d[55]), "+f"(d[56]), "+f"(d[57]), "+f"(d[58]), "+f"(d[59]), "+f"(d[60]), "+f"(d[61]), "+f"(d[62]), "+f"(d[63]), "+f"(d[64]), "+f"(d[65]), "+f"(d[66]), "+f"(d[67]), "+f"(d[68]), "+f"(d[69]), "+f"(d[70]), "+f"(d[71]), "+f"(d[72]), "+f"(d[73]), "+f"(d[74]), "+f"(d[75]), "+f"(d[76]), "+f"(d[77]), "+f"(d[78]), "+f"(d[79]), "+f"(d[80]), "+f"(d[81]), "+f"(d[82]), "+f"(d[83]), "+f"(d[84]), "+f"(d[85]), "+f"(d[86]), "+f"(d[87]), "+f"(d[88]), "+f"(d[89]), "+f"(d[90]), "+f"(d[91]), "+f"(d[92]), "+f"(d[93]), "+f"(d[94]), "+f"(d[95])
      : "l"(da), "l"(db));
  } else {
    asm volatile("{\n.reg .pred p;\nsetp.ne.b32 p, 0, 0;\n"
      "wgmma.mma_async.sync.aligned.m64n192k16.f32.bf16.bf16 {%0, %1, %2, %3, %4, %5, %6, %7, %8, %9, %10, %11, %12, %13, %14, %15, %16, %17, %18, %19, %20, %21, %22, %23, %24, %25, %26, %27, %28, %29, %30, %31, %32, %33, %34, %35, %36, %37, %38, %39, %40, %41, %42, %43, %44, %45, %46, %47, %48, %49, %50, %51, %52, %53, %54, %55, %56, %57, %58, %59, %60, %61, %62, %63, %64, %65, %66, %67, %68, %69, %70, %71, %72, %73, %74, %75, %76, %77, %78, %79, %80, %81, %82, %83, %84, %85, %86, %87, %88, %89, %90, %91, %92, %93, %94, %95}, %96, %97, p, 1, 1, 0, 1;\n}\n"
      : "=f"(d[0]), "=f"(d[1]), "=f"(d[2]), "=f"(d[3]), "=f"(d[4]), "=f"(d[5]), "=f"(d[6]), "=f"(d[7]), "=f"(d[8]), "=f"(d[9]), "=f"(d[10]), "=f"(d[11]), "=f"(d[12]), "=f"(d[13]), "=f"(d[14]), "=f"(d[15]), "=f"(d[16]), "=f"(d[17]), "=f"(d[18]), "=f"(d[19]), "=f"(d[20]), "=f"(d[21]), "=f"(d[22]), "=f"(d[23]), "=f"(d[24]), "=f"(d[25]), "=f"(d[26]), "=f"(d[27]), "=f"(d[28]), "=f"(d[29]), "=f"(d[30]), "=f"(d[31]), "=f"(d[32]), "=f"(d[33]), "=f"(d[34]), "=f"(d[35]), "=f"(d[36]), "=f"(d[37]), "=f"(d[38]), "=f"(d[39]), "=f"(d[40]), "=f"(d[41]), "=f"(d[42]), "=f"(d[43]), "=f"(d[44]), "=f"(d[45]), "=f"(d[46]), "=f"(d[47]), "=f"(d[48]), "=f"(d[49]), "=f"(d[50]), "=f"(d[51]), "=f"(d[52]), "=f"(d[53]), "=f"(d[54]), "=f"(d[55]), "=f"(d[56]), "=f"(d[57]), "=f"(d[58]), "=f"(d[59]), "=f"(d[60]), "=f"(d[61]), "=f"(d[62]), "=f"(d[63]), "=f"(d[64]), "=f"(d[65]), "=f"(d[66]), "=f"(d[67]), "=f"(d[68]), "=f"(d[69]), "=f"(d[70]), "=f"(d[71]), "=f"(d[72]), "=f"(d[73]), "=f"(d[74]), "=f"(d[75]), "=f"(d[76]), "=f"(d[77]), "=f"(d[78]), "=f"(d[79]), "=f"(d[80]), "=f"(d[81]), "=f"(d[82]), "=f"(d[83]), "=f"(d[84]), "=f"(d[85]), "=f"(d[86]), "=f"(d[87]), "=f"(d[88]), "=f"(d[89]), "=f"(d[90]), "=f"(d[91]), "=f"(d[92]), "=f"(d[93]), "=f"(d[94]), "=f"(d[95])
      : "l"(da), "l"(db));
  }
}
template <int SD> __device__ __forceinline__ void wgmma_ss_n96_t1(float (&d)[48], uint64_t da, uint64_t db) {
  if constexpr (SD) {
    asm volatile("{\n.reg .pred p;\nsetp.ne.b32 p, 1, 0;\n"
      "wgmma.mma_async.sync.aligned.m64n96k16.f32.bf16.bf16 {%0, %1, %2, %3, %4, %5, %6, %7, %8, %9, %10, %11, %12, %13, %14, %15, %16, %17, %18, %19, %20, %21, %22, %23, %24, %25, %26, %27, %28, %29, %30, %31, %32, %33, %34, %35, %36, %37, %38, %39, %40, %41, %42, %43, %44, %45, %46, %47}, %48, %49, p, 1, 1, 0, 1;\n}\n"
      : "+f"(d[0]), "+f"(d[1]), "+f"(d[2]), "+f"(d[3]), "+f"(d[4]), "+f"(d[5]), "+f"(d[6]), "+f"(d[7]), "+f"(d[8]), "+f"(d[9]), "+f"(d[10]), "+f"(d[11]), "+f"(d[12]), "+f"(d[13]), "+f"(d[14]), "+f"(d[15]), "+f"(d[16]), "+f"(d[17]), "+f"(d[18]), "+f"(d[19]), "+f"(d[20]), "+f"(d[21]), "+f"(d[22]), "+f"(d[23]), "+f"(d[24]), "+f"(d[25]), "+f"(d[26]), "+f"(d[27]), "+f"(d[28]), "+f"(d[29]), "+f"(d[30]), "+f"(d[31]), "+f"(d[32]), "+f"(d[33]), "+f"(d[34]), "+f"(d[35]), "+f"(d[36]), "+f"(d[37]), "+f"(d[38]), "+f"(d[39]), "+f"(d[40]), "+f"(d[41]), "+f"(d[42]), "+f"(d[43]), "+f"(d[44]), "+f"(d[45]), "+f"(d[46]), "+f"(d[47])
      : "l"(da), "l"(db));
  } else {
    asm volatile("{\n.reg .pred p;\nsetp.ne.b32 p, 0, 0;\n"
      "wgmma.mma_async.sync.aligned.m64n96k16.f32.bf16.bf16 {%0, %1, %2, %3, %4, %5, %6, %7, %8, %9, %10, %11, %12, %13, %14, %15, %16, %17, %18, %19, %20, %21, %22, %23, %24, %25, %26, %27, %28, %29, %30, %31, %32, %33, %34, %35, %36, %37, %38, %39, %40, %41, %42, %43, %44, %45, %46, %47}, %48, %49, p, 1, 1, 0, 1;\n}\n"
      : "=f"(d[0]), "=f"(d[1]), "=f"(d[2]), "=f"(d[3]), "=f"(d[4]), "=f"(d[5]), "=f"(d[6]), "=f"(d[7]), "=f"(d[8]), "=f"(d[9]), "=f"(d[10]), "=f"(d[11]), "=f"(d[12]), "=f"(d[13]), "=f"(d[14]), "=f"(d[15]), "=f"(d[16]), "=f"(d[17]), "=f"(d[18]), "=f"(d[19]), "=f"(d[20]), "=f"(d[21]), "=f"(d[22]), "=f"(d[23]), "=f"(d[24]), "=f"(d[25]), "=f"(d[26]), "=f"(d[27]), "=f"(d[28]), "=f"(d[29]), "=f"(d[30]), "=f"(d[31]), "=f"(d[32]), "=f"(d[33]), "=f"(d[34]), "=f"(d[35]), "=f"(d[36]), "=f"(d[37]), "=f"(d[38]), "=f"(d[39]), "=f"(d[40]), "=f"(d[41]), "=f"(d[42]), "=f"(d[43]), "=f"(d[44]), "=f"(d[45]), "=f"(d[46]), "=f"(d[47])
      : "l"(da), "l"(db));
  }
}
template <int SD> __device__ __forceinline__ void wgmma_rs_n96_t1(float (&d)[48], uint32_t a0, uint32_t a1, uint32_t a2, uint32_t a3, uint64_t db) {
  if constexpr (SD) {
    asm volatile("{\n.reg .pred p;\nsetp.ne.b32 p, 1, 0;\n"
      "wgmma.mma_async.sync.aligned.m64n96k16.f32.bf16.bf16 {%0, %1, %2, %3, %4, %5, %6, %7, %8, %9, %10, %11, %12, %13, %14, %15, %16, %17, %18, %19, %20, %21, %22, %23, %24, %25, %26, %27, %28, %29, %30, %31, %32, %33, %34, %35, %36, %37, %38, %39, %40, %41, %42, %43, %44, %45, %46, %47}, {%48, %49, %50, %51}, %52, p, 1, 1, 1;\n}\n"
      : "+f"(d[0]), "+f"(d[1]), "+f"(d[2]), "+f"(d[3]), "+f"(d[4]), "+f"(d[5]), "+f"(d[6]), "+f"(d[7]), "+f"(d[8]), "+f"(d[9]), "+f"(d[10]), "+f"(d[11]), "+f"(d[12]), "+f"(d[13]), "+f"(d[14]), "+f"(d[15]), "+f"(d[16]), "+f"(d[17]), "+f"(d[18]), "+f"(d[19]), "+f"(d[20]), "+f"(d[21]), "+f"(d[22]), "+f"(d[23]), "+f"(d[24]), "+f"(d[25]), "+f"(d[26]), "+f"(d[27]), "+f"(d[28]), "+f"(d[29]), "+f"(d[30]), "+f"(d[31]), "+f"(d[32]), "+f"(d[33]), "+f"(d[34]), "+f"(d[35]), "+f"(d[36]), "+f"(d[37]), "+f"(d[38]), "+f"(d[39]), "+f"(d[40]), "+f"(d[41]), "+f"(d[42]), "+f"(d[43]), "+f"(d[44]), "+f"(d[45]), "+f"(d[46]), "+f"(d[47])
      : "r"(a0), "r"(a1), "r"(a2), "r"(a3), "l"(db));
  } else {
    asm volatile("{\n.reg .pred p;\nsetp.ne.b32 p, 0, 0;\n"
      "wgmma.mma_async.sync.aligned.m64n96k16.f32.bf16.bf16 {%0, %1, %2, %3, %4, %5, %6, %7, %8, %9, %10, %11, %12, %13, %14, %15, %16, %17, %18, %19, %20, %21, %22, %23, %24, %25, %26, %27, %28, %29, %30, %31, %32, %33, %34, %35, %36, %37, %38, %39, %40, %41, %42, %43, %44, %45, %46, %47}, {%48, %49, %50, %51}, %52, p, 1, 1, 1;\n}\n"
      : "=f"(d[0]), "=f"(d[1]), "=f"(d[2]), "=f"(d[3]), "=f"(d[4]), "=f"(d[5]), "=f"(d[6]), "=f"(d[7]), "=f"(d[8]), "=f"(d[9]), "=f"(d[10]), "=f"(d[11]), "=f"(d[12]), "=f"(d[13]), "=f"(d[14]), "=f"(d[15]), "=f"(d[16]), "=f"(d[17]), "=f"(d[18]), "=f"(d[19]), "=f"(d[20]), "=f"(d[21]), "=f"(d[22]), "=f"(d[23]), "=f"(d[24]), "=f"(d[25]), "=f"(d[26]), "=f"(d[27]), "=f"(d[28]), "=f"(d[29]), "=f"(d[30]), "=f"(d[31]), "=f"(d[32]), "=f"(d[33]), "=f"(d[34]), "=f"(d[35]), "=f"(d[36]), "=f"(d[37]), "=f"(d[38]), "=f"(d[39]), "=f"(d[40]), "=f"(d[41]), "=f"(d[42]), "=f"(d[43]), "=f"(d[44]), "=f"(d[45]), "=f"(d[46]), "=f"(d[47])
      : "r"(a0), "r"(a1), "r"(a2), "r"(a3), "l"(db));
  }
}
template <int SD> __device__ __forceinline__ void wgmma_rs_n64_t0(float (&d)[32], uint32_t a0, uint32_t a1, uint32_t a2, uint32_t a3, uint64_t db) {
  if constexpr (SD) {
    asm volatile("{\n.reg .pred p;\nsetp.ne.b32 p, 1, 0;\n"
      "wgmma.mma_async.sync.aligned.m64n64k16.f32.bf16.bf16 {%0, %1, %2, %3, %4, %5, %6, %7, %8, %9, %10, %11, %12, %13, %14, %15, %16, %17, %18, %19, %20, %21, %22, %23, %24, %25, %26, %27, %28, %29, %30, %31}, {%32, %33, %34, %35}, %36, p, 1, 1, 0;\n}\n"
      : "+f"(d[0]), "+f"(d[1]), "+f"(d[2]), "+f"(d[3]), "+f"(d[4]), "+f"(d[5]), "+f"(d[6]), "+f"(d[7]), "+f"(d[8]), "+f"(d[9]), "+f"(d[10]), "+f"(d[11]), "+f"(d[12]), "+f"(d[13]), "+f"(d[14]), "+f"(d[15]), "+f"(d[16]), "+f"(d[17]), "+f"(d[18]), "+f"(d[19]), "+f"(d[20]), "+f"(d[21]), "+f"(d[22]), "+f"(d[23]), "+f"(d[24]), "+f"(d[25]), "+f"(d[26]), "+f"(d[27]), "+f"(d[28]), "+f"(d[29]), "+f"(d[30]), "+f"(d[31])
      : "r"(a0), "r"(a1), "r"(a2), "r"(a3), "l"(db));
  } else {
    asm volatile("{\n.reg .pred p;\nsetp.ne.b32 p, 0, 0;\n"
      "wgmma.mma_async.sync.aligned.m64n64k16.f32.bf16.bf16 {%0, %1, %2, %3, %4, %5, %6, %7, %8, %9, %10, %11, %12, %13, %14, %15, %16, %17, %18, %19, %20, %21, %22, %23, %24, %25, %26, %27, %28, %29, %30, %31}, {%32, %33, %34, %35}, %36, p, 1, 1, 0;\n}\n"
      : "=f"(d[0]), "=f"(d[1]), "=f"(d[2]), "=f"(d[3]), "=f"(d[4]), "=f"(d[5]), "=f"(d[6]), "=f"(d[7]), "=f"(d[8]), "=f"(d[9]), "=f"(d[10]), "=f"(d[11]), "=f"(d[12]), "=f"(d[13]), "=f"(d[14]), "=f"(d[15]), "=f"(d[16]), "=f"(d[17]), "=f"(d[18]), "=f"(d[19]), "=f"(d[20]), "=f"(d[21]), "=f"(d[22]), "=f"(d[23]), "=f"(d[24]), "=f"(d[25]), "=f"(d[26]), "=f"(d[27]), "=f"(d[28]), "=f"(d[29]), "=f"(d[30]), "=f"(d[31])
      : "r"(a0), "r"(a1), "r"(a2), "r"(a3), "l"(db));
  }
}
template <int SD> __device__ __forceinline__ void wgmma_rs_n32_t1(float (&d)[16], uint32_t a0, uint32_t a1, uint32_t a2, uint32_t a3, uint64_t db) {
  if constexpr (SD) {
    asm volatile("{\n.reg .pred p;\nsetp.ne.b32 p, 1, 0;\n"
      "wgmma.mma_async.sync.aligned.m64n32k16.f32.bf16.bf16 {%0, %1, %2, %3, %4, %5, %6, %7, %8, %9, %10, %11, %12, %13, %14, %15}, {%16, %17, %18, %19}, %20, p, 1, 1, 1;\n}\n"
      : "+f"(d[0]), "+f"(d[1]), "+f"(d[2]), "+f"(d[3]), "+f"(d[4]), "+f"(d[5]), "+f"(d[6]), "+f"(d[7]), "+f"(d[8]), "+f"(d[9]), "+f"(d[10]), "+f"(d[11]), "+f"(d[12]), "+f"(d[13]), "+f"(d[14]), "+f"(d[15])
      : "r"(a0), "r"(a1), "r"(a2), "r"(a3), "l"(db));
  } else {
    asm volatile("{\n.reg .pred p;\nsetp.ne.b32 p, 0, 0;\n"
      "wgmma.mma_async.sync.aligned.m64n32k16.f32.bf16.bf16 {%0, %1, %2, %3, %4, %5, %6, %7, %8, %9, %10, %11, %12, %13, %14, %15}, {%16, %17, %18, %19}, %20, p, 1, 1, 1;\n}\n"
      : "=f"(d[0]), "=f"(d[1]), "=f"(d[2]), "=f"(d[3]), "=f"(d[4]), "=f"(d[5]), "=f"(d[6]), "=f"(d[7]), "=f"(d[8]), "=f"(d[9]), "=f"(d[10]), "=f"(d[11]), "=f"(d[12]), "=f"(d[13]), "=f"(d[14]), "=f"(d[15])
      : "r"(a0), "r"(a1), "r"(a2), "r"(a3), "l"(db));
  }
}
template <int SD> __device__ __forceinline__ void wgmma_rs_n8_t0(float (&d)[4], uint32_t a0, uint32_t a1, uint32_t a2, uint32_t a3, uint64_t db) {
  if constexpr (SD) {
    asm volatile("{\n.reg .pred p;\nsetp.ne.b32 p, 1, 0;\n"
      "wgmma.mma_async.sync.aligned.m64n8k16.f32.bf16.bf16 {%0, %1, %2, %3}, {%4, %5, %6, %7}, %8, p, 1, 1, 0;\n}\n"
      : "+f"(d[0]), "+f"(d[1]), "+f"(d[2]), "+f"(d[3])
      : "r"(a0), "r"(a1), "r"(a2), "r"(a3), "l"(db));
  } else {
    asm volatile("{\n.reg .pred p;\nsetp.ne.b32 p, 0, 0;\n"
      "wgmma.mma_async.sync.aligned.m64n8k16.f32.bf16.bf16 {%0, %1, %2, %3}, {%4, %5, %6, %7}, %8, p, 1, 1, 0;\n}\n"
      : "=f"(d[0]), "=f"(d[1]), "=f"(d[2]), "=f"(d[3])
      : "r"(a0), "r"(a1), "r"(a2), "r"(a3), "l"(db));
  }
}

__device__ __forceinline__ void wg_fence()  { asm volatile("wgmma.fence.sync.aligned;" ::: "memory"); }
__device__ __forceinline__ void wg_commit() { asm volatile("wgmma.commit_group.sync.aligned;" ::: "memory"); }
template <int N> __device__ __forceinline__ void wg_wait() { asm volatile("wgmma.wait_group.sync.aligned %0;" :: "n"(N) : "memory"); }
template <int N> __device__ __forceinline__ void fence_regs(float (&d)[N]) {
#pragma unroll
  for (int i = 0; i < N; i++) asm volatile("" : "+f"(d[i]) :: "memory");
}
__device__ __forceinline__ constexpr uint64_t mk_desc(uint32_t addr, uint32_t lbo, uint32_t sbo, uint32_t swz) {
  return (uint64_t)(addr >> 4) | ((uint64_t)(lbo >> 4) << 16) | ((uint64_t)(sbo >> 4) << 32) | ((uint64_t)swz << 62);
}
__device__ __forceinline__ uint32_t pack_bf16(float lo, float hi) {
  uint32_t r; asm("cvt.rn.bf16x2.f32 %0, %1, %2;" : "=r"(r) : "f"(hi), "f"(lo)); return r;
}
__device__ __forceinline__ uint32_t hmul2(uint32_t a, uint32_t b) {
  uint32_t r; asm("mul.rn.bf16x2 %0, %1, %2;" : "=r"(r) : "r"(a), "r"(b)); return r;
}
template <int HI> __device__ __forceinline__ uint32_t hmul2_b(uint32_t a, uint32_t b) {
  uint32_t r;
  if (HI) asm("{\n.reg .b16 l, h;\n.reg .b32 t;\nmov.b32 {l, h}, %2;\nmov.b32 t, {h, h};\nmul.rn.bf16x2 %0, %1, t;\n}\n" : "=r"(r) : "r"(a), "r"(b));
  else    asm("{\n.reg .b16 l, h;\n.reg .b32 t;\nmov.b32 {l, h}, %2;\nmov.b32 t, {l, l};\nmul.rn.bf16x2 %0, %1, t;\n}\n" : "=r"(r) : "r"(a), "r"(b));
  return r;
}
__device__ __forceinline__ uint32_t hfma2(uint32_t a, uint32_t b, uint32_t c) {
  uint32_t r; asm("fma.rn.bf16x2 %0, %1, %2, %3;" : "=r"(r) : "r"(a), "r"(b), "r"(c)); return r;
}
__device__ __forceinline__ float ex2(float x) { float r; asm("ex2.approx.ftz.f32 %0, %1;" : "=f"(r) : "f"(x)); return r; }
__device__ __forceinline__ float rsq(float x) { float r; asm("rsqrt.approx.ftz.f32 %0, %1;" : "=f"(r) : "f"(x)); return r; }
__device__ __forceinline__ float rcp(float x) { float r; asm("rcp.approx.ftz.f32 %0, %1;" : "=f"(r) : "f"(x)); return r; }
__device__ __forceinline__ void stsm4(uint32_t addr, uint32_t r0, uint32_t r1, uint32_t r2, uint32_t r3) {
  asm volatile("stmatrix.sync.aligned.m8n8.x4.shared.b16 [%0], {%1,%2,%3,%4};" :: "r"(addr), "r"(r0), "r"(r1), "r"(r2), "r"(r3) : "memory");
}
__device__ __forceinline__ void fence_async() { asm volatile("fence.proxy.async.shared::cta;" ::: "memory"); }
__device__ __forceinline__ void bar_sync_n(int id, int n) { asm volatile("bar.sync %0, %1;" :: "r"(id), "r"(n) : "memory"); }
__device__ __forceinline__ void bar_arrive_n(int id, int n) { asm volatile("bar.arrive %0, %1;" :: "r"(id), "r"(n) : "memory"); }
__device__ __forceinline__ bool bar_wg_or(int id, bool v) {
  uint32_t r;
  asm volatile("{\n.reg .pred p, q;\nsetp.ne.u32 q, %2, 0;\nbar.red.or.pred p, %1, 128, q;\nselp.u32 %0, 0, 1, p;\n}\n"
               : "=r"(r) : "r"(id), "r"((uint32_t)v) : "memory");
  return __ballot_sync(0xffffffffu, r != 0) == 0;
}
__device__ __forceinline__ void mbar_init(uint32_t bar, uint32_t cnt) { asm volatile("mbarrier.init.shared::cta.b64 [%0], %1;" :: "r"(bar), "r"(cnt) : "memory"); }
__device__ __forceinline__ void mbar_expect(uint32_t bar, uint32_t bytes) {
  asm volatile("mbarrier.arrive.expect_tx.shared::cta.b64 _, [%0], %1;" :: "r"(bar), "r"(bytes) : "memory");
}
__device__ __forceinline__ void mbar_arrive(uint32_t bar) { asm volatile("mbarrier.arrive.shared::cta.b64 _, [%0];" :: "r"(bar) : "memory"); }
__device__ __forceinline__ void mbar_wait(uint32_t bar, uint32_t parity) {
  asm volatile("{\n.reg .pred p;\n.reg .u32 n;\nmov.u32 n, 0;\n"
               "LW_%=:\nmbarrier.try_wait.parity.shared::cta.b64 p, [%0], %1;\n@p bra.uni LD_%=;\n"
               "add.u32 n, n, 1;\nsetp.lt.u32 p, n, 4194304;\n@p bra.uni LW_%=;\ntrap;\nLD_%=:\n}\n"
               :: "r"(bar), "r"(parity) : "memory");
}
__device__ __forceinline__ void tma5(uint32_t dst, const CUtensorMap* m, uint32_t bar, int c0, int c1, int c2, int c3, int c4) {
  asm volatile("cp.async.bulk.tensor.5d.shared::cluster.global.mbarrier::complete_tx::bytes [%0], [%1, {%3, %4, %5, %6, %7}], [%2];"
               :: "r"(dst), "l"(m), "r"(bar), "r"(c0), "r"(c1), "r"(c2), "r"(c3), "r"(c4) : "memory");
}
__device__ __forceinline__ void tma3(uint32_t dst, const CUtensorMap* m, uint32_t bar, int c0, int c1, int c2) {
  asm volatile("cp.async.bulk.tensor.3d.shared::cluster.global.mbarrier::complete_tx::bytes [%0], [%1, {%3, %4, %5}], [%2];"
               :: "r"(dst), "l"(m), "r"(bar), "r"(c0), "r"(c1), "r"(c2) : "memory");
}
__device__ __forceinline__ void bulk_g2s(uint32_t dst, const void* src, uint32_t bytes, uint32_t bar) {
  asm volatile("cp.async.bulk.shared::cluster.global.mbarrier::complete_tx::bytes [%0], [%1], %2, [%3];"
               :: "r"(dst), "l"(src), "r"(bytes), "r"(bar) : "memory");
}
__device__ __forceinline__ uint32_t lds32(uint32_t addr) {
  uint32_t v; asm volatile("ld.shared.u32 %0, [%1];" : "=r"(v) : "r"(addr)); return v;
}
__device__ __forceinline__ uint64_t opaque(uint64_t v) { asm volatile("" : "+l"(v)); return v; }
__device__ __forceinline__ uint4 lds128(uint32_t addr) {
  uint4 v; asm volatile("ld.shared.v4.u32 {%0,%1,%2,%3}, [%4];" : "=r"(v.x), "=r"(v.y), "=r"(v.z), "=r"(v.w) : "r"(addr)); return v;
}
__device__ __forceinline__ uint4 ldg128_stream(const void* p) {
  uint4 v; asm volatile("ld.global.nc.L1::no_allocate.v4.u32 {%0,%1,%2,%3}, [%4];" : "=r"(v.x), "=r"(v.y), "=r"(v.z), "=r"(v.w) : "l"(p)); return v;
}
__device__ __forceinline__ void stg128(void* p, uint32_t a, uint32_t b, uint32_t c, uint32_t d) {
  asm volatile("st.global.v4.u32 [%0], {%1,%2,%3,%4};" :: "l"(p), "r"(a), "r"(b), "r"(c), "r"(d) : "memory");
}
__device__ __forceinline__ void prefetch_l2(const void* p, uint32_t bytes) {
  asm volatile("cp.async.bulk.prefetch.L2.global [%0], %1;" :: "l"(p), "r"(bytes) : "memory");
}
__device__ __forceinline__ bool elect_one() {
  uint32_t r; asm volatile("{\n.reg .pred p;\nelect.sync _|p, 0xffffffff;\nselp.u32 %0, 1, 0, p;\n}\n" : "=r"(r)); return r != 0;
}
__device__ __forceinline__ float bf_lo(uint32_t u) { return __uint_as_float(u << 16); }
__device__ __forceinline__ float bf_hi(uint32_t u) { return __uint_as_float(u & 0xFFFF0000u); }
__device__ __forceinline__ float rbf(float x) { return bf_lo(pack_bf16(x, 0.f)); }
__device__ __forceinline__ int orig_tok(int r) { return ((r & 31) >> 2) * 8 + (r >> 5) * 4 + (r & 3); }

__device__ __forceinline__ int slot_window(int s, bool g132) {
  const int A0 = g132 ? 396 + 264 + 60 : 47 * 47, A1 = A0 + 72, B0 = g132 ? 3 * 396 + 264 + 60 : A1, B1 = B0 + 23;
  const int i = s - (s >= B1 ? 95 : s >= A1 ? 72 : 0);
  const int k = s >= B0 ? s - B0 + 72 : s - A0;
  const bool border = (s >= A0 && s < A1) || (s >= B0 && s < B1);
  const int iy = (i * 2789) >> 17;
  return border ? (k < 48 ? (47 << 8 | k) : ((k - 48) << 8 | 47)) : (iy << 8 | (i - iy * 47));
}

#define EB_WORD(e, j, a) ((((a) ^ ((j) & 1)) == 0) ? (e).x : (((a) ^ ((j) & 1)) == 1) ? (e).y : (((a) ^ ((j) & 1)) == 2) ? (e).z : (e).w)

__device__ __forceinline__ void load_eb(uint32_t (&e)[16], uint32_t eb_addr) {
#pragma unroll
  for (int j = 0; j < 4; j++) {
    const uint4 v = lds128(eb_addr + j * 2048);
#pragma unroll
    for (int a = 0; a < 4; a++) e[4 * j + a] = EB_WORD(v, j, a);
  }
}
__device__ __forceinline__ void softmax_fast(const float (&s)[32], uint32_t (&p)[16]) {
#pragma unroll
  for (int i = 0; i < 16; i++) p[i] = hmul2(pack_bf16(ex2(s[2 * i]), ex2(s[2 * i + 1])), p[i]);
}
__device__ __forceinline__ uint32_t hmax2(uint32_t a, uint32_t b) {
  uint32_t r; asm("max.bf16x2 %0, %1, %2;" : "=r"(r) : "r"(a), "r"(b)); return r;
}
__device__ __forceinline__ uint32_t hmax2_nan(uint32_t a, uint32_t b) {
  uint32_t r; asm("max.NaN.bf16x2 %0, %1, %2;" : "=r"(r) : "r"(a), "r"(b)); return r;
}
__device__ __forceinline__ float quad_max(float m) {
  m = fmaxf(m, __shfl_xor_sync(0xffffffffu, m, 1));
  return fmaxf(m, __shfl_xor_sync(0xffffffffu, m, 2));
}
__device__ __forceinline__ void softmax_true_max(const float (&s)[32], uint32_t (&p)[16]) {
  float m0 = s[0], m1 = s[2];
#pragma unroll
  for (int g = 0; g < 8; g++) {
    m0 = fmaxf(m0, fmaxf(s[4 * g + 0], s[4 * g + 1]));
    m1 = fmaxf(m1, fmaxf(s[4 * g + 2], s[4 * g + 3]));
  }
  m0 = quad_max(m0); m1 = quad_max(m1);
  uint32_t n0 = 0, n1 = 0;
#pragma unroll
  for (int g = 0; g < 8; g++) {
    p[2 * g + 0] = hmul2(pack_bf16(ex2(s[4 * g + 0] - m0), ex2(s[4 * g + 1] - m0)), p[2 * g + 0]);
    p[2 * g + 1] = hmul2(pack_bf16(ex2(s[4 * g + 2] - m1), ex2(s[4 * g + 3] - m1)), p[2 * g + 1]);
    n0 = hmax2(n0, p[2 * g]); n1 = hmax2(n1, p[2 * g + 1]);
  }
  const uint32_t r = pack_bf16(rcp(quad_max(fmaxf(bf_lo(n0), bf_hi(n0)))), rcp(quad_max(fmaxf(bf_lo(n1), bf_hi(n1)))));
#pragma unroll
  for (int g = 0; g < 8; g++) { p[2 * g] = hmul2_b<0>(p[2 * g], r); p[2 * g + 1] = hmul2_b<1>(p[2 * g + 1], r); }
}
template <int H> __device__ __forceinline__ void issue_s(float (&s)[32], const uint32_t (&q)[24], uint64_t dK) {
  constexpr int Q0 = (H == 0 ? 0 : H == 1 ? 4 : H == 2 ? 12 : 16), P0 = (H == 0 ? 0 : H == 1 ? 3 : H == 2 ? 7 : 10);
  wgmma_rs_n64_t0<0>(s, q[Q0], q[Q0 + 1], q[Q0 + 2], q[Q0 + 3], dK + P0 * 64);
  wgmma_rs_n64_t0<1>(s, q[Q0 + 4], q[Q0 + 5], q[Q0 + 6], q[Q0 + 7], dK + P0 * 64 + 128);
}
template <int H> __device__ __forceinline__ void issue_pv(float (&o)[16], const uint32_t (&p)[16], uint64_t dV) {
  constexpr int P0 = (H == 0 ? 0 : H == 1 ? 3 : H == 2 ? 7 : 10);
  wgmma_rs_n32_t1<0>(o, p[0], p[1], p[2], p[3], dV + P0 * 64);
  wgmma_rs_n32_t1<1>(o, p[4], p[5], p[6], p[7], dV + P0 * 64 + 16);
  wgmma_rs_n32_t1<1>(o, p[8], p[9], p[10], p[11], dV + P0 * 64 + 32);
  wgmma_rs_n32_t1<1>(o, p[12], p[13], p[14], p[15], dV + P0 * 64 + 48);
}
__device__ __forceinline__ void issue_proj(float (&d)[48], uint64_t dX, uint64_t dW) {
#pragma unroll
  for (int s = 0; s < 6; s++) {
    const uint64_t a = dX + (s >> 1) * 256 + (s & 1) * 2, b = dW + s * 64;
    if (s == 0) wgmma_ss_n96_t1<0>(d, a, b); else wgmma_ss_n96_t1<1>(d, a, b);
  }
}
__device__ __forceinline__ void issue_qk(float (&d)[96], uint64_t dX, uint64_t dW) {
#pragma unroll
  for (int s = 0; s < 6; s++) {
    const uint64_t a = dX + (s >> 1) * 256 + (s & 1) * 2, b = dW + s * 128;
    if (s == 0) wgmma_ss_n192_t1<0>(d, a, b); else wgmma_ss_n192_t1<1>(d, a, b);
  }
}
__device__ __forceinline__ void pack_sumsq(const float* a, uint32_t (&f)[24], uint32_t (&sq)[8], uint32_t init) {
#pragma unroll
  for (int i = 0; i < 24; i++) f[i] = pack_bf16(a[2 * i], a[2 * i + 1]);
#pragma unroll
  for (int h = 0; h < 4; h++)
#pragma unroll
    for (int r = 0; r < 2; r++) {
      uint32_t u = f[6 * h + r], v = f[6 * h + 2 + r], w = f[6 * h + 4 + r];
      sq[2 * h + r] = hfma2(w, w, hfma2(v, v, hfma2(u, u, init)));
    }
}
__device__ __forceinline__ void scale_heads(uint32_t (&f)[24], const float (&r)[8]) {
#pragma unroll
  for (int h = 0; h < 4; h++) {
    const uint32_t p = pack_bf16(r[2 * h], r[2 * h + 1]);
#pragma unroll
    for (int c = 0; c < 3; c++) {
      f[6 * h + 2 * c] = hmul2_b<0>(f[6 * h + 2 * c], p);
      f[6 * h + 2 * c + 1] = hmul2_b<1>(f[6 * h + 2 * c + 1], p);
    }
  }
}
template <int ODD> __device__ __forceinline__ void norm_o(const float (&o)[16], uint32_t* of) {
  constexpr int SO = ODD ? 0 : 12, VO = ODD ? 4 : 0;
  const uint32_t p = pack_bf16(rcp(o[SO]), rcp(o[SO + 2]));
#pragma unroll
  for (int g = 0; g < 3; g++) {
    of[2 * g + 0] = hmul2_b<0>(pack_bf16(o[VO + 4 * g + 0], o[VO + 4 * g + 1]), p);
    of[2 * g + 1] = hmul2_b<1>(pack_bf16(o[VO + 4 * g + 2], o[VO + 4 * g + 3]), p);
  }
}

#define TL(i)
#define TG(i)

constexpr int BAR_KV = 1;
constexpr int BAR_AUX = 4;
constexpr int BAR_TAB = 7, BAR_SETUP = 8;
constexpr int NO_TICKET = 0xFF;
#define BORDER_EXTRA 1
constexpr int MB_WQK = 0, MB_X = 8, MB_KV = 32, MB_WV = 56, MB_WO = 64, MB_TURN = 72, MB_RDY = 128, MB_WOC = 136;
constexpr uint32_t sb = 1024, mbar = sb + SM_BAR;
constexpr uint32_t EPS8 = 0x2A0D2A0Du;

__device__ __forceinline__ void load_x_interior(const CUtensorMap* tm_x, int w, int g) {
  mbar_expect(mbar + MB_X + 8 * g, 12288);
  tma5(sb + SM_WG + g * WG_SZ + WG_X, tm_x, mbar + MB_X + 8 * g, 0, 0, ((w >> 8) & 255) * 8 + 4, (w & 255) * 2 + 1, 0);
}
__device__ __forceinline__ void load_x(const CUtensorMap* tm_x, const CUtensorMap* tm_xq, int w, int g) {
  const uint32_t dst = sb + SM_WG + g * WG_SZ + WG_X, bar = mbar + MB_X + 8 * g;
  const int wy = (w >> 8) & 255, wx = w & 255;
  mbar_expect(bar, 12288);
  if (wy != NWX - 1 && wx != NWX - 1) {
    tma5(dst, tm_x, bar, 0, 0, wy * 8 + 4, wx * 2 + 1, 0);
  } else {
#pragma unroll 1
    for (int i = 0; i < 12; i++) {
      const int q = i & 3, c = i >> 2;
      int y = wy * 8 + 4 + (q & 1) * 4; if (y >= IMG) y -= IMG;
      int xq = wx * 2 + 1 + (q >> 1);   if (xq >= IMG / 4) xq -= IMG / 4;
      tma5(dst + i * 1024, tm_xq, bar, 0, 0, y, xq, c);
    }
  }
}
__device__ __forceinline__ uint32_t mask_off(int w) { return (uint32_t)(((w >> 8) & 255) * NWX + (w & 255)) * 8192u; }
__device__ __forceinline__ int lds_uniform(uint32_t addr) { return __shfl_sync(0xffffffffu, lds32(addr), 0); }

__device__ __forceinline__ void qkv_epilogue(float (&qk)[96], uint32_t (&qa)[24], uint64_t dX, uint64_t dWv, uint32_t k_dst) {
  uint32_t ka[24], sk[8], sq[8];
  float k01[4], k23[4], q01[4], q23[4], vv[48];
  constexpr uint64_t dSel = mk_desc(sb + SM_SEL, 128, 256, 0);
  wg_wait<0>(); fence_regs(qk);
  pack_sumsq(qk + 48, ka, sk, EPS8);
  pack_sumsq(qk, qa, sq, EPS8);
  wg_fence();
  wgmma_rs_n8_t0<0>(k01, sk[0], sk[1], sk[2], sk[3], dSel);
  wgmma_rs_n8_t0<0>(k23, sk[4], sk[5], sk[6], sk[7], dSel);
  wgmma_rs_n8_t0<0>(q01, sq[0], sq[1], sq[2], sq[3], dSel);
  wgmma_rs_n8_t0<0>(q23, sq[4], sq[5], sq[6], sq[7], dSel);
  wg_commit();
  issue_proj(vv, dX, dWv); wg_commit();
  const uint4 qs = lds128(sb + SM_MISC);
  wg_wait<1>(); fence_regs(k01); fence_regs(k23); fence_regs(q01); fence_regs(q23);
  const float rk[8] = {rsq(k01[0]), rsq(k01[2]), rsq(k01[1]), rsq(k01[3]), rsq(k23[0]), rsq(k23[2]), rsq(k23[1]), rsq(k23[3])};
  scale_heads(ka, rk);
#pragma unroll
  for (int i = 0; i < 6; i++) stsm4(k_dst + (i + (i >= 3)) * 1024, ka[2 * i], ka[2 * i + 1], ka[12 + 2 * i], ka[12 + 2 * i + 1]);
  wg_wait<0>(); fence_regs(vv);
#pragma unroll
  for (int i = 0; i < 6; i++)
    stsm4(k_dst + (WG_V - WG_K) + (i + (i >= 3)) * 1024, pack_bf16(vv[4 * i], vv[4 * i + 1]), pack_bf16(vv[4 * i + 2], vv[4 * i + 3]),
          pack_bf16(vv[24 + 4 * i], vv[24 + 4 * i + 1]), pack_bf16(vv[24 + 4 * i + 2], vv[24 + 4 * i + 3]));
  const float s0 = __uint_as_float(qs.x), s1 = __uint_as_float(qs.y), s2 = __uint_as_float(qs.z), s3 = __uint_as_float(qs.w);
  const float rq[8] = {rsq(q01[0]) * s0, rsq(q01[2]) * s0, rsq(q01[1]) * s1, rsq(q01[3]) * s1,
                       rsq(q23[0]) * s2, rsq(q23[2]) * s2, rsq(q23[1]) * s3, rsq(q23[3]) * s3};
  scale_heads(qa, rq);
  fence_async();
}
__device__ __forceinline__ void issue_out(float (&y)[48], const uint32_t (&of)[24], uint64_t dWo) {
  wg_fence();
#pragma unroll
  for (int s = 0; s < 6; s++) {
    if (s == 0) wgmma_rs_n96_t1<0>(y, of[0], of[1], of[2], of[3], dWo);
    else wgmma_rs_n96_t1<1>(y, of[4 * s], of[4 * s + 1], of[4 * s + 2], of[4 * s + 3], dWo + s * 16);
  }
  wg_commit();
}
__device__ __forceinline__ void ln_head(float (&y)[48], uint32_t (&yb)[24], float (&var)[4], uint64_t dOnes) {
  uint32_t sy[8];
  wg_wait<0>(); fence_regs(y);
  pack_sumsq(y, yb, sy, 0u);
  wg_fence();
  wgmma_rs_n8_t0<0>(var, sy[0], sy[1], sy[2], sy[3], dOnes);
  wgmma_rs_n8_t0<1>(var, sy[4], sy[5], sy[6], sy[7], dOnes);
  wg_commit();
}
__device__ __forceinline__ char* out_ptr(__nv_bfloat16* out, int win, int warp, uint32_t t16) {
  int py = ((win >> 8) & 255) * 8 + 4 + (warp & 1) * 4;  if (py >= IMG) py -= IMG;
  int px = (win & 255) * 8 + 4 + (warp >> 1) * 4;        if (px >= IMG) px -= IMG;
  return reinterpret_cast<char*>(out) + ((uint32_t)(py * IMG + px) * PIXB - warp * 512 + t16 + ((t16 & 0xC0) << 1) + (t16 & 0x100) * 287);
}
__device__ __forceinline__ uint32_t ln_tail(const uint32_t (&yb)[24], float (&var)[4], char* optr) {
  fence_regs(var);
  uint32_t last;
  const uint32_t nn = pack_bf16(rsq(fmaf(var[0], 1.f / 96.f, 1e-5f)), rsq(fmaf(var[2], 1.f / 96.f, 1e-5f)));
#pragma unroll
  for (int j = 0; j < 3; j++) {
    stg128(optr + j * 64, hmul2_b<0>(yb[8 * j], nn), hmul2_b<0>(yb[8 * j + 2], nn), hmul2_b<0>(yb[8 * j + 4], nn), hmul2_b<0>(yb[8 * j + 6], nn));
    last = hmul2_b<1>(yb[8 * j + 7], nn);
    stg128(optr + 2 * ROWB + j * 64, hmul2_b<1>(yb[8 * j + 1], nn), hmul2_b<1>(yb[8 * j + 3], nn), hmul2_b<1>(yb[8 * j + 5], nn), last);
  }
  return last;
}

__device__ __forceinline__ void load_mask_frag(uint32_t (&mk)[16], const char* tile, uint32_t t16) {
  asm volatile("" : "+r"(t16));
  const char* mrow = tile + (orig_tok(((t16 >> 9) << 4) + ((t16 >> 6) & 7)) * 128 + (t16 & 32) / 2 + (t16 & 16) / 4);
#pragma unroll
  for (int i = 0; i < 16; i++)
    asm volatile("ld.global.nc.u32 %0, [%1];" : "=r"(mk[i]) : "l"(mrow + (i & 1) * 2048 + ((i >> 1) & 3) * 32 + (i >> 3) * 8) : "memory");
}
__device__ __forceinline__ bool mask_unsafe(const uint32_t (&mk)[16]) {
  uint32_t x0 = mk[0], x1 = mk[1];
#pragma unroll
  for (int i = 2; i < 16; i += 2) { x0 = hmax2_nan(x0, mk[i]); x1 = hmax2_nan(x1, mk[i + 1]); }
  const bool nan_in = !(bf_lo(x0) == bf_lo(x0) && bf_hi(x0) == bf_hi(x0) && bf_lo(x1) == bf_lo(x1) && bf_hi(x1) == bf_hi(x1));
  const float r0 = quad_max(fmaxf(bf_lo(x0), bf_hi(x0))), r1 = quad_max(fmaxf(bf_lo(x1), bf_hi(x1)));
  return nan_in || !(fabsf(r0) <= 8.f && fabsf(r1) <= 8.f);
}

__device__ __forceinline__ void general_windows(const CUtensorMap* tm_x, const CUtensorMap* tm_xq, const char* mb, __nv_bfloat16* out, uint32_t xph) {
  int tid;
  asm volatile("mov.u32 %0, %%tid.x;" : "=r"(tid));
  const int lane = tid & 31;
  const int warp = __shfl_sync(0xffffffffu, (tid >> 5) & 3, 0), wg = __shfl_sync(0xffffffffu, tid >> 7, 0);
  const uint32_t t16 = (tid & 127) * 16, wgb = sb + SM_WG + wg * WG_SZ, bar_x = mbar + MB_X + 8 * wg;
  const uint32_t k_dst = wgb + WG_K + (lane >> 4) * 7168 + warp * 256 + (lane & 15) * 16;
  if (lds_uniform(sb + SM_GEN + wg * NENT * 4) < 0) return;
  mbar_wait(mbar + MB_WV, 0);
  mbar_wait(mbar + MB_RDY, 0);
  mbar_wait(mbar + MB_WOC, 0);
  const uint32_t slow_heads = lds_uniform(sb + SM_SLOW);
  const uint64_t dX = mk_desc(WG_X, 16, 512, 2) + (wgb >> 4), dK = mk_desc(WG_K, 1024, 128, 0) + (wgb >> 4), dV = mk_desc(WG_V, 128, 1024, 0) + (wgb >> 4);
#pragma unroll 1
  for (uint32_t gl = sb + SM_GEN + wg * NENT * 4;; gl += 4) {
    const int win = lds_uniform(gl);
    if (win < 0) break;
    uint32_t qa[24], of[24], mk[16];
    uint32_t tm;
    {
      load_mask_frag(mk, mb + mask_off(win), t16);
      float qk[96];
      mbar_wait(bar_x, xph); xph ^= 1;
      wg_fence();
      issue_qk(qk, dX, mk_desc(sb + SM_W, 12288, 1024, 1)); wg_commit();
      uint32_t any = 0;
#pragma unroll
      for (int i = 0; i < 16; i += 2) any |= mk[i] | mk[i + 1];
      tm = bar_wg_or(BAR_KV + wg, (any & 0x7FFF7FFFu) != 0) ? 0x1Fu : slow_heads;
      qkv_epilogue(qk, qa, dX, mk_desc(sb + SM_WV, 6144, 512, 2), k_dst);
    }
    bar_sync_n(BAR_AUX + wg, 128);
    if (warp == 0 && elect_one()) {
      const int nxt = lds32(gl + 4);
      if (nxt >= 0) { load_x(tm_x, tm_xq, nxt, wg); prefetch_l2(mb + mask_off(nxt), 8192); }
    }
    __syncwarp();
    auto head = [&](float (&sc)[32], uint32_t (&p)[16], bool tmax) {
      if (tmax) {
        if (tm & 16) {
#pragma unroll
          for (int i = 0; i < 16; i++) {
            sc[2 * i] = fmaf(bf_lo(mk[i]), LOG2E, sc[2 * i]); sc[2 * i + 1] = fmaf(bf_hi(mk[i]), LOG2E, sc[2 * i + 1]);
          }
        }
        softmax_true_max(sc, p);
      } else {
        softmax_fast(sc, p);
      }
    };
#pragma unroll
    for (int i = 0; i < 24; i++) of[i] = 0;
#pragma unroll 1
    for (int hp = 0; hp < 2; hp++) {
      float sA[32], sB[32], oA[16], oB[16]; uint32_t p[16];
      const uint32_t po = hp * 7 * 64;
      wg_fence();
      issue_s<0>(sA, qa, dK + po);
      issue_s<1>(sB, qa, dK + po); wg_commit();
      load_eb(p, sb + SM_EB + t16 + hp * 16384);
      wg_wait<0>(); fence_regs(sA); fence_regs(sB);
#pragma unroll
      for (int i = 0; i < 12; i++) { qa[i] = qa[i + 12]; of[i] = of[i + 12]; }
      head(sA, p, (tm >> (2 * hp)) & 1);
      wg_fence(); issue_pv<0>(oA, p, dV + po); wg_commit();
      uint32_t p2[16];
      load_eb(p2, sb + SM_EB + t16 + hp * 16384 + 8192);
      head(sB, p2, (tm >> (2 * hp + 1)) & 1);
      wg_fence(); issue_pv<1>(oB, p2, dV + po); wg_commit();
      wg_wait<1>(); fence_regs(oA);
      norm_o<0>(oA, of + 12);
      wg_wait<0>(); fence_regs(oB);
      norm_o<1>(oB, of + 18);
    }
    float y[48], var[4]; uint32_t yb[24];
    issue_out(y, of, mk_desc(sb + SM_WO, 128, 1536, 0));
    ln_head(y, yb, var, dV + 3 * 64);
    wg_wait<0>();
    ln_tail(yb, var, out_ptr(out, win, warp, t16));
  }
}

__global__ void __launch_bounds__(384, 1)
swin_kernel(const __grid_constant__ CUtensorMap tm_x, const __grid_constant__ CUtensorMap tm_xq, const __grid_constant__ CUtensorMap tm_wqk,
            const __grid_constant__ CUtensorMap tm_wv,
            const __nv_bfloat16* __restrict__ wo,
            const __nv_bfloat16* __restrict__ logit_scale, const __nv_bfloat16* __restrict__ w1, const __nv_bfloat16* __restrict__ w2,
            const __nv_bfloat16* __restrict__ coords, const int* __restrict__ rel_idx, const __nv_bfloat16* __restrict__ mask,
            __nv_bfloat16* __restrict__ out) {
  extern __shared__ __align__(1024) uint8_t smem[];
  const int tid = threadIdx.x, lane = tid & 31;
  const int warp = __shfl_sync(0xffffffffu, (tid >> 5) & 3, 0), wg = __shfl_sync(0xffffffffu, tid >> 7, 0);
  const int G = gridDim.x;
  const char* mb = reinterpret_cast<const char*>(mask);
  TL(0); TG(14);

  const bool g132 = G == 132;
  const uint2 lsw = __ldg(reinterpret_cast<const uint2*>(logit_scale));
  uint32_t cw = 0;
  int4 rid[4];
  if (wg == 0) {
    if (warp == 0) {
      if (elect_one()) {
#pragma unroll
        for (int i = 0; i < 13; i++) mbar_init(mbar + 8 * i, ((i >= 4 && i < 7) || i >= 9) ? 4 : 1);
        mbar_init(mbar + MB_RDY, 8); mbar_init(mbar + MB_WOC, 4);
        fence_async();
        mbar_expect(mbar + MB_WQK, 3 * 12288);
        tma3(sb + SM_W, &tm_wqk, mbar + MB_WQK, 0, 0, 0);
        load_x_interior(&tm_x, slot_window(blockIdx.x, g132), 0);
        mbar_expect(mbar + MB_WV, 3 * 6144);
        tma3(sb + SM_WV, &tm_wv, mbar + MB_WV, 0, 0, 0);
        mbar_expect(mbar + MB_WO, 18432);
        bulk_g2s(sb + SM_WOR, wo, 18432, mbar + MB_WO);
      }
      __syncwarp();
    }
  } else {
    const int i = tid - 128;
    if (i < 12) *reinterpret_cast<uint4*>(smem + SM_PAR + 16 * i) = __ldg(i < 4 ? reinterpret_cast<const uint4*>(w1) + i : reinterpret_cast<const uint4*>(w2) + (i - 4));
    if (i < 225) cw = __ldg(reinterpret_cast<const uint32_t*>(coords) + i);
  }
  if ((uint32_t)__cvta_generic_to_shared(smem) != sb) __trap();
  auto const_tiles = [&]() {
    const int i = tid & 127;
    uint8_t* vt = smem + SM_WG + wg * WG_SZ + WG_V + (i < 64 ? 3 : 10) * 1024 + (i & 63) * 16;
    *reinterpret_cast<uint4*>(vt) = make_uint4(0x3F803F80u, 0x3F803F80u, 0x3F803F80u, 0x3F803F80u);
    *reinterpret_cast<uint4*>(vt - (WG_V - WG_K)) = make_uint4(0u, 0u, 0u, 0u);
  };
  if (wg != 2) const_tiles();
  float tau[4]; uint32_t slow_heads = 0;
  {
    const float ls[4] = {bf_lo(lsw.x), bf_hi(lsw.x), bf_lo(lsw.y), bf_hi(lsw.y)};
#pragma unroll
    for (int h = 0; h < 4; h++) {
      const float c = ls[h] < -100.f ? -100.f : (ls[h] > 4.59375f ? 4.59375f : ls[h]);
      tau[h] = rbf(ex2(c * LOG2E)) * LOG2E;
      if (!(tau[h] <= TAU_FAST_MAX)) slow_heads |= 1u << h;
    }
    slow_heads = __shfl_sync(0xffffffffu, slow_heads, 0);
  }
  if (wg == 0 && warp == 1) {
    const int eg = lane / NENT, ei = lane - eg * NENT, sl = blockIdx.x + eg * G + ei * 3 * G;
    const int w = (sl < NWIN && eg < 3) ? slot_window(sl, g132) : -1;
    const bool queues = w >= 0 && (w >> 8) != NWX - 1 && (w & 255) != NWX - 1;
    const uint32_t qmask = __ballot_sync(0xffffffffu, queues);
    const int key = (eg + 3 * ei + BORDER_EXTRA * __popc((~qmask >> (eg * NENT)) & ((1u << ei) - 1))) * 3 + eg;
    const uint32_t k0 = __reduce_or_sync(0xffffffffu, queues && key < 32 ? 1u << key : 0u), k1 = __reduce_or_sync(0xffffffffu, queues && (key >> 5) == 1 ? 1u << (key & 31) : 0u);
    const uint32_t k2 = __reduce_or_sync(0xffffffffu, queues && (key >> 5) == 2 ? 1u << (key & 31) : 0u), k3 = __reduce_or_sync(0xffffffffu, queues && (key >> 5) == 3 ? 1u << (key & 31) : 0u);
    const uint32_t lo = (1u << (key & 31)) - 1;
    const int kw = key >> 5;
    const int ticket = __popc(kw > 0 ? k0 : k0 & lo) + (kw >= 1 ? __popc(kw > 1 ? k1 : k1 & lo) : 0) + (kw >= 2 ? __popc(kw > 2 ? k2 : k2 & lo) : 0) + (kw >= 3 ? __popc(k3 & lo) : 0);
    const int ent = w | (queues ? ticket : NO_TICKET) << 16;
    if (eg < 3) {
      *reinterpret_cast<int*>(smem + SM_WIN + lane * 4) = slow_heads ? -1 : ent;
      *reinterpret_cast<int*>(smem + SM_GEN + lane * 4) = slow_heads ? ent : -1;
    }
  }
  if (wg == 0 && warp == 3 && lane < 16) {
    const uint32_t v = (((lane >> 3) ^ lane) & 1) ? 0u : 0x3F803F80u;
    *reinterpret_cast<uint4*>(smem + SM_SEL + lane * 16) = make_uint4(v, v, v, v);
  }
  TL(3);
  if (wg == 0) {
    if (tid == 0) {
      *reinterpret_cast<float4*>(smem + SM_MISC) = make_float4(tau[0], tau[1], tau[2], tau[3]);
      *reinterpret_cast<uint32_t*>(smem + SM_SLOW) = slow_heads;
    }
    fence_async();
    bar_arrive_n(BAR_SETUP, 384);
    bar_sync_n(BAR_AUX, 128);
  } else {
    const int i = tid - 128;
#pragma unroll
    for (int c = 0; c < 4; c++) {
      const uint4 r = ldg128_stream(reinterpret_cast<const int4*>(rel_idx) + c * 256 + i);
      rid[c] = make_int4(r.x, r.y, r.z, r.w);
    }
    bar_sync_n(BAR_TAB, 256);
    TL(4);
    if (i < 225) {
      const float c0 = bf_lo(cw), c1 = bf_hi(cw);
      float z[4] = {0.f, 0.f, 0.f, 0.f};
#pragma unroll
      for (int jj = 0; jj < 2; jj++) {
        const uint4 ua4 = lds128(sb + SM_PAR + 16 * jj), ub4 = lds128(sb + SM_PAR + 32 + 16 * jj);
        const uint32_t ua[4] = {ua4.x, ua4.y, ua4.z, ua4.w}, ub[4] = {ub4.x, ub4.y, ub4.z, ub4.w};
#pragma unroll
        for (int j = 0; j < 4; j++) {
          const uint4 wb = lds128(sb + SM_PAR + 64 + 64 * jj + 16 * j);
          const uint32_t hp = pack_bf16(fmaf(c1, bf_lo(ub[j]), c0 * bf_lo(ua[j])), fmaf(c1, bf_hi(ub[j]), c0 * bf_hi(ua[j])));
          float h0 = bf_lo(hp), h1 = bf_hi(hp);
          h0 = h0 > 0.f ? h0 : h0 * 0.f; h1 = h1 > 0.f ? h1 : h1 * 0.f;
          z[0] = fmaf(h0, bf_lo(wb.x), z[0]); z[1] = fmaf(h0, bf_hi(wb.x), z[1]); z[2] = fmaf(h0, bf_lo(wb.y), z[2]); z[3] = fmaf(h0, bf_hi(wb.y), z[3]);
          z[0] = fmaf(h1, bf_lo(wb.z), z[0]); z[1] = fmaf(h1, bf_hi(wb.z), z[1]); z[2] = fmaf(h1, bf_lo(wb.w), z[2]); z[3] = fmaf(h1, bf_hi(wb.w), z[3]);
        }
      }
      float e[4];
#pragma unroll
      for (int q = 0; q < 4; q++) {
        const float sh = ((slow_heads >> q) & 1) ? 0.f : fminf(0.f, 25.f - 1.02f * tau[q]);
        e[q] = ex2(fmaf(16.f * LOG2E, rbf(rcp(1.f + ex2(-LOG2E * rbf(z[q])))), sh));
      }
      *reinterpret_cast<uint2*>(smem + SM_TAB + 8 * i) = make_uint2(pack_bf16(e[0], e[1]), pack_bf16(e[2], e[3]));
    }
    TL(5);
    bar_sync_n(BAR_SETUP, 384);
    if (tid == 128 + 127) {
      const int w = slot_window(blockIdx.x + G, g132);
      load_x_interior(&tm_x, w, 1);
      prefetch_l2(mb + mask_off(w), 8192);
    }
    __syncwarp();
#pragma unroll
    for (int c = 0; c < 4; c++) asm volatile("" : "+r"(rid[c].x), "+r"(rid[c].y), "+r"(rid[c].z), "+r"(rid[c].w));
    {
      const int y = (i & 15) >> 1, xh = i & 1, j = 2 * xh + (y >> 2);
      const int X = (i >> 4) & 7, Yl = (i >> 7) & 1;
      uint8_t* dst = smem + SM_EB + j * 2048 + ((X >> 2) * 64 + (Yl * 4 + (X & 3)) * 4 + 2 * (y & 1)) * 16 + ((y >> 1) & 1) * 8;
#pragma unroll
      for (int c = 0; c < 4; c++) {
        const int ia0 = xh ? rid[c].z : rid[c].x, ia1 = xh ? rid[c].w : rid[c].y, ib0 = xh ? rid[c].x : rid[c].z, ib1 = xh ? rid[c].y : rid[c].w;
        const uint2 a0 = *reinterpret_cast<const uint2*>(smem + SM_TAB + 8 * ia0), a1 = *reinterpret_cast<const uint2*>(smem + SM_TAB + 8 * ia1);
        const uint2 b0 = *reinterpret_cast<const uint2*>(smem + SM_TAB + 8 * ib0), b1 = *reinterpret_cast<const uint2*>(smem + SM_TAB + 8 * ib1);
        uint8_t* d0 = dst + (c >> 1) * 512 + (((c & 1) ^ (j & 1)) * 4) + xh * 16;
        uint8_t* d1 = dst + (c >> 1) * 512 + (((c & 1) ^ (j & 1)) * 4) + (xh ^ 1) * 16;
        *reinterpret_cast<uint32_t*>(d0)         = __byte_perm(a0.x, a1.x, 0x5410); *reinterpret_cast<uint32_t*>(d1)         = __byte_perm(b0.x, b1.x, 0x5410);
        *reinterpret_cast<uint32_t*>(d0 + 8192)  = __byte_perm(a0.x, a1.x, 0x7632); *reinterpret_cast<uint32_t*>(d1 + 8192)  = __byte_perm(b0.x, b1.x, 0x7632);
        *reinterpret_cast<uint32_t*>(d0 + 16384) = __byte_perm(a0.y, a1.y, 0x5410); *reinterpret_cast<uint32_t*>(d1 + 16384) = __byte_perm(b0.y, b1.y, 0x5410);
        *reinterpret_cast<uint32_t*>(d0 + 24576) = __byte_perm(a0.y, a1.y, 0x7632); *reinterpret_cast<uint32_t*>(d1 + 24576) = __byte_perm(b0.y, b1.y, 0x7632);
      }
    }
    TL(6);
    if (tid == 256) {
      const int w = slot_window(blockIdx.x + 2 * G, g132);
      load_x_interior(&tm_x, w, 2);
      prefetch_l2(mb + mask_off(w), 8192);
    }
    __syncwarp();
    fence_async();
    if (elect_one()) mbar_arrive(mbar + MB_RDY);
    __syncwarp();
    bar_sync_n(BAR_TAB, 256);
    if (wg == 2) {
      mbar_wait(mbar + MB_WO, 0);
      uint4 v[9];
#pragma unroll
      for (int c = 0; c < 9; c++) v[c] = lds128(sb + SM_WOR + ((c / 3) * 32 + ((tid & 127) >> 2)) * 192 + (c % 3) * 64 + (lane & 3) * 16);
      bar_sync_n(BAR_AUX + 2, 128);
      const_tiles();
#pragma unroll
      for (int r = 0; r < 3; r++) {
        float sum = 0.f;
#pragma unroll
        for (int c = 3 * r; c < 3 * r + 3; c++)
          sum += (bf_lo(v[c].x) + bf_hi(v[c].x)) + (bf_lo(v[c].y) + bf_hi(v[c].y)) + (bf_lo(v[c].z) + bf_hi(v[c].z)) + (bf_lo(v[c].w) + bf_hi(v[c].w));
        sum += __shfl_xor_sync(0xffffffffu, sum, 1);
        sum += __shfl_xor_sync(0xffffffffu, sum, 2);
        const float mu = sum * (1.f / 96.f);
        auto cen = [&](uint32_t u) { return pack_bf16(bf_lo(u) - mu, bf_hi(u) - mu); };
        uint8_t* dst = smem + SM_WO + (r * 4 + warp) * 128 + lane * 4;
#pragma unroll
        for (int j = 0; j < 3; j++) {
          *reinterpret_cast<uint32_t*>(dst + (4 * j + 0) * 1536) = cen(v[3 * r + j].x);
          *reinterpret_cast<uint32_t*>(dst + (4 * j + 1) * 1536) = cen(v[3 * r + j].y);
          *reinterpret_cast<uint32_t*>(dst + (4 * j + 2) * 1536) = cen(v[3 * r + j].z);
          *reinterpret_cast<uint32_t*>(dst + (4 * j + 3) * 1536) = cen(v[3 * r + j].w);
        }
      }
      fence_async();
      __syncwarp();
      if (elect_one()) { mbar_arrive(mbar + MB_TURN); mbar_arrive(mbar + MB_WOC); }
      __syncwarp();
    }
  }
  TL(1);
  mbar_wait(mbar + MB_WQK, 0);
  uint32_t xpar = 0;

  uint32_t wl = sb + SM_WIN + wg * NENT * 4;
  int win = lds_uniform(wl), nxt = lds_uniform(wl + 4);
  if (win >= 0) {
    const uint32_t wgb = sb + SM_WG + wg * WG_SZ, bar_x = mbar + MB_X + 8 * wg;
    const uint32_t t16 = (tid & 127) * 16;
    const uint32_t k_dst = wgb + WG_K + (tid & 16) * 448 + warp * 256 + (tid & 15) * 16;
    const uint32_t eb_base = sb + SM_EB + t16;
    uint4 mw[4];
    auto load_mask = [&](uint32_t off) {
      const char* src = mb + (off + t16);
#pragma unroll
      for (int i = 0; i < 4; i++) mw[i] = ldg128_stream(src + i * 2048);
    };
    auto mask_or = [&](uint32_t seed) {
      uint32_t r = seed & 0x80008000u;
#pragma unroll
      for (int i = 0; i < 4; i++) {
        asm("lop3.b32 %0, %0, %1, %2, 0xFE;" : "+r"(r) : "r"(mw[i].x), "r"(mw[i].y));
        asm("lop3.b32 %0, %0, %1, %2, 0xFE;" : "+r"(r) : "r"(mw[i].z), "r"(mw[i].w));
      }
      return r;
    };
    float qk[96];
    load_mask(mask_off(win));
    mbar_wait(bar_x, 0);
    TL(2);
    wg_fence();
    issue_qk(qk, mk_desc(WG_X, 16, 512, 2) + (wgb >> 4), mk_desc(sb + SM_W, 12288, 1024, 1)); wg_commit();
    if (warp == 0 && nxt >= 0 && elect_one()) prefetch_l2(mb + mask_off(nxt), 8192);
    __syncwarp();
    uint32_t mword = mask_or(0);
    TL(7);
    mbar_wait(mbar + MB_WV, 0);
    mbar_wait(mbar + MB_RDY, 0);
    TL(8);
    while (true) {
      const int nxt2 = lds_uniform(wl + 8);
      int tk = win >> 16;
      const bool more = nxt >= 0;
      const uint32_t z0 = wl >> 20, zw = z0 + (wgb >> 4);
      const uint64_t dX = opaque(mk_desc(WG_X, 16, 512, 2) + zw);
      TL(0);
      uint32_t qa[24];
      qkv_epilogue(qk, qa, dX, opaque(mk_desc(sb + SM_WV, 6144, 512, 2) + z0), k_dst);
      TL(5);
      const bool masked = bar_wg_or(BAR_KV + wg, (mword & 0x7FFF7FFFu) != 0u);
      TL(6);
      const uint64_t dK = opaque(mk_desc(WG_K, 1024, 128, 0) + zw), dV = opaque(mk_desc(WG_V, 128, 1024, 0) + zw);
      auto prefetch_next = [&]() {
        if (warp == 0 && more) {
          if (elect_one()) {
            load_x(&tm_x, &tm_xq, nxt, wg);
            if (nxt2 >= 0) prefetch_l2(mb + mask_off(nxt2), 8192);
          }
          __syncwarp();
        }
      };
      auto wait_turn = [&]() { if (tk != NO_TICKET) mbar_wait(mbar + MB_TURN + (tk & 3) * 8, (tk >> 2) & 1); };
      auto pass_turn = [&]() {
        asm volatile("{\n.reg .pred p, q;\nelect.sync _|p, 0xffffffff;\nsetp.ne.and.s32 q, %1, 255, p;\n@q mbarrier.arrive.shared::cta.b64 _, [%0];\n}\n"
                     :: "r"(mbar + MB_TURN + ((tk + 1) & 3) * 8), "r"(tk) : "memory");
      };
      auto next_qk = [&]() { issue_qk(qk, dX, opaque(mk_desc(sb + SM_W, 12288, 1024, 1) + z0)); wg_commit(); };
      auto tiles_ready = [&]() {
        if (elect_one()) mbar_arrive(bar_x + (MB_KV - MB_X));
        __syncwarp();
        const uint32_t par = (wl >> 2) & 1;
        mbar_wait(bar_x, par ^ 1);
        mbar_wait(bar_x + (MB_KV - MB_X), par);
      };
      uint32_t of[24];
      {
        float sA[32], sB[32], oA[16], oB[16], oC[16], oD[16];
        uint32_t pA[16], pB[16], pC[16], pD[16];
        wg_fence();
        issue_s<0>(sA, qa, dK);
        issue_s<1>(sB, qa, dK); wg_commit();
        load_eb(pA, eb_base);
        load_eb(pB, eb_base + 8192);
        uint32_t eb_hi = sb + SM_EB + 16384;
        if (__builtin_expect(!masked, 1)) {
          prefetch_next();
          wait_turn();
        } else {
          uint32_t mk[16];
          load_mask_frag(mk, mb + mask_off(win), t16);
          wait_turn(); pass_turn();
          tk = NO_TICKET;
          wg_wait<0>();
          if (bar_wg_or(BAR_AUX + wg, mask_unsafe(mk))) {
            if (t16 == 0) {
              uint32_t gl = sb + SM_GEN + wg * NENT * 4;
              while ((int)lds32(gl) >= 0) gl += 4;
              asm volatile("st.shared.u32 [%0], %1;" :: "r"(gl), "r"(win) : "memory");
            }
            __syncwarp();
            if (!more) break;
            prefetch_next();
            load_mask(mask_off(nxt));
            tiles_ready();
            wg_fence();
            next_qk();
            mword = mask_or(0);
            wl += 4;
            win = nxt; nxt = nxt2;
            continue;
          }
#pragma unroll
          for (int i = 0; i < 16; i++) {
            mk[i] = pack_bf16(ex2(bf_lo(mk[i]) * LOG2E), ex2(bf_hi(mk[i]) * LOG2E));
            pA[i] = hmul2(pA[i], mk[i]); pB[i] = hmul2(pB[i], mk[i]);
          }
#pragma unroll
          for (int j = 0; j < 8; j++) {
            const uint4 e = lds128(eb_base + 16384 + j * 2048);
            const int m = 4 * (j & 3), x = j & 1;
            asm volatile("st.shared.v4.u32 [%0], {%1,%2,%3,%4};" :: "r"(wgb + WG_X + t16 + j * 2048),
                         "r"(hmul2(e.x, mk[m + x])), "r"(hmul2(e.y, mk[m + (1 ^ x)])), "r"(hmul2(e.z, mk[m + (2 ^ x)])), "r"(hmul2(e.w, mk[m + (3 ^ x)])) : "memory");
          }
          eb_hi = wgb + WG_X;
        }
        wg_wait<0>(); fence_regs(sA); fence_regs(sB);
        TL(7);
        softmax_fast(sA, pA);
        wg_fence();
        issue_s<2>(sA, qa, dK); wg_commit();
        issue_pv<0>(oA, pA, dV); wg_commit();
        TL(8);
        softmax_fast(sB, pB);
        load_eb(pC, eb_hi + t16);
        wg_wait<1>(); fence_regs(sA);
        wg_fence();
        issue_s<3>(sB, qa, dK); wg_commit();
        issue_pv<1>(oB, pB, dV); wg_commit();
        TL(9);
        softmax_fast(sA, pC);
        pass_turn();
        load_eb(pD, eb_hi + t16 + 8192);
        wg_wait<1>(); fence_regs(sB); fence_regs(oA);
        wg_fence();
        issue_pv<2>(oC, pC, dV); wg_commit();
        TL(10);
        norm_o<0>(oA, of);
        softmax_fast(sB, pD);
        wg_fence();
        issue_pv<3>(oD, pD, dV); wg_commit();
        if (__builtin_expect(masked, 0)) {
          if (t16 >= 1024) asm volatile("st.shared.v4.u32 [%0], {%1,%1,%1,%1};" :: "r"(wgb + WG_K + 2048 + t16), "r"(0) : "memory");
          fence_async();
          bar_sync_n(BAR_AUX + wg, 128);
          prefetch_next();
        }
        if (more) load_mask(mask_off(nxt));
        else { mw[0] = mw[1] = mw[2] = mw[3] = make_uint4(0, 0, 0, 0); }
        wg_wait<1>(); fence_regs(oB); fence_regs(oC);
        norm_o<1>(oB, of + 6);
        norm_o<0>(oC, of + 12);
        wg_wait<0>(); fence_regs(oD);
        norm_o<1>(oD, of + 18);
      }
      TL(11);
      float y[48], var[4]; uint32_t yb[24];
      issue_out(y, of, opaque(mk_desc(sb + SM_WO, 128, 1536, 0) + z0));
      char* const optr = out_ptr(out, win, warp, t16);
      if (!more) { ln_head(y, yb, var, dV + 3 * 64); wg_wait<0>(); ln_tail(yb, var, optr); TL(14); break; }
      tiles_ready();
      ln_head(y, yb, var, dV + 3 * 64);
      TL(12);
      next_qk();
      wg_wait<1>();
      TL(13);
      mword = mask_or(ln_tail(yb, var, optr));
      if ((nxt >> 16) == NO_TICKET && t16 == 0) prefetch_l2(mb + mask_off(nxt), 8192);
      TL(14);
      wl += 4;
      win = nxt; nxt = nxt2;
    }
    xpar = ((wl >> 2) & 1) ^ 1;
    bar_sync_n(BAR_AUX + wg, 128);
    if (warp == 0 && elect_one()) {
      const int w = lds32(sb + SM_GEN + wg * NENT * 4);
      if (w >= 0) load_x(&tm_x, &tm_xq, w, wg);
    }
    __syncwarp();
  }
  general_windows(&tm_x, &tm_xq, mb, out, xpar);
  TG(15);
}

typedef CUresult (*EncodeFn)(CUtensorMap*, CUtensorMapDataType, cuuint32_t, void*, const cuuint64_t*, const cuuint64_t*,
                             const cuuint32_t*, const cuuint32_t*, CUtensorMapInterleave, CUtensorMapSwizzle,
                             CUtensorMapL2promotion, CUtensorMapFloatOOBfill);

}

extern "C" void kernel_launch(void* const* d_in, const int* in_sizes, int n_in, void* d_out, int out_size) {
  static int sms = 0;
  static EncodeFn encode = nullptr;
  if (sms == 0) {
    int dev = 0;
    cudaGetDevice(&dev);
    cudaDeviceGetAttribute(&sms, cudaDevAttrMultiProcessorCount, dev);
    if (sms < 96) sms = 96;
    cudaFuncSetAttribute(swin_kernel, cudaFuncAttributeMaxDynamicSharedMemorySize, SM_TOTAL);
    cudaDriverEntryPointQueryResult qr;
    void* fn = nullptr;
    cudaGetDriverEntryPoint("cuTensorMapEncodeTiled", &fn, cudaEnableDefault, &qr);
    encode = (EncodeFn)fn;
  }
  CUtensorMap tm_x, tm_xq, tm_wqk, tm_wv;
  {
    cuuint64_t dims[5] = {32, 4, IMG, IMG / 4, 3};
    cuuint64_t strides[4] = {PIXB, ROWB, 4 * PIXB, 64};
    cuuint32_t es[5] = {1, 1, 1, 1, 1};
    cuuint32_t box[5] = {32, 4, 8, 2, 3}, boxq[5] = {32, 4, 4, 1, 1};
    encode(&tm_x, CU_TENSOR_MAP_DATA_TYPE_BFLOAT16, 5, d_in[0], dims, strides, box, es, CU_TENSOR_MAP_INTERLEAVE_NONE,
           CU_TENSOR_MAP_SWIZZLE_64B, CU_TENSOR_MAP_L2_PROMOTION_L2_128B, CU_TENSOR_MAP_FLOAT_OOB_FILL_NONE);
    encode(&tm_xq, CU_TENSOR_MAP_DATA_TYPE_BFLOAT16, 5, d_in[0], dims, strides, boxq, es, CU_TENSOR_MAP_INTERLEAVE_NONE,
           CU_TENSOR_MAP_SWIZZLE_64B, CU_TENSOR_MAP_L2_PROMOTION_L2_128B, CU_TENSOR_MAP_FLOAT_OOB_FILL_NONE);
    cuuint64_t qd[3] = {64, 96, 3}, qs[2] = {576, 128}, vd[3] = {32, 96, 3}, vs[2] = {576, 64};
    cuuint32_t qb[3] = {64, 96, 3}, vb[3] = {32, 96, 3};
    encode(&tm_wqk, CU_TENSOR_MAP_DATA_TYPE_BFLOAT16, 3, d_in[1], qd, qs, qb, es, CU_TENSOR_MAP_INTERLEAVE_NONE,
           CU_TENSOR_MAP_SWIZZLE_128B, CU_TENSOR_MAP_L2_PROMOTION_L2_256B, CU_TENSOR_MAP_FLOAT_OOB_FILL_NONE);
    encode(&tm_wv, CU_TENSOR_MAP_DATA_TYPE_BFLOAT16, 3, (char*)d_in[1] + 384, vd, vs, vb, es, CU_TENSOR_MAP_INTERLEAVE_NONE,
           CU_TENSOR_MAP_SWIZZLE_64B, CU_TENSOR_MAP_L2_PROMOTION_L2_256B, CU_TENSOR_MAP_FLOAT_OOB_FILL_NONE);
  }
  swin_kernel<<<sms, 384, SM_TOTAL>>>(
      tm_x, tm_xq, tm_wqk, tm_wv, (const __nv_bfloat16*)d_in[2], (const __nv_bfloat16*)d_in[3],
      (const __nv_bfloat16*)d_in[4], (const __nv_bfloat16*)d_in[5], (const __nv_bfloat16*)d_in[6], (const int*)d_in[7],
      (const __nv_bfloat16*)d_in[8], (__nv_bfloat16*)d_out);
}
```

```cpp
#include <cuda_runtime.h>
#include <cuda.h>
#include <cuda_bf16.h>
#include <stdint.h>
#include <type_traits>

#define TOKEN 4
namespace {

constexpr int IMG   = 384;
constexpr int NWX   = 48;
constexpr int NWIN  = NWX * NWX;
constexpr int PIXB  = 192;
constexpr int ROWB  = IMG * PIXB;
constexpr float LOG2E = 1.4426950408889634f;
constexpr float TAU_FAST_MAX = 50.f;

constexpr int SM_W    = 0;
constexpr int SM_WV   = 3 * 12288;
constexpr int SM_WO   = SM_W + 9 * 6144;
constexpr int SM_EB   = SM_WO + 12 * 1536;
constexpr int SM_WG   = SM_EB + 32768;
constexpr int WG_X    = 0;
constexpr int WG_K    = 12288;
constexpr int WG_V    = WG_K + 14336;
constexpr int WG_SZ   = WG_V + 14336;
constexpr int SM_TAB  = SM_WG + WG_SZ + WG_V + 4096;
constexpr int SM_WOR  = SM_WG + 2 * WG_SZ + WG_K;
constexpr int SM_SEL  = SM_WG + 3 * WG_SZ;
constexpr int SM_MISC = SM_SEL + 256;
constexpr int SM_BAR  = SM_MISC + 16;
constexpr int SM_SLOW = SM_BAR + 104;
constexpr int SM_PAR  = SM_BAR + 160;
constexpr int NENT    = 10;
constexpr int SM_WIN  = SM_PAR + 192;
constexpr int SM_GEN  = SM_WIN + 3 * NENT * 4;
constexpr int SM_TOTAL = SM_GEN + 3 * NENT * 4;
static_assert((SM_WIN & 7) == 0 && (NENT & 1) == 0, "list parity");

template <int SD> __device__ __forceinline__ void wgmma_ss_n192_t1(float (&d)[96], uint64_t da, uint64_t db) {
  if constexpr (SD) {
    asm volatile("{\n.reg .pred p;\nsetp.ne.b32 p, 1, 0;\n"
      "wgmma.mma_async.sync.aligned.m64n192k16.f32.bf16.bf16 {%0, %1, %2, %3, %4, %5, %6, %7, %8, %9, %10, %11, %12, %13, %14, %15, %16, %17, %18, %19, %20, %21, %22, %23, %24, %25, %26, %27, %28, %29, %30, %31, %32, %33, %34, %35, %36, %37, %38, %39, %40, %41, %42, %43, %44, %45, %46, %47, %48, %49, %50, %51, %52, %53, %54, %55, %56, %57, %58, %59, %60, %61, %62, %63, %64, %65, %66, %67, %68, %69, %70, %71, %72, %73, %74, %75, %76, %77, %78, %79, %80, %81, %82, %83, %84, %85, %86, %87, %88, %89, %90, %91, %92, %93, %94, %95}, %96, %97, p, 1, 1, 0, 1;\n}\n"
      : "+f"(d[0]), "+f"(d[1]), "+f"(d[2]), "+f"(d[3]), "+f"(d[4]), "+f"(d[5]), "+f"(d[6]), "+f"(d[7]), "+f"(d[8]), "+f"(d[9]), "+f"(d[10]), "+f"(d[11]), "+f"(d[12]), "+f"(d[13]), "+f"(d[14]), "+f"(d[15]), "+f"(d[16]), "+f"(d[17]), "+f"(d[18]), "+f"(d[19]), "+f"(d[20]), "+f"(d[21]), "+f"(d[22]), "+f"(d[23]), "+f"(d[24]), "+f"(d[25]), "+f"(d[26]), "+f"(d[27]), "+f"(d[28]), "+f"(d[29]), "+f"(d[30]), "+f"(d[31]), "+f"(d[32]), "+f"(d[33]), "+f"(d[34]), "+f"(d[35]), "+f"(d[36]), "+f"(d[37]), "+f"(d[38]), "+f"(d[39]), "+f"(d[40]), "+f"(d[41]), "+f"(d[42]), "+f"(d[43]), "+f"(d[44]), "+f"(d[45]), "+f"(d[46]), "+f"(d[47]), "+f"(d[48]), "+f"(d[49]), "+f"(d[50]), "+f"(d[51]), "+f"(d[52]), "+f"(d[53]), "+f"(d[54]), "+f"(d[55]), "+f"(d[56]), "+f"(d[57]), "+f"(d[58]), "+f"(d[59]), "+f"(d[60]), "+f"(d[61]), "+f"(d[62]), "+f"(d[63]), "+f"(d[64]), "+f"(d[65]), "+f"(d[66]), "+f"(d[67]), "+f"(d[68]), "+f"(d[69]), "+f"(d[70]), "+f"(d[71]), "+f"(d[72]), "+f"(d[73]), "+f"(d[74]), "+f"(d[75]), "+f"(d[76]), "+f"(d[77]), "+f"(d[78]), "+f"(d[79]), "+f"(d[80]), "+f"(d[81]), "+f"(d[82]), "+f"(d[83]), "+f"(d[84]), "+f"(d[85]), "+f"(d[86]), "+f"(d[87]), "+f"(d[88]), "+f"(d[89]), "+f"(d[90]), "+f"(d[91]), "+f"(d[92]), "+f"(d[93]), "+f"(d[94]), "+f"(d[95])
      : "l"(da), "l"(db));
  } else {
    asm volatile("{\n.reg .pred p;\nsetp.ne.b32 p, 0, 0;\n"
      "wgmma.mma_async.sync.aligned.m64n192k16.f32.bf16.bf16 {%0, %1, %2, %3, %4, %5, %6, %7, %8, %9, %10, %11, %12, %13, %14, %15, %16, %17, %18, %19, %20, %21, %22, %23, %24, %25, %26, %27, %28, %29, %30, %31, %32, %33, %34, %35, %36, %37, %38, %39, %40, %41, %42, %43, %44, %45, %46, %47, %48, %49, %50, %51, %52, %53, %54, %55, %56, %57, %58, %59, %60, %61, %62, %63, %64, %65, %66, %67, %68, %69, %70, %71, %72, %73, %74, %75, %76, %77, %78, %79, %80, %81, %82, %83, %84, %85, %86, %87, %88, %89, %90, %91, %92, %93, %94, %95}, %96, %97, p, 1, 1, 0, 1;\n}\n"
      : "=f"(d[0]), "=f"(d[1]), "=f"(d[2]), "=f"(d[3]), "=f"(d[4]), "=f"(d[5]), "=f"(d[6]), "=f"(d[7]), "=f"(d[8]), "=f"(d[9]), "=f"(d[10]), "=f"(d[11]), "=f"(d[12]), "=f"(d[13]), "=f"(d[14]), "=f"(d[15]), "=f"(d[16]), "=f"(d[17]), "=f"(d[18]), "=f"(d[19]), "=f"(d[20]), "=f"(d[21]), "=f"(d[22]), "=f"(d[23]), "=f"(d[24]), "=f"(d[25]), "=f"(d[26]), "=f"(d[27]), "=f"(d[28]), "=f"(d[29]), "=f"(d[30]), "=f"(d[31]), "=f"(d[32]), "=f"(d[33]), "=f"(d[34]), "=f"(d[35]), "=f"(d[36]), "=f"(d[37]), "=f"(d[38]), "=f"(d[39]), "=f"(d[40]), "=f"(d[41]), "=f"(d[42]), "=f"(d[43]), "=f"(d[44]), "=f"(d[45]), "=f"(d[46]), "=f"(d[47]), "=f"(d[48]), "=f"(d[49]), "=f"(d[50]), "=f"(d[51]), "=f"(d[52]), "=f"(d[53]), "=f"(d[54]), "=f"(d[55]), "=f"(d[56]), "=f"(d[57]), "=f"(d[58]), "=f"(d[59]), "=f"(d[60]), "=f"(d[61]), "=f"(d[62]), "=f"(d[63]), "=f"(d[64]), "=f"(d[65]), "=f"(d[66]), "=f"(d[67]), "=f"(d[68]), "=f"(d[69]), "=f"(d[70]), "=f"(d[71]), "=f"(d[72]), "=f"(d[73]), "=f"(d[74]), "=f"(d[75]), "=f"(d[76]), "=f"(d[77]), "=f"(d[78]), "=f"(d[79]), "=f"(d[80]), "=f"(d[81]), "=f"(d[82]), "=f"(d[83]), "=f"(d[84]), "=f"(d[85]), "=f"(d[86]), "=f"(d[87]), "=f"(d[88]), "=f"(d[89]), "=f"(d[90]), "=f"(d[91]), "=f"(d[92]), "=f"(d[93]), "=f"(d[94]), "=f"(d[95])
      : "l"(da), "l"(db));
  }
}
template <int SD> __device__ __forceinline__ void wgmma_ss_n96_t1(float (&d)[48], uint64_t da, uint64_t db) {
  if constexpr (SD) {
    asm volatile("{\n.reg .pred p;\nsetp.ne.b32 p, 1, 0;\n"
      "wgmma.mma_async.sync.aligned.m64n96k16.f32.bf16.bf16 {%0, %1, %2, %3, %4, %5, %6, %7, %8, %9, %10, %11, %12, %13, %14, %15, %16, %17, %18, %19, %20, %21, %22, %23, %24, %25, %26, %27, %28, %29, %30, %31, %32, %33, %34, %35, %36, %37, %38, %39, %40, %41, %42, %43, %44, %45, %46, %47}, %48, %49, p, 1, 1, 0, 1;\n}\n"
      : "+f"(d[0]), "+f"(d[1]), "+f"(d[2]), "+f"(d[3]), "+f"(d[4]), "+f"(d[5]), "+f"(d[6]), "+f"(d[7]), "+f"(d[8]), "+f"(d[9]), "+f"(d[10]), "+f"(d[11]), "+f"(d[12]), "+f"(d[13]), "+f"(d[14]), "+f"(d[15]), "+f"(d[16]), "+f"(d[17]), "+f"(d[18]), "+f"(d[19]), "+f"(d[20]), "+f"(d[21]), "+f"(d[22]), "+f"(d[23]), "+f"(d[24]), "+f"(d[25]), "+f"(d[26]), "+f"(d[27]), "+f"(d[28]), "+f"(d[29]), "+f"(d[30]), "+f"(d[31]), "+f"(d[32]), "+f"(d[33]), "+f"(d[34]), "+f"(d[35]), "+f"(d[36]), "+f"(d[37]), "+f"(d[38]), "+f"(d[39]), "+f"(d[40]), "+f"(d[41]), "+f"(d[42]), "+f"(d[43]), "+f"(d[44]), "+f"(d[45]), "+f"(d[46]), "+f"(d[47])
      : "l"(da), "l"(db));
  } else {
    asm volatile("{\n.reg .pred p;\nsetp.ne.b32 p, 0, 0;\n"
      "wgmma.mma_async.sync.aligned.m64n96k16.f32.bf16.bf16 {%0, %1, %2, %3, %4, %5, %6, %7, %8, %9, %10, %11, %12, %13, %14, %15, %16, %17, %18, %19, %20, %21, %22, %23, %24, %25, %26, %27, %28, %29, %30, %31, %32, %33, %34, %35, %36, %37, %38, %39, %40, %41, %42, %43, %44, %45, %46, %47}, %48, %49, p, 1, 1, 0, 1;\n}\n"
      : "=f"(d[0]), "=f"(d[1]), "=f"(d[2]), "=f"(d[3]), "=f"(d[4]), "=f"(d[5]), "=f"(d[6]), "=f"(d[7]), "=f"(d[8]), "=f"(d[9]), "=f"(d[10]), "=f"(d[11]), "=f"(d[12]), "=f"(d[13]), "=f"(d[14]), "=f"(d[15]), "=f"(d[16]), "=f"(d[17]), "=f"(d[18]), "=f"(d[19]), "=f"(d[20]), "=f"(d[21]), "=f"(d[22]), "=f"(d[23]), "=f"(d[24]), "=f"(d[25]), "=f"(d[26]), "=f"(d[27]), "=f"(d[28]), "=f"(d[29]), "=f"(d[30]), "=f"(d[31]), "=f"(d[32]), "=f"(d[33]), "=f"(d[34]), "=f"(d[35]), "=f"(d[36]), "=f"(d[37]), "=f"(d[38]), "=f"(d[39]), "=f"(d[40]), "=f"(d[41]), "=f"(d[42]), "=f"(d[43]), "=f"(d[44]), "=f"(d[45]), "=f"(d[46]), "=f"(d[47])
      : "l"(da), "l"(db));
  }
}
template <int SD> __device__ __forceinline__ void wgmma_rs_n96_t1(float (&d)[48], uint32_t a0, uint32_t a1, uint32_t a2, uint32_t a3, uint64_t db) {
  if constexpr (SD) {
    asm volatile("{\n.reg .pred p;\nsetp.ne.b32 p, 1, 0;\n"
      "wgmma.mma_async.sync.aligned.m64n96k16.f32.bf16.bf16 {%0, %1, %2, %3, %4, %5, %6, %7, %8, %9, %10, %11, %12, %13, %14, %15, %16, %17, %18, %19, %20, %21, %22, %23, %24, %25, %26, %27, %28, %29, %30, %31, %32, %33, %34, %35, %36, %37, %38, %39, %40, %41, %42, %43, %44, %45, %46, %47}, {%48, %49, %50, %51}, %52, p, 1, 1, 1;\n}\n"
      : "+f"(d[0]), "+f"(d[1]), "+f"(d[2]), "+f"(d[3]), "+f"(d[4]), "+f"(d[5]), "+f"(d[6]), "+f"(d[7]), "+f"(d[8]), "+f"(d[9]), "+f"(d[10]), "+f"(d[11]), "+f"(d[12]), "+f"(d[13]), "+f"(d[14]), "+f"(d[15]), "+f"(d[16]), "+f"(d[17]), "+f"(d[18]), "+f"(d[19]), "+f"(d[20]), "+f"(d[21]), "+f"(d[22]), "+f"(d[23]), "+f"(d[24]), "+f"(d[25]), "+f"(d[26]), "+f"(d[27]), "+f"(d[28]), "+f"(d[29]), "+f"(d[30]), "+f"(d[31]), "+f"(d[32]), "+f"(d[33]), "+f"(d[34]), "+f"(d[35]), "+f"(d[36]), "+f"(d[37]), "+f"(d[38]), "+f"(d[39]), "+f"(d[40]), "+f"(d[41]), "+f"(d[42]), "+f"(d[43]), "+f"(d[44]), "+f"(d[45]), "+f"(d[46]), "+f"(d[47])
      : "r"(a0), "r"(a1), "r"(a2), "r"(a3), "l"(db));
  } else {
    asm volatile("{\n.reg .pred p;\nsetp.ne.b32 p, 0, 0;\n"
      "wgmma.mma_async.sync.aligned.m64n96k16.f32.bf16.bf16 {%0, %1, %2, %3, %4, %5, %6, %7, %8, %9, %10, %11, %12, %13, %14, %15, %16, %17, %18, %19, %20, %21, %22, %23, %24, %25, %26, %27, %28, %29, %30, %31, %32, %33, %34, %35, %36, %37, %38, %39, %40, %41, %42, %43, %44, %45, %46, %47}, {%48, %49, %50, %51}, %52, p, 1, 1, 1;\n}\n"
      : "=f"(d[0]), "=f"(d[1]), "=f"(d[2]), "=f"(d[3]), "=f"(d[4]), "=f"(d[5]), "=f"(d[6]), "=f"(d[7]), "=f"(d[8]), "=f"(d[9]), "=f"(d[10]), "=f"(d[11]), "=f"(d[12]), "=f"(d[13]), "=f"(d[14]), "=f"(d[15]), "=f"(d[16]), "=f"(d[17]), "=f"(d[18]), "=f"(d[19]), "=f"(d[20]), "=f"(d[21]), "=f"(d[22]), "=f"(d[23]), "=f"(d[24]), "=f"(d[25]), "=f"(d[26]), "=f"(d[27]), "=f"(d[28]), "=f"(d[29]), "=f"(d[30]), "=f"(d[31]), "=f"(d[32]), "=f"(d[33]), "=f"(d[34]), "=f"(d[35]), "=f"(d[36]), "=f"(d[37]), "=f"(d[38]), "=f"(d[39]), "=f"(d[40]), "=f"(d[41]), "=f"(d[42]), "=f"(d[43]), "=f"(d[44]), "=f"(d[45]), "=f"(d[46]), "=f"(d[47])
      : "r"(a0), "r"(a1), "r"(a2), "r"(a3), "l"(db));
  }
}
template <int SD> __device__ __forceinline__ void wgmma_rs_n64_t0(float (&d)[32], uint32_t a0, uint32_t a1, uint32_t a2, uint32_t a3, uint64_t db) {
  if constexpr (SD) {
    asm volatile("{\n.reg .pred p;\nsetp.ne.b32 p, 1, 0;\n"
      "wgmma.mma_async.sync.aligned.m64n64k16.f32.bf16.bf16 {%0, %1, %2, %3, %4, %5, %6, %7, %8, %9, %10, %11, %12, %13, %14, %15, %16, %17, %18, %19, %20, %21, %22, %23, %24, %25, %26, %27, %28, %29, %30, %31}, {%32, %33, %34, %35}, %36, p, 1, 1, 0;\n}\n"
      : "+f"(d[0]), "+f"(d[1]), "+f"(d[2]), "+f"(d[3]), "+f"(d[4]), "+f"(d[5]), "+f"(d[6]), "+f"(d[7]), "+f"(d[8]), "+f"(d[9]), "+f"(d[10]), "+f"(d[11]), "+f"(d[12]), "+f"(d[13]), "+f"(d[14]), "+f"(d[15]), "+f"(d[16]), "+f"(d[17]), "+f"(d[18]), "+f"(d[19]), "+f"(d[20]), "+f"(d[21]), "+f"(d[22]), "+f"(d[23]), "+f"(d[24]), "+f"(d[25]), "+f"(d[26]), "+f"(d[27]), "+f"(d[28]), "+f"(d[29]), "+f"(d[30]), "+f"(d[31])
      : "r"(a0), "r"(a1), "r"(a2), "r"(a3), "l"(db));
  } else {
    asm volatile("{\n.reg .pred p;\nsetp.ne.b32 p, 0, 0;\n"
      "wgmma.mma_async.sync.aligned.m64n64k16.f32.bf16.bf16 {%0, %1, %2, %3, %4, %5, %6, %7, %8, %9, %10, %11, %12, %13, %14, %15, %16, %17, %18, %19, %20, %21, %22, %23, %24, %25, %26, %27, %28, %29, %30, %31}, {%32, %33, %34, %35}, %36, p, 1, 1, 0;\n}\n"
      : "=f"(d[0]), "=f"(d[1]), "=f"(d[2]), "=f"(d[3]), "=f"(d[4]), "=f"(d[5]), "=f"(d[6]), "=f"(d[7]), "=f"(d[8]), "=f"(d[9]), "=f"(d[10]), "=f"(d[11]), "=f"(d[12]), "=f"(d[13]), "=f"(d[14]), "=f"(d[15]), "=f"(d[16]), "=f"(d[17]), "=f"(d[18]), "=f"(d[19]), "=f"(d[20]), "=f"(d[21]), "=f"(d[22]), "=f"(d[23]), "=f"(d[24]), "=f"(d[25]), "=f"(d[26]), "=f"(d[27]), "=f"(d[28]), "=f"(d[29]), "=f"(d[30]), "=f"(d[31])
      : "r"(a0), "r"(a1), "r"(a2), "r"(a3), "l"(db));
  }
}
template <int SD> __device__ __forceinline__ void wgmma_rs_n32_t1(float (&d)[16], uint32_t a0, uint32_t a1, uint32_t a2, uint32_t a3, uint64_t db) {
  if constexpr (SD) {
    asm volatile("{\n.reg .pred p;\nsetp.ne.b32 p, 1, 0;\n"
      "wgmma.mma_async.sync.aligned.m64n32k16.f32.bf16.bf16 {%0, %1, %2, %3, %4, %5, %6, %7, %8, %9, %10, %11, %12, %13, %14, %15}, {%16, %17, %18, %19}, %20, p, 1, 1, 1;\n}\n"
      : "+f"(d[0]), "+f"(d[1]), "+f"(d[2]), "+f"(d[3]), "+f"(d[4]), "+f"(d[5]), "+f"(d[6]), "+f"(d[7]), "+f"(d[8]), "+f"(d[9]), "+f"(d[10]), "+f"(d[11]), "+f"(d[12]), "+f"(d[13]), "+f"(d[14]), "+f"(d[15])
      : "r"(a0), "r"(a1), "r"(a2), "r"(a3), "l"(db));
  } else {
    asm volatile("{\n.reg .pred p;\nsetp.ne.b32 p, 0, 0;\n"
      "wgmma.mma_async.sync.aligned.m64n32k16.f32.bf16.bf16 {%0, %1, %2, %3, %4, %5, %6, %7, %8, %9, %10, %11, %12, %13, %14, %15}, {%16, %17, %18, %19}, %20, p, 1, 1, 1;\n}\n"
      : "=f"(d[0]), "=f"(d[1]), "=f"(d[2]), "=f"(d[3]), "=f"(d[4]), "=f"(d[5]), "=f"(d[6]), "=f"(d[7]), "=f"(d[8]), "=f"(d[9]), "=f"(d[10]), "=f"(d[11]), "=f"(d[12]), "=f"(d[13]), "=f"(d[14]), "=f"(d[15])
      : "r"(a0), "r"(a1), "r"(a2), "r"(a3), "l"(db));
  }
}
template <int SD> __device__ __forceinline__ void wgmma_rs_n8_t0(float (&d)[4], uint32_t a0, uint32_t a1, uint32_t a2, uint32_t a3, uint64_t db) {
  if constexpr (SD) {
    asm volatile("{\n.reg .pred p;\nsetp.ne.b32 p, 1, 0;\n"
      "wgmma.mma_async.sync.aligned.m64n8k16.f32.bf16.bf16 {%0, %1, %2, %3}, {%4, %5, %6, %7}, %8, p, 1, 1, 0;\n}\n"
      : "+f"(d[0]), "+f"(d[1]), "+f"(d[2]), "+f"(d[3])
      : "r"(a0), "r"(a1), "r"(a2), "r"(a3), "l"(db));
  } else {
    asm volatile("{\n.reg .pred p;\nsetp.ne.b32 p, 0, 0;\n"
      "wgmma.mma_async.sync.aligned.m64n8k16.f32.bf16.bf16 {%0, %1, %2, %3}, {%4, %5, %6, %7}, %8, p, 1, 1, 0;\n}\n"
      : "=f"(d[0]), "=f"(d[1]), "=f"(d[2]), "=f"(d[3])
      : "r"(a0), "r"(a1), "r"(a2), "r"(a3), "l"(db));
  }
}

__device__ __forceinline__ void wg_fence()  { asm volatile("wgmma.fence.sync.aligned;" ::: "memory"); }
__device__ __forceinline__ void wg_commit() { asm volatile("wgmma.commit_group.sync.aligned;" ::: "memory"); }
template <int N> __device__ __forceinline__ void wg_wait() { asm volatile("wgmma.wait_group.sync.aligned %0;" :: "n"(N) : "memory"); }
template <int N> __device__ __forceinline__ void fence_regs(float (&d)[N]) {
#pragma unroll
  for (int i = 0; i < N; i++) asm volatile("" : "+f"(d[i]) :: "memory");
}
__device__ __forceinline__ constexpr uint64_t mk_desc(uint32_t addr, uint32_t lbo, uint32_t sbo, uint32_t swz) {
  return (uint64_t)(addr >> 4) | ((uint64_t)(lbo >> 4) << 16) | ((uint64_t)(sbo >> 4) << 32) | ((uint64_t)swz << 62);
}
__device__ __forceinline__ uint32_t pack_bf16(float lo, float hi) {
  uint32_t r; asm("cvt.rn.bf16x2.f32 %0, %1, %2;" : "=r"(r) : "f"(hi), "f"(lo)); return r;
}
__device__ __forceinline__ uint32_t hmul2(uint32_t a, uint32_t b) {
  uint32_t r; asm("mul.rn.bf16x2 %0, %1, %2;" : "=r"(r) : "r"(a), "r"(b)); return r;
}
template <int HI> __device__ __forceinline__ uint32_t hmul2_b(uint32_t a, uint32_t b) {
  uint32_t r;
  if (HI) asm("{\n.reg .b16 l, h;\n.reg .b32 t;\nmov.b32 {l, h}, %2;\nmov.b32 t, {h, h};\nmul.rn.bf16x2 %0, %1, t;\n}\n" : "=r"(r) : "r"(a), "r"(b));
  else    asm("{\n.reg .b16 l, h;\n.reg .b32 t;\nmov.b32 {l, h}, %2;\nmov.b32 t, {l, l};\nmul.rn.bf16x2 %0, %1, t;\n}\n" : "=r"(r) : "r"(a), "r"(b));
  return r;
}
__device__ __forceinline__ uint32_t hfma2(uint32_t a, uint32_t b, uint32_t c) {
  uint32_t r; asm("fma.rn.bf16x2 %0, %1, %2, %3;" : "=r"(r) : "r"(a), "r"(b), "r"(c)); return r;
}
__device__ __forceinline__ float ex2(float x) { float r; asm("ex2.approx.ftz.f32 %0, %1;" : "=f"(r) : "f"(x)); return r; }
__device__ __forceinline__ float rsq(float x) { float r; asm("rsqrt.approx.ftz.f32 %0, %1;" : "=f"(r) : "f"(x)); return r; }
__device__ __forceinline__ float rcp(float x) { float r; asm("rcp.approx.ftz.f32 %0, %1;" : "=f"(r) : "f"(x)); return r; }
__device__ __forceinline__ void stsm4(uint32_t addr, uint32_t r0, uint32_t r1, uint32_t r2, uint32_t r3) {
  asm volatile("stmatrix.sync.aligned.m8n8.x4.shared.b16 [%0], {%1,%2,%3,%4};" :: "r"(addr), "r"(r0), "r"(r1), "r"(r2), "r"(r3) : "memory");
}
__device__ __forceinline__ void fence_async() { asm volatile("fence.proxy.async.shared::cta;" ::: "memory"); }
__device__ __forceinline__ void bar_sync_n(int id, int n) { asm volatile("bar.sync %0, %1;" :: "r"(id), "r"(n) : "memory"); }
__device__ __forceinline__ void bar_arrive_n(int id, int n) { asm volatile("bar.arrive %0, %1;" :: "r"(id), "r"(n) : "memory"); }
__device__ __forceinline__ bool bar_wg_or(int id, bool v) {
  uint32_t r;
  asm volatile("{\n.reg .pred p, q;\nsetp.ne.u32 q, %2, 0;\nbar.red.or.pred p, %1, 128, q;\nselp.u32 %0, 0, 1, p;\n}\n"
               : "=r"(r) : "r"(id), "r"((uint32_t)v) : "memory");
  return __ballot_sync(0xffffffffu, r != 0) == 0;
}
__device__ __forceinline__ void mbar_init(uint32_t bar, uint32_t cnt) { asm volatile("mbarrier.init.shared::cta.b64 [%0], %1;" :: "r"(bar), "r"(cnt) : "memory"); }
__device__ __forceinline__ void mbar_expect(uint32_t bar, uint32_t bytes) {
  asm volatile("mbarrier.arrive.expect_tx.shared::cta.b64 _, [%0], %1;" :: "r"(bar), "r"(bytes) : "memory");
}
__device__ __forceinline__ void mbar_arrive(uint32_t bar) { asm volatile("mbarrier.arrive.shared::cta.b64 _, [%0];" :: "r"(bar) : "memory"); }
__device__ __forceinline__ void mbar_wait(uint32_t bar, uint32_t parity) {
  asm volatile("{\n.reg .pred p;\n.reg .u32 n;\nmov.u32 n, 0;\n"
               "LW_%=:\nmbarrier.try_wait.parity.shared::cta.b64 p, [%0], %1;\n@p bra.uni LD_%=;\n"
               "add.u32 n, n, 1;\nsetp.lt.u32 p, n, 4194304;\n@p bra.uni LW_%=;\ntrap;\nLD_%=:\n}\n"
               :: "r"(bar), "r"(parity) : "memory");
}
__device__ __forceinline__ void tma5(uint32_t dst, const CUtensorMap* m, uint32_t bar, int c0, int c1, int c2, int c3, int c4) {
  asm volatile("cp.async.bulk.tensor.5d.shared::cluster.global.mbarrier::complete_tx::bytes [%0], [%1, {%3, %4, %5, %6, %7}], [%2];"
               :: "r"(dst), "l"(m), "r"(bar), "r"(c0), "r"(c1), "r"(c2), "r"(c3), "r"(c4) : "memory");
}
__device__ __forceinline__ void tma3(uint32_t dst, const CUtensorMap* m, uint32_t bar, int c0, int c1, int c2) {
  asm volatile("cp.async.bulk.tensor.3d.shared::cluster.global.mbarrier::complete_tx::bytes [%0], [%1, {%3, %4, %5}], [%2];"
               :: "r"(dst), "l"(m), "r"(bar), "r"(c0), "r"(c1), "r"(c2) : "memory");
}
__device__ __forceinline__ void bulk_g2s(uint32_t dst, const void* src, uint32_t bytes, uint32_t bar) {
  asm volatile("cp.async.bulk.shared::cluster.global.mbarrier::complete_tx::bytes [%0], [%1], %2, [%3];"
               :: "r"(dst), "l"(src), "r"(bytes), "r"(bar) : "memory");
}
__device__ __forceinline__ uint32_t lds32(uint32_t addr) {
  uint32_t v; asm volatile("ld.shared.u32 %0, [%1];" : "=r"(v) : "r"(addr)); return v;
}
__device__ __forceinline__ uint64_t opaque(uint64_t v) { asm volatile("" : "+l"(v)); return v; }
__device__ __forceinline__ uint4 lds128(uint32_t addr) {
  uint4 v; asm volatile("ld.shared.v4.u32 {%0,%1,%2,%3}, [%4];" : "=r"(v.x), "=r"(v.y), "=r"(v.z), "=r"(v.w) : "r"(addr)); return v;
}
__device__ __forceinline__ uint4 ldg128_stream(const void* p) {
  uint4 v; asm volatile("ld.global.nc.L1::no_allocate.v4.u32 {%0,%1,%2,%3}, [%4];" : "=r"(v.x), "=r"(v.y), "=r"(v.z), "=r"(v.w) : "l"(p)); return v;
}
__device__ __forceinline__ void stg128(void* p, uint32_t a, uint32_t b, uint32_t c, uint32_t d) {
  asm volatile("st.global.v4.u32 [%0], {%1,%2,%3,%4};" :: "l"(p), "r"(a), "r"(b), "r"(c), "r"(d) : "memory");
}
__device__ __forceinline__ void prefetch_l2(const void* p, uint32_t bytes) {
  asm volatile("cp.async.bulk.prefetch.L2.global [%0], %1;" :: "l"(p), "r"(bytes) : "memory");
}
__device__ __forceinline__ bool elect_one() {
  uint32_t r; asm volatile("{\n.reg .pred p;\nelect.sync _|p, 0xffffffff;\nselp.u32 %0, 1, 0, p;\n}\n" : "=r"(r)); return r != 0;
}
__device__ __forceinline__ float bf_lo(uint32_t u) { return __uint_as_float(u << 16); }
__device__ __forceinline__ float bf_hi(uint32_t u) { return __uint_as_float(u & 0xFFFF0000u); }
__device__ __forceinline__ float rbf(float x) { return bf_lo(pack_bf16(x, 0.f)); }
__device__ __forceinline__ int orig_tok(int r) { return ((r & 31) >> 2) * 8 + (r >> 5) * 4 + (r & 3); }

__device__ __forceinline__ int slot_window(int s, bool g132) {
  const int A0 = g132 ? 396 + 264 + 60 : 47 * 47, A1 = A0 + 72, B0 = g132 ? 3 * 396 + 264 + 60 : A1, B1 = B0 + 23;
  const int i = s - (s >= B1 ? 95 : s >= A1 ? 72 : 0);
  const int k = s >= B0 ? s - B0 + 72 : s - A0;
  const bool border = (s >= A0 && s < A1) || (s >= B0 && s < B1);
  const int iy = (i * 2789) >> 17;
  return border ? (k < 48 ? (47 << 8 | k) : ((k - 48) << 8 | 47)) : (iy << 8 | (i - iy * 47));
}

#define EB_WORD(e, j, a) ((((a) ^ ((j) & 1)) == 0) ? (e).x : (((a) ^ ((j) & 1)) == 1) ? (e).y : (((a) ^ ((j) & 1)) == 2) ? (e).z : (e).w)

__device__ __forceinline__ void load_eb(uint32_t (&e)[16], uint32_t eb_addr) {
#pragma unroll
  for (int j = 0; j < 4; j++) {
    const uint4 v = lds128(eb_addr + j * 2048);
#pragma unroll
    for (int a = 0; a < 4; a++) e[4 * j + a] = EB_WORD(v, j, a);
  }
}
__device__ __forceinline__ void softmax_fast(const float (&s)[32], uint32_t (&p)[16]) {
#pragma unroll
  for (int i = 0; i < 16; i++) p[i] = hmul2(pack_bf16(ex2(s[2 * i]), ex2(s[2 * i + 1])), p[i]);
}
__device__ __forceinline__ uint32_t hmax2(uint32_t a, uint32_t b) {
  uint32_t r; asm("max.bf16x2 %0, %1, %2;" : "=r"(r) : "r"(a), "r"(b)); return r;
}
__device__ __forceinline__ uint32_t hmax2_nan(uint32_t a, uint32_t b) {
  uint32_t r; asm("max.NaN.bf16x2 %0, %1, %2;" : "=r"(r) : "r"(a), "r"(b)); return r;
}
__device__ __forceinline__ float quad_max(float m) {
  m = fmaxf(m, __shfl_xor_sync(0xffffffffu, m, 1));
  return fmaxf(m, __shfl_xor_sync(0xffffffffu, m, 2));
}
__device__ __forceinline__ void softmax_true_max(const float (&s)[32], uint32_t (&p)[16]) {
  float m0 = s[0], m1 = s[2];
#pragma unroll
  for (int g = 0; g < 8; g++) {
    m0 = fmaxf(m0, fmaxf(s[4 * g + 0], s[4 * g + 1]));
    m1 = fmaxf(m1, fmaxf(s[4 * g + 2], s[4 * g + 3]));
  }
  m0 = quad_max(m0); m1 = quad_max(m1);
  uint32_t n0 = 0, n1 = 0;
#pragma unroll
  for (int g = 0; g < 8; g++) {
    p[2 * g + 0] = hmul2(pack_bf16(ex2(s[4 * g + 0] - m0), ex2(s[4 * g + 1] - m0)), p[2 * g + 0]);
    p[2 * g + 1] = hmul2(pack_bf16(ex2(s[4 * g + 2] - m1), ex2(s[4 * g + 3] - m1)), p[2 * g + 1]);
    n0 = hmax2(n0, p[2 * g]); n1 = hmax2(n1, p[2 * g + 1]);
  }
  const uint32_t r = pack_bf16(rcp(quad_max(fmaxf(bf_lo(n0), bf_hi(n0)))), rcp(quad_max(fmaxf(bf_lo(n1), bf_hi(n1)))));
#pragma unroll
  for (int g = 0; g < 8; g++) { p[2 * g] = hmul2_b<0>(p[2 * g], r); p[2 * g + 1] = hmul2_b<1>(p[2 * g + 1], r); }
}
template <int H> __device__ __forceinline__ void issue_s(float (&s)[32], const uint32_t (&q)[24], uint64_t dK) {
  constexpr int Q0 = (H == 0 ? 0 : H == 1 ? 4 : H == 2 ? 12 : 16), P0 = (H == 0 ? 0 : H == 1 ? 3 : H == 2 ? 7 : 10);
  wgmma_rs_n64_t0<0>(s, q[Q0], q[Q0 + 1], q[Q0 + 2], q[Q0 + 3], dK + P0 * 64);
  wgmma_rs_n64_t0<1>(s, q[Q0 + 4], q[Q0 + 5], q[Q0 + 6], q[Q0 + 7], dK + P0 * 64 + 128);
}
template <int H> __device__ __forceinline__ void issue_pv(float (&o)[16], const uint32_t (&p)[16], uint64_t dV) {
  constexpr int P0 = (H == 0 ? 0 : H == 1 ? 3 : H == 2 ? 7 : 10);
  wgmma_rs_n32_t1<0>(o, p[0], p[1], p[2], p[3], dV + P0 * 64);
  wgmma_rs_n32_t1<1>(o, p[4], p[5], p[6], p[7], dV + P0 * 64 + 16);
  wgmma_rs_n32_t1<1>(o, p[8], p[9], p[10], p[11], dV + P0 * 64 + 32);
  wgmma_rs_n32_t1<1>(o, p[12], p[13], p[14], p[15], dV + P0 * 64 + 48);
}
__device__ __forceinline__ void issue_proj(float (&d)[48], uint64_t dX, uint64_t dW) {
#pragma unroll
  for (int s = 0; s < 6; s++) {
    const uint64_t a = dX + (s >> 1) * 256 + (s & 1) * 2, b = dW + s * 64;
    if (s == 0) wgmma_ss_n96_t1<0>(d, a, b); else wgmma_ss_n96_t1<1>(d, a, b);
  }
}
__device__ __forceinline__ void issue_qk(float (&d)[96], uint64_t dX, uint64_t dW) {
#pragma unroll
  for (int s = 0; s < 6; s++) {
    const uint64_t a = dX + (s >> 1) * 256 + (s & 1) * 2, b = dW + s * 128;
    if (s == 0) wgmma_ss_n192_t1<0>(d, a, b); else wgmma_ss_n192_t1<1>(d, a, b);
  }
}
__device__ __forceinline__ void pack_sumsq(const float* a, uint32_t (&f)[24], uint32_t (&sq)[8], uint32_t init) {
#pragma unroll
  for (int i = 0; i < 24; i++) f[i] = pack_bf16(a[2 * i], a[2 * i + 1]);
#pragma unroll
  for (int h = 0; h < 4; h++)
#pragma unroll
    for (int r = 0; r < 2; r++) {
      uint32_t u = f[6 * h + r], v = f[6 * h + 2 + r], w = f[6 * h + 4 + r];
      sq[2 * h + r] = hfma2(w, w, hfma2(v, v, hfma2(u, u, init)));
    }
}
__device__ __forceinline__ void scale_heads(uint32_t (&f)[24], const float (&r)[8]) {
#pragma unroll
  for (int h = 0; h < 4; h++) {
    const uint32_t p = pack_bf16(r[2 * h], r[2 * h + 1]);
#pragma unroll
    for (int c = 0; c < 3; c++) {
      f[6 * h + 2 * c] = hmul2_b<0>(f[6 * h + 2 * c], p);
      f[6 * h + 2 * c + 1] = hmul2_b<1>(f[6 * h + 2 * c + 1], p);
    }
  }
}
template <int ODD> __device__ __forceinline__ void norm_o(const float (&o)[16], uint32_t* of) {
  constexpr int SO = ODD ? 0 : 12, VO = ODD ? 4 : 0;
  const uint32_t p = pack_bf16(rcp(o[SO]), rcp(o[SO + 2]));
#pragma unroll
  for (int g = 0; g < 3; g++) {
    of[2 * g + 0] = hmul2_b<0>(pack_bf16(o[VO + 4 * g + 0], o[VO + 4 * g + 1]), p);
    of[2 * g + 1] = hmul2_b<1>(pack_bf16(o[VO + 4 * g + 2], o[VO + 4 * g + 3]), p);
  }
}

#define TL(i)
#define TG(i)

constexpr int BAR_KV = 1;
constexpr int BAR_AUX = 4;
constexpr int BAR_TAB = 7, BAR_SETUP = 8, BAR_PAR = 9;
constexpr int NO_TICKET = 0xFF;
#define TPOS 3
#define ORDER 2
#define BORDER_EXTRA 1
constexpr int MB_WQK = 0, MB_X = 8, MB_KV = 32, MB_WV = 56, MB_WO = 64, MB_TURN = 72, MB_RDY = 128, MB_WOC = 136;
constexpr uint32_t sb = 1024, mbar = sb + SM_BAR;
constexpr uint32_t EPS8 = 0x2A0D2A0Du;

__device__ __forceinline__ void load_x_interior(const CUtensorMap* tm_x, int w, int g) {
  mbar_expect(mbar + MB_X + 8 * g, 12288);
  tma5(sb + SM_WG + g * WG_SZ + WG_X, tm_x, mbar + MB_X + 8 * g, 0, 0, ((w >> 8) & 255) * 8 + 4, (w & 255) * 2 + 1, 0);
}
__device__ __forceinline__ void load_x(const CUtensorMap* tm_x, const CUtensorMap* tm_xq, int w, int g) {
  const uint32_t dst = sb + SM_WG + g * WG_SZ + WG_X, bar = mbar + MB_X + 8 * g;
  const int wy = (w >> 8) & 255, wx = w & 255;
  mbar_expect(bar, 12288);
  if (wy != NWX - 1 && wx != NWX - 1) {
    tma5(dst, tm_x, bar, 0, 0, wy * 8 + 4, wx * 2 + 1, 0);
  } else {
#pragma unroll 1
    for (int i = 0; i < 12; i++) {
      const int q = i & 3, c = i >> 2;
      int y = wy * 8 + 4 + (q & 1) * 4; if (y >= IMG) y -= IMG;
      int xq = wx * 2 + 1 + (q >> 1);   if (xq >= IMG / 4) xq -= IMG / 4;
      tma5(dst + i * 1024, tm_xq, bar, 0, 0, y, xq, c);
    }
  }
}
__device__ __forceinline__ uint32_t mask_off(int w) { return (uint32_t)(((w >> 8) & 255) * NWX + (w & 255)) * 8192u; }
__device__ __forceinline__ int lds_uniform(uint32_t addr) { return __shfl_sync(0xffffffffu, lds32(addr), 0); }

__device__ __forceinline__ void qkv_epilogue(float (&qk)[96], uint32_t (&qa)[24], uint64_t dX, uint64_t dWv, uint32_t k_dst) {
  uint32_t ka[24], sk[8], sq[8];
  float k01[4], k23[4], q01[4], q23[4], vv[48];
  constexpr uint64_t dSel = mk_desc(sb + SM_SEL, 128, 256, 0);
  wg_wait<0>(); fence_regs(qk);
  pack_sumsq(qk + 48, ka, sk, EPS8);
  pack_sumsq(qk, qa, sq, EPS8);
  wg_fence();
  wgmma_rs_n8_t0<0>(k01, sk[0], sk[1], sk[2], sk[3], dSel);
  wgmma_rs_n8_t0<0>(k23, sk[4], sk[5], sk[6], sk[7], dSel);
  wgmma_rs_n8_t0<0>(q01, sq[0], sq[1], sq[2], sq[3], dSel);
  wgmma_rs_n8_t0<0>(q23, sq[4], sq[5], sq[6], sq[7], dSel);
  wg_commit();
  issue_proj(vv, dX, dWv); wg_commit();
  const uint4 qs = lds128(sb + SM_MISC);
  wg_wait<1>(); fence_regs(k01); fence_regs(k23); fence_regs(q01); fence_regs(q23);
  const float rk[8] = {rsq(k01[0]), rsq(k01[2]), rsq(k01[1]), rsq(k01[3]), rsq(k23[0]), rsq(k23[2]), rsq(k23[1]), rsq(k23[3])};
  scale_heads(ka, rk);
#pragma unroll
  for (int i = 0; i < 6; i++) stsm4(k_dst + (i + (i >= 3)) * 1024, ka[2 * i], ka[2 * i + 1], ka[12 + 2 * i], ka[12 + 2 * i + 1]);
  wg_wait<0>(); fence_regs(vv);
#pragma unroll
  for (int i = 0; i < 6; i++)
    stsm4(k_dst + (WG_V - WG_K) + (i + (i >= 3)) * 1024, pack_bf16(vv[4 * i], vv[4 * i + 1]), pack_bf16(vv[4 * i + 2], vv[4 * i + 3]),
          pack_bf16(vv[24 + 4 * i], vv[24 + 4 * i + 1]), pack_bf16(vv[24 + 4 * i + 2], vv[24 + 4 * i + 3]));
  const float s0 = __uint_as_float(qs.x), s1 = __uint_as_float(qs.y), s2 = __uint_as_float(qs.z), s3 = __uint_as_float(qs.w);
  const float rq[8] = {rsq(q01[0]) * s0, rsq(q01[2]) * s0, rsq(q01[1]) * s1, rsq(q01[3]) * s1,
                       rsq(q23[0]) * s2, rsq(q23[2]) * s2, rsq(q23[1]) * s3, rsq(q23[3]) * s3};
  scale_heads(qa, rq);
  fence_async();
}
__device__ __forceinline__ void issue_out(float (&y)[48], const uint32_t (&of)[24], uint64_t dWo) {
  wg_fence();
#pragma unroll
  for (int s = 0; s < 6; s++) {
    if (s == 0) wgmma_rs_n96_t1<0>(y, of[0], of[1], of[2], of[3], dWo);
    else wgmma_rs_n96_t1<1>(y, of[4 * s], of[4 * s + 1], of[4 * s + 2], of[4 * s + 3], dWo + s * 16);
  }
  wg_commit();
}
__device__ __forceinline__ void ln_head(float (&y)[48], uint32_t (&yb)[24], float (&var)[4], uint64_t dOnes) {
  uint32_t sy[8];
  wg_wait<0>(); fence_regs(y);
  pack_sumsq(y, yb, sy, 0u);
  wg_fence();
  wgmma_rs_n8_t0<0>(var, sy[0], sy[1], sy[2], sy[3], dOnes);
  wgmma_rs_n8_t0<1>(var, sy[4], sy[5], sy[6], sy[7], dOnes);
  wg_commit();
}
__device__ __forceinline__ char* out_ptr(__nv_bfloat16* out, int win, int warp, uint32_t t16) {
  int py = ((win >> 8) & 255) * 8 + 4 + (warp & 1) * 4;  if (py >= IMG) py -= IMG;
  int px = (win & 255) * 8 + 4 + (warp >> 1) * 4;        if (px >= IMG) px -= IMG;
  return reinterpret_cast<char*>(out) + ((uint32_t)(py * IMG + px) * PIXB - warp * 512 + t16 + ((t16 & 0xC0) << 1) + (t16 & 0x100) * 287);
}
__device__ __forceinline__ uint32_t ln_tail(const uint32_t (&yb)[24], float (&var)[4], char* optr) {
  fence_regs(var);
  uint32_t last;
  const uint32_t nn = pack_bf16(rsq(fmaf(var[0], 1.f / 96.f, 1e-5f)), rsq(fmaf(var[2], 1.f / 96.f, 1e-5f)));
#pragma unroll
  for (int j = 0; j < 3; j++) {
    stg128(optr + j * 64, hmul2_b<0>(yb[8 * j], nn), hmul2_b<0>(yb[8 * j + 2], nn), hmul2_b<0>(yb[8 * j + 4], nn), hmul2_b<0>(yb[8 * j + 6], nn));
    last = hmul2_b<1>(yb[8 * j + 7], nn);
    stg128(optr + 2 * ROWB + j * 64, hmul2_b<1>(yb[8 * j + 1], nn), hmul2_b<1>(yb[8 * j + 3], nn), hmul2_b<1>(yb[8 * j + 5], nn), last);
  }
  return last;
}

__device__ __forceinline__ void load_mask_frag(uint32_t (&mk)[16], const char* tile, uint32_t t16) {
  asm volatile("" : "+r"(t16));
  const char* mrow = tile + (orig_tok(((t16 >> 9) << 4) + ((t16 >> 6) & 7)) * 128 + (t16 & 32) / 2);
  const bool odd = t16 & 16;
#pragma unroll
  for (int i = 0; i < 8; i++) {
    const uint4 v = ldg128_stream(mrow + (i & 1) * 2048 + (i >> 1) * 32);
    mk[i] = odd ? v.y : v.x; mk[8 + i] = odd ? v.w : v.z;
  }
}
__device__ __forceinline__ bool mask_unsafe(const uint32_t (&mk)[16]) {
  uint32_t x0 = mk[0], x1 = mk[1];
#pragma unroll
  for (int i = 2; i < 16; i += 2) { x0 = hmax2_nan(x0, mk[i]); x1 = hmax2_nan(x1, mk[i + 1]); }
  const bool nan_in = !(bf_lo(x0) == bf_lo(x0) && bf_hi(x0) == bf_hi(x0) && bf_lo(x1) == bf_lo(x1) && bf_hi(x1) == bf_hi(x1));
  const float r0 = quad_max(fmaxf(bf_lo(x0), bf_hi(x0))), r1 = quad_max(fmaxf(bf_lo(x1), bf_hi(x1)));
  return nan_in || !(fabsf(r0) <= 8.f && fabsf(r1) <= 8.f);
}

__device__ __forceinline__ void general_windows(const CUtensorMap* tm_x, const CUtensorMap* tm_xq, const char* mb, __nv_bfloat16* out, uint32_t xph) {
  int tid;
  asm volatile("mov.u32 %0, %%tid.x;" : "=r"(tid));
  const int lane = tid & 31;
  const int warp = __shfl_sync(0xffffffffu, (tid >> 5) & 3, 0), wg = __shfl_sync(0xffffffffu, tid >> 7, 0);
  const uint32_t t16 = (tid & 127) * 16, wgb = sb + SM_WG + wg * WG_SZ, bar_x = mbar + MB_X + 8 * wg;
  const uint32_t k_dst = wgb + WG_K + (lane >> 4) * 7168 + warp * 256 + (lane & 15) * 16;
  if (lds_uniform(sb + SM_GEN + wg * NENT * 4) < 0) return;
  mbar_wait(mbar + MB_WV, 0);
  mbar_wait(mbar + MB_RDY, 0);
  mbar_wait(mbar + MB_WOC, 0);
  const uint32_t slow_heads = lds_uniform(sb + SM_SLOW);
  const uint64_t dX = mk_desc(WG_X, 16, 512, 2) + (wgb >> 4), dK = mk_desc(WG_K, 1024, 128, 0) + (wgb >> 4), dV = mk_desc(WG_V, 128, 1024, 0) + (wgb >> 4);
#pragma unroll 1
  for (uint32_t gl = sb + SM_GEN + wg * NENT * 4;; gl += 4) {
    const int win = lds_uniform(gl);
    if (win < 0) break;
    uint32_t qa[24], of[24], mk[16];
    uint32_t tm;
    {
      load_mask_frag(mk, mb + mask_off(win), t16);
      float qk[96];
      mbar_wait(bar_x, xph); xph ^= 1;
      wg_fence();
      issue_qk(qk, dX, mk_desc(sb + SM_W, 12288, 1024, 1)); wg_commit();
      uint32_t any = 0;
#pragma unroll
      for (int i = 0; i < 16; i += 2) any |= mk[i] | mk[i + 1];
      tm = bar_wg_or(BAR_KV + wg, (any & 0x7FFF7FFFu) != 0) ? 0x1Fu : slow_heads;
      qkv_epilogue(qk, qa, dX, mk_desc(sb + SM_WV, 6144, 512, 2), k_dst);
    }
    bar_sync_n(BAR_AUX + wg, 128);
    if (warp == 0 && elect_one()) {
      const int nxt = lds32(gl + 4);
      if (nxt >= 0) { load_x(tm_x, tm_xq, nxt, wg); prefetch_l2(mb + mask_off(nxt), 8192); }
    }
    __syncwarp();
    auto head = [&](float (&sc)[32], uint32_t (&p)[16], bool tmax) {
      if (tmax) {
        if (tm & 16) {
#pragma unroll
          for (int i = 0; i < 16; i++) {
            sc[2 * i] = fmaf(bf_lo(mk[i]), LOG2E, sc[2 * i]); sc[2 * i + 1] = fmaf(bf_hi(mk[i]), LOG2E, sc[2 * i + 1]);
          }
        }
        softmax_true_max(sc, p);
      } else {
        softmax_fast(sc, p);
      }
    };
#pragma unroll
    for (int i = 0; i < 24; i++) of[i] = 0;
#pragma unroll 1
    for (int hp = 0; hp < 2; hp++) {
      float sA[32], sB[32], oA[16], oB[16]; uint32_t p[16];
      const uint32_t po = hp * 7 * 64;
      wg_fence();
      issue_s<0>(sA, qa, dK + po);
      issue_s<1>(sB, qa, dK + po); wg_commit();
      load_eb(p, sb + SM_EB + t16 + hp * 16384);
      wg_wait<0>(); fence_regs(sA); fence_regs(sB);
#pragma unroll
      for (int i = 0; i < 12; i++) { qa[i] = qa[i + 12]; of[i] = of[i + 12]; }
      head(sA, p, (tm >> (2 * hp)) & 1);
      wg_fence(); issue_pv<0>(oA, p, dV + po); wg_commit();
      uint32_t p2[16];
      load_eb(p2, sb + SM_EB + t16 + hp * 16384 + 8192);
      head(sB, p2, (tm >> (2 * hp + 1)) & 1);
      wg_fence(); issue_pv<1>(oB, p2, dV + po); wg_commit();
      wg_wait<1>(); fence_regs(oA);
      norm_o<0>(oA, of + 12);
      wg_wait<0>(); fence_regs(oB);
      norm_o<1>(oB, of + 18);
    }
    float y[48], var[4]; uint32_t yb[24];
    issue_out(y, of, mk_desc(sb + SM_WO, 128, 1536, 0));
    ln_head(y, yb, var, dV + 3 * 64);
    wg_wait<0>();
    ln_tail(yb, var, out_ptr(out, win, warp, t16));
  }
}

__global__ void __launch_bounds__(384, 1)
swin_kernel(const __nv_bfloat16* __restrict__ logit_scale, const __nv_bfloat16* __restrict__ w1, const __nv_bfloat16* __restrict__ w2,
            const __nv_bfloat16* __restrict__ coords, const int* __restrict__ rel_idx, const __nv_bfloat16* __restrict__ wo,
            const __nv_bfloat16* __restrict__ mask, __nv_bfloat16* __restrict__ out,
            const __grid_constant__ CUtensorMap tm_wqk, const __grid_constant__ CUtensorMap tm_x,
            const __grid_constant__ CUtensorMap tm_wv, const __grid_constant__ CUtensorMap tm_xq) {
  extern __shared__ __align__(1024) uint8_t smem[];
  const int tid = threadIdx.x, lane = tid & 31;
  const int warp = __shfl_sync(0xffffffffu, (tid >> 5) & 3, 0), wg = __shfl_sync(0xffffffffu, tid >> 7, 0);
  const int G = gridDim.x;
  const char* mb = reinterpret_cast<const char*>(mask);
  TL(0); TG(14);

  const bool g132 = G == 132;
  uint32_t cw = 0;
  uint4 rid[4];
  if (tid >= 128) {
    const int i = tid - 128;
    if (i < 225) cw = __ldg(reinterpret_cast<const uint32_t*>(coords) + i);
  } else if (tid >= 64 && tid < 96) {
    if (lane < 12) *reinterpret_cast<uint4*>(smem + SM_PAR + 16 * lane) =
        ldg128_stream(lane < 4 ? reinterpret_cast<const uint4*>(w1) + lane : reinterpret_cast<const uint4*>(w2) + (lane - 4));
    __syncwarp();
    bar_arrive_n(BAR_PAR, 288);
  }
  const uint2 lsw = __ldg(reinterpret_cast<const uint2*>(logit_scale));
  if (tid >= 128) {
#pragma unroll
    for (int c = 0; c < 4; c++) rid[c] = ldg128_stream(reinterpret_cast<const int4*>(rel_idx) + c * 256 + (tid - 128));
  } else if (tid < 32) {
    if (elect_one()) {
#pragma unroll
      for (int i = 0; i < 13; i++) mbar_init(mbar + 8 * i, ((i >= 4 && i < 7) || i >= 9) ? 4 : 1);
      mbar_init(mbar + MB_RDY, 8); mbar_init(mbar + MB_WOC, 4);
      fence_async();
      auto first = [&](int g) { const int i = blockIdx.x + g * G, iy = (i * 2789) >> 17; return iy << 8 | (i - iy * 47); };
      mbar_expect(mbar + MB_WQK, 3 * 12288);
      tma3(sb + SM_W, &tm_wqk, mbar + MB_WQK, 0, 0, 0);
      load_x_interior(&tm_x, first(0), 0);
      mbar_expect(mbar + MB_WV, 3 * 6144);
      tma3(sb + SM_WV, &tm_wv, mbar + MB_WV, 0, 0, 0);
      mbar_expect(mbar + MB_WO, 18432);
      bulk_g2s(sb + SM_WOR, wo, 18432, mbar + MB_WO);
      load_x_interior(&tm_x, first(1), 1);
      prefetch_l2(mb + mask_off(first(0)), 8192);
    }
    __syncwarp();
  }
  if ((uint32_t)__cvta_generic_to_shared(smem) != sb) __trap();
  auto const_tiles = [&]() {
    const int i = tid & 127;
    uint8_t* vt = smem + SM_WG + wg * WG_SZ + WG_V + (i < 64 ? 3 : 10) * 1024 + (i & 63) * 16;
    *reinterpret_cast<uint4*>(vt) = make_uint4(0x3F803F80u, 0x3F803F80u, 0x3F803F80u, 0x3F803F80u);
    *reinterpret_cast<uint4*>(vt - (WG_V - WG_K)) = make_uint4(0u, 0u, 0u, 0u);
  };
  if (wg != 2) const_tiles();
  float tau[4]; uint32_t slow_heads = 0;
  auto head_scales = [&]() {
    const float ls[4] = {bf_lo(lsw.x), bf_hi(lsw.x), bf_lo(lsw.y), bf_hi(lsw.y)};
#pragma unroll
    for (int h = 0; h < 4; h++) {
      float c;
      asm("max.NaN.f32 %0, %1, 0fC2C80000;" : "=f"(c) : "f"(ls[h]));
      asm("min.NaN.f32 %0, %0, 0f40930000;" : "+f"(c));
      tau[h] = rbf(ex2(c * LOG2E)) * LOG2E;
      if (!(tau[h] <= TAU_FAST_MAX)) slow_heads |= 1u << h;
    }
    slow_heads = __shfl_sync(0xffffffffu, slow_heads, 0);
  };
  if (wg == 0) head_scales();
  if (wg == 0 && warp == 1) {
    const int eg = lane / NENT, ei = lane - eg * NENT, sl = blockIdx.x + eg * G + ei * 3 * G;
    const int w = (sl < NWIN && eg < 3) ? slot_window(sl, g132) : -1;
    const bool queues = w >= 0 && (w >> 8) != NWX - 1 && (w & 255) != NWX - 1;
    const uint32_t qmask = __ballot_sync(0xffffffffu, queues);
    const int key = (eg + 3 * ei + BORDER_EXTRA * __popc((~qmask >> (eg * NENT)) & ((1u << ei) - 1))) * 3 + eg;
    const uint32_t k0 = __reduce_or_sync(0xffffffffu, queues && key < 32 ? 1u << key : 0u), k1 = __reduce_or_sync(0xffffffffu, queues && (key >> 5) == 1 ? 1u << (key & 31) : 0u);
    const uint32_t k2 = __reduce_or_sync(0xffffffffu, queues && (key >> 5) == 2 ? 1u << (key & 31) : 0u), k3 = __reduce_or_sync(0xffffffffu, queues && (key >> 5) == 3 ? 1u << (key & 31) : 0u);
    const uint32_t lo = (1u << (key & 31)) - 1;
    const int kw = key >> 5;
    const int ticket = __popc(kw > 0 ? k0 : k0 & lo) + (kw >= 1 ? __popc(kw > 1 ? k1 : k1 & lo) : 0) + (kw >= 2 ? __popc(kw > 2 ? k2 : k2 & lo) : 0) + (kw >= 3 ? __popc(k3 & lo) : 0);
    const int ent = w | (queues ? ticket : NO_TICKET) << 16;
    if (eg < 3) {
      *reinterpret_cast<int*>(smem + SM_WIN + lane * 4) = slow_heads ? -1 : ent;
      *reinterpret_cast<int*>(smem + SM_GEN + lane * 4) = slow_heads ? ent : -1;
    }
  }
  if (wg == 0 && warp == 3 && lane < 16) {
    const uint32_t v = (((lane >> 3) ^ lane) & 1) ? 0u : 0x3F803F80u;
    *reinterpret_cast<uint4*>(smem + SM_SEL + lane * 16) = make_uint4(v, v, v, v);
  }
  TL(3);
  if (wg == 0) {
    if (tid == 0) {
      *reinterpret_cast<float4*>(smem + SM_MISC) = make_float4(tau[0], tau[1], tau[2], tau[3]);
      *reinterpret_cast<uint32_t*>(smem + SM_SLOW) = slow_heads;
    }
    fence_async();
    bar_arrive_n(BAR_SETUP, 384);
    bar_sync_n(BAR_AUX, 128);
  } else {
    const int i = tid - 128;
    bar_sync_n(BAR_PAR, 288);
    TL(4);
    head_scales();
    if (i < 225) {
      const float c0 = bf_lo(cw), c1 = bf_hi(cw);
      float z[4] = {0.f, 0.f, 0.f, 0.f};
#pragma unroll
      for (int jj = 0; jj < 2; jj++) {
        const uint4 ua4 = lds128(sb + SM_PAR + 16 * jj), ub4 = lds128(sb + SM_PAR + 32 + 16 * jj);
        const uint32_t ua[4] = {ua4.x, ua4.y, ua4.z, ua4.w}, ub[4] = {ub4.x, ub4.y, ub4.z, ub4.w};
#pragma unroll
        for (int j = 0; j < 4; j++) {
          const uint4 wb = lds128(sb + SM_PAR + 64 + 64 * jj + 16 * j);
          const uint32_t hp = pack_bf16(fmaf(c1, bf_lo(ub[j]), c0 * bf_lo(ua[j])), fmaf(c1, bf_hi(ub[j]), c0 * bf_hi(ua[j])));
          float h0 = bf_lo(hp), h1 = bf_hi(hp);
          h0 = h0 > 0.f ? h0 : h0 * 0.f; h1 = h1 > 0.f ? h1 : h1 * 0.f;
          z[0] = fmaf(h0, bf_lo(wb.x), z[0]); z[1] = fmaf(h0, bf_hi(wb.x), z[1]); z[2] = fmaf(h0, bf_lo(wb.y), z[2]); z[3] = fmaf(h0, bf_hi(wb.y), z[3]);
          z[0] = fmaf(h1, bf_lo(wb.z), z[0]); z[1] = fmaf(h1, bf_hi(wb.z), z[1]); z[2] = fmaf(h1, bf_lo(wb.w), z[2]); z[3] = fmaf(h1, bf_hi(wb.w), z[3]);
        }
      }
      float e[4];
#pragma unroll
      for (int q = 0; q < 4; q++) {
        const float sh = ((slow_heads >> q) & 1) ? 0.f : fminf(0.f, 25.f - 1.02f * tau[q]);
        e[q] = ex2(fmaf(16.f * LOG2E, rbf(rcp(1.f + ex2(-LOG2E * rbf(z[q])))), sh));
      }
      *reinterpret_cast<uint2*>(smem + SM_TAB + 8 * i) = make_uint2(pack_bf16(e[0], e[1]), pack_bf16(e[2], e[3]));
    }
    TL(5);
    bar_sync_n(BAR_SETUP, 384);
#pragma unroll
    for (int c = 0; c < 4; c++) asm volatile("" : "+r"(rid[c].x), "+r"(rid[c].y), "+r"(rid[c].z), "+r"(rid[c].w));
    {
      const int y = (i & 15) >> 1, xh = i & 1, j = 2 * xh + (y >> 2);
      const int X = (i >> 4) & 7, Yl = (i >> 7) & 1;
      uint8_t* dst = smem + SM_EB + j * 2048 + ((X >> 2) * 64 + (Yl * 4 + (X & 3)) * 4 + 2 * (y & 1)) * 16 + ((y >> 1) & 1) * 8;
      uint2 e[16];
#pragma unroll
      for (int c = 0; c < 4; c++) {
        const uint32_t id[4] = {xh ? rid[c].z : rid[c].x, xh ? rid[c].w : rid[c].y, xh ? rid[c].x : rid[c].z, xh ? rid[c].y : rid[c].w};
#pragma unroll
        for (int q = 0; q < 4; q++) e[4 * c + q] = *reinterpret_cast<const uint2*>(smem + SM_TAB + 8 * id[q]);
      }
#pragma unroll
      for (int c = 0; c < 4; c++) {
        const uint2 a0 = e[4 * c], a1 = e[4 * c + 1], b0 = e[4 * c + 2], b1 = e[4 * c + 3];
        uint8_t* d0 = dst + (c >> 1) * 512 + (((c & 1) ^ (j & 1)) * 4) + xh * 16;
        uint8_t* d1 = dst + (c >> 1) * 512 + (((c & 1) ^ (j & 1)) * 4) + (xh ^ 1) * 16;
        *reinterpret_cast<uint32_t*>(d0)         = __byte_perm(a0.x, a1.x, 0x5410); *reinterpret_cast<uint32_t*>(d1)         = __byte_perm(b0.x, b1.x, 0x5410);
        *reinterpret_cast<uint32_t*>(d0 + 8192)  = __byte_perm(a0.x, a1.x, 0x7632); *reinterpret_cast<uint32_t*>(d1 + 8192)  = __byte_perm(b0.x, b1.x, 0x7632);
        *reinterpret_cast<uint32_t*>(d0 + 16384) = __byte_perm(a0.y, a1.y, 0x5410); *reinterpret_cast<uint32_t*>(d1 + 16384) = __byte_perm(b0.y, b1.y, 0x5410);
        *reinterpret_cast<uint32_t*>(d0 + 24576) = __byte_perm(a0.y, a1.y, 0x7632); *reinterpret_cast<uint32_t*>(d1 + 24576) = __byte_perm(b0.y, b1.y, 0x7632);
      }
    }
    TL(6);
    if (tid == 256) {
      load_x_interior(&tm_x, slot_window(blockIdx.x + 2 * G, g132), 2);
      prefetch_l2(mb + mask_off(slot_window(blockIdx.x + G, g132)), 8192);
      prefetch_l2(mb + mask_off(slot_window(blockIdx.x + 2 * G, g132)), 8192);
    }
    __syncwarp();
    fence_async();
    if (elect_one()) mbar_arrive(mbar + MB_RDY);
    __syncwarp();
    bar_sync_n(BAR_TAB, 256);
    if (wg == 2) {
      mbar_wait(mbar + MB_WO, 0);
      uint4 v[9];
#pragma unroll
      for (int c = 0; c < 9; c++) v[c] = lds128(sb + SM_WOR + ((c / 3) * 32 + ((tid & 127) >> 2)) * 192 + (c % 3) * 64 + (lane & 3) * 16);
      bar_sync_n(BAR_AUX + 2, 128);
      const_tiles();
#pragma unroll
      for (int r = 0; r < 3; r++) {
        float sum = 0.f;
#pragma unroll
        for (int c = 3 * r; c < 3 * r + 3; c++)
          sum += (bf_lo(v[c].x) + bf_hi(v[c].x)) + (bf_lo(v[c].y) + bf_hi(v[c].y)) + (bf_lo(v[c].z) + bf_hi(v[c].z)) + (bf_lo(v[c].w) + bf_hi(v[c].w));
        sum += __shfl_xor_sync(0xffffffffu, sum, 1);
        sum += __shfl_xor_sync(0xffffffffu, sum, 2);
        const float mu = sum * (1.f / 96.f);
        auto cen = [&](uint32_t u) { return pack_bf16(bf_lo(u) - mu, bf_hi(u) - mu); };
        uint8_t* dst = smem + SM_WO + (r * 4 + warp) * 128 + lane * 4;
#pragma unroll
        for (int j = 0; j < 3; j++) {
          *reinterpret_cast<uint32_t*>(dst + (4 * j + 0) * 1536) = cen(v[3 * r + j].x);
          *reinterpret_cast<uint32_t*>(dst + (4 * j + 1) * 1536) = cen(v[3 * r + j].y);
          *reinterpret_cast<uint32_t*>(dst + (4 * j + 2) * 1536) = cen(v[3 * r + j].z);
          *reinterpret_cast<uint32_t*>(dst + (4 * j + 3) * 1536) = cen(v[3 * r + j].w);
        }
      }
      fence_async();
      __syncwarp();
      if (elect_one()) { mbar_arrive(mbar + MB_TURN); mbar_arrive(mbar + MB_WOC); }
      __syncwarp();
    }
  }
  TL(1);
  mbar_wait(mbar + MB_WQK, 0);
  uint32_t xpar = 0;

  uint32_t wl = sb + SM_WIN + wg * NENT * 4;
  int win = lds_uniform(wl), nxt = lds_uniform(wl + 4);
  if (win >= 0) {
    const uint32_t wgb = sb + SM_WG + wg * WG_SZ, bar_x = mbar + MB_X + 8 * wg;
    const uint32_t t16 = (tid & 127) * 16;
    const uint32_t k_dst = wgb + WG_K + (tid & 16) * 448 + warp * 256 + (tid & 15) * 16;
    const uint32_t eb_base = sb + SM_EB + t16;
    uint4 mw[4];
    auto load_mask = [&](uint32_t off) {
      const char* src = mb + (off + t16);
#pragma unroll
      for (int i = 0; i < 4; i++) mw[i] = ldg128_stream(src + i * 2048);
    };
    auto mask_or = [&](uint32_t seed) {
      uint32_t r = seed & 0x80008000u;
#pragma unroll
      for (int i = 0; i < 4; i++) {
        asm("lop3.b32 %0, %0, %1, %2, 0xFE;" : "+r"(r) : "r"(mw[i].x), "r"(mw[i].y));
        asm("lop3.b32 %0, %0, %1, %2, 0xFE;" : "+r"(r) : "r"(mw[i].z), "r"(mw[i].w));
      }
      return r;
    };
    float qk[96];
    mbar_wait(bar_x, 0);
    TL(2);
    wg_fence();
    issue_qk(qk, mk_desc(WG_X, 16, 512, 2) + (wgb >> 4), mk_desc(sb + SM_W, 12288, 1024, 1)); wg_commit();
    uint32_t mword = 0;
    bool first = true;
    mbar_wait(mbar + MB_WV, 0);
    TL(8);
    while (true) {
      const int nxt2 = lds_uniform(wl + 8);
      int tk = win >> 16;
      const bool more = nxt >= 0;
      const uint32_t z0 = wl >> 20, zw = z0 + (wgb >> 4);
      const uint64_t dX = opaque(mk_desc(WG_X, 16, 512, 2) + zw);
      TL(0);
      uint32_t qa[24];
      qkv_epilogue(qk, qa, dX, opaque(mk_desc(sb + SM_WV, 6144, 512, 2) + z0), k_dst);
      TL(5);
      if (__builtin_expect(first, 0)) {
        load_mask(mask_off(win));
        if (t16 == 0 && more) prefetch_l2(mb + mask_off(nxt), 8192);
        __syncwarp();
        mbar_wait(mbar + MB_RDY, 0);
        mword = mask_or(0);
        first = false;
      }
      uint32_t pA[16], pB[16];
      load_eb(pA, eb_base);
      load_eb(pB, eb_base + 8192);
      const bool masked = bar_wg_or(BAR_KV + wg, (mword & 0x7FFF7FFFu) != 0u);
      TL(6);
      const uint64_t dK = opaque(mk_desc(WG_K, 1024, 128, 0) + zw), dV = opaque(mk_desc(WG_V, 128, 1024, 0) + zw);
      auto prefetch_next = [&]() {
        if (warp == 0 && more) {
          if (elect_one()) {
            load_x(&tm_x, &tm_xq, nxt, wg);
            if (nxt2 >= 0) prefetch_l2(mb + mask_off(nxt2), 8192);
          }
          __syncwarp();
        }
      };
      auto wait_turn = [&]() { if (tk != NO_TICKET) mbar_wait(mbar + MB_TURN + (tk & 3) * 8, (tk >> 2) & 1); };
      auto pass_turn = [&](uint32_t after = 0) {
        asm volatile("{\n.reg .pred p, q;\nelect.sync _|p, 0xffffffff;\nsetp.ne.and.s32 q, %1, 255, p;\nsetp.ne.and.s32 q, %2, -1, q;\n"
                     "@q mbarrier.arrive.shared::cta.b64 _, [%0];\n}\n"
                     :: "r"(mbar + MB_TURN + ((tk + 1) & 3) * 8), "r"(tk), "r"(after) : "memory");
      };
      auto next_qk = [&]() { issue_qk(qk, dX, opaque(mk_desc(sb + SM_W, 12288, 1024, 1) + z0)); wg_commit(); };
      auto tiles_ready = [&]() {
        if (elect_one()) mbar_arrive(bar_x + (MB_KV - MB_X));
        __syncwarp();
        const uint32_t par = (wl >> 2) & 1;
        mbar_wait(bar_x, par ^ 1);
        mbar_wait(bar_x + (MB_KV - MB_X), par);
      };
      uint32_t of[24];
      {
        float sA[32], sB[32], oA[16], oB[16], oC[16], oD[16];
        uint32_t pC[16], pD[16];
        wg_fence();
        issue_s<0>(sA, qa, dK);
        issue_s<1>(sB, qa, dK); wg_commit();
        uint32_t eb_hi = sb + SM_EB + 16384;
        if (__builtin_expect(!masked, 1)) {
          prefetch_next();
          wait_turn();
        } else {
          uint32_t mk[16];
          load_mask_frag(mk, mb + mask_off(win), t16);
          if (t16 == 0 && more)
            asm volatile("cp.async.bulk.prefetch.tensor.5d.L2.global.tile [%0, {%1, %1, %2, %3, %1}];"
                         :: "l"(&tm_x), "r"(0), "r"(((nxt >> 8) & 255) * 8 + 4), "r"((nxt & 255) * 2 + 1) : "memory");
          __syncwarp();
          wait_turn(); pass_turn();
          tk = NO_TICKET;
          wg_wait<0>();
          if (bar_wg_or(BAR_AUX + wg, mask_unsafe(mk))) {
            if (t16 == 0) {
              uint32_t gl = sb + SM_GEN + wg * NENT * 4;
              while ((int)lds32(gl) >= 0) gl += 4;
              asm volatile("st.shared.u32 [%0], %1;" :: "r"(gl), "r"(win) : "memory");
            }
            __syncwarp();
            if (!more) break;
            prefetch_next();
            load_mask(mask_off(nxt));
            tiles_ready();
            wg_fence();
            next_qk();
            mword = mask_or(0);
            wl += 4;
            win = nxt; nxt = nxt2;
            continue;
          }
#pragma unroll
          for (int i = 0; i < 16; i++) {
            mk[i] = pack_bf16(ex2(bf_lo(mk[i]) * LOG2E), ex2(bf_hi(mk[i]) * LOG2E));
            pA[i] = hmul2(pA[i], mk[i]); pB[i] = hmul2(pB[i], mk[i]);
          }
#pragma unroll
          for (int h = 0; h < 2; h++) {
            uint4 e[4];
#pragma unroll
            for (int j = 0; j < 4; j++) e[j] = lds128(eb_base + 16384 + h * 8192 + j * 2048);
#pragma unroll
            for (int j = 0; j < 4; j++) {
              const int m = 4 * j, x = j & 1;
              asm volatile("st.shared.v4.u32 [%0], {%1,%2,%3,%4};" :: "r"(wgb + WG_X + t16 + h * 8192 + j * 2048), "r"(hmul2(e[j].x, mk[m + x])),
                           "r"(hmul2(e[j].y, mk[m + (1 ^ x)])), "r"(hmul2(e[j].z, mk[m + (2 ^ x)])), "r"(hmul2(e[j].w, mk[m + (3 ^ x)])) : "memory");
            }
          }
          eb_hi = wgb + WG_X;
        }
        wg_wait<0>(); fence_regs(sA); fence_regs(sB);
        TL(7);
        softmax_fast(sA, pA);
        wg_fence();
        issue_s<2>(sA, qa, dK); wg_commit();
        issue_pv<0>(oA, pA, dV); wg_commit();
        TL(8);
        softmax_fast(sB, pB);
        load_eb(pC, eb_hi + t16);
        wg_wait<1>(); fence_regs(sA);
        wg_fence();
        issue_s<3>(sB, qa, dK); wg_commit();
        issue_pv<1>(oB, pB, dV); wg_commit();
        TL(9);
        softmax_fast(sA, pC);
        load_eb(pD, eb_hi + t16 + 8192);
        wg_wait<1>(); fence_regs(sB); fence_regs(oA);
        wg_fence();
        issue_pv<2>(oC, pC, dV); wg_commit();
        TL(10);
        norm_o<0>(oA, of);
        softmax_fast(sB, pD);
        pass_turn(pD[TPOS]);
        wg_fence();
        issue_pv<3>(oD, pD, dV); wg_commit();
        if (more) load_mask(mask_off(nxt));
        else { mw[0] = mw[1] = mw[2] = mw[3] = make_uint4(0, 0, 0, 0); }
        wg_wait<1>(); fence_regs(oB); fence_regs(oC);
        norm_o<1>(oB, of + 6);
        norm_o<0>(oC, of + 12);
        wg_wait<0>(); fence_regs(oD);
        norm_o<1>(oD, of + 18);
      }
      TL(11);
      float y[48], var[4]; uint32_t yb[24];
      issue_out(y, of, opaque(mk_desc(sb + SM_WO, 128, 1536, 0) + z0));
      if (__builtin_expect(masked, 0)) {
        if (t16 >= 1024) asm volatile("st.shared.v4.u32 [%0], {%1,%1,%1,%1};" :: "r"(wgb + WG_K + 2048 + t16), "r"(0) : "memory");
        fence_async();
        bar_sync_n(BAR_AUX + wg, 128);
        prefetch_next();
      }
      char* const optr = out_ptr(out, win, warp, t16);
      if (!more) { ln_head(y, yb, var, dV + 3 * 64); wg_wait<0>(); ln_tail(yb, var, optr); TL(14); break; }
      tiles_ready();
      ln_head(y, yb, var, dV + 3 * 64);
      TL(12);
      next_qk();
      wg_wait<1>();
      TL(13);
      mword = mask_or(ln_tail(yb, var, optr));
      if ((nxt >> 16) == NO_TICKET && t16 == 0) prefetch_l2(mb + mask_off(nxt), 8192);
      TL(14);
      wl += 4;
      win = nxt; nxt = nxt2;
    }
    xpar = ((wl >> 2) & 1) ^ 1;
    bar_sync_n(BAR_AUX + wg, 128);
    if (warp == 0 && elect_one()) {
      const int w = lds32(sb + SM_GEN + wg * NENT * 4);
      if (w >= 0) load_x(&tm_x, &tm_xq, w, wg);
    }
    __syncwarp();
  }
  general_windows(&tm_x, &tm_xq, mb, out, xpar);
  TG(15);
}

typedef CUresult (*EncodeFn)(CUtensorMap*, CUtensorMapDataType, cuuint32_t, void*, const cuuint64_t*, const cuuint64_t*,
                             const cuuint32_t*, const cuuint32_t*, CUtensorMapInterleave, CUtensorMapSwizzle,
                             CUtensorMapL2promotion, CUtensorMapFloatOOBfill);

}

extern "C" void kernel_launch(void* const* d_in, const int* in_sizes, int n_in, void* d_out, int out_size) {
  static int sms = 0;
  static EncodeFn encode = nullptr;
  if (sms == 0) {
    int dev = 0;
    cudaGetDevice(&dev);
    cudaDeviceGetAttribute(&sms, cudaDevAttrMultiProcessorCount, dev);
    if (sms < 96) sms = 96;
    cudaFuncSetAttribute(swin_kernel, cudaFuncAttributeMaxDynamicSharedMemorySize, SM_TOTAL);
    cudaDriverEntryPointQueryResult qr;
    void* fn = nullptr;
    cudaGetDriverEntryPoint("cuTensorMapEncodeTiled", &fn, cudaEnableDefault, &qr);
    encode = (EncodeFn)fn;
  }
  CUtensorMap tm_x, tm_xq, tm_wqk, tm_wv;
  {
    cuuint64_t dims[5] = {32, 4, IMG, IMG / 4, 3};
    cuuint64_t strides[4] = {PIXB, ROWB, 4 * PIXB, 64};
    cuuint32_t es[5] = {1, 1, 1, 1, 1};
    cuuint32_t box[5] = {32, 4, 8, 2, 3}, boxq[5] = {32, 4, 4, 1, 1};
    encode(&tm_x, CU_TENSOR_MAP_DATA_TYPE_BFLOAT16, 5, d_in[0], dims, strides, box, es, CU_TENSOR_MAP_INTERLEAVE_NONE,
           CU_TENSOR_MAP_SWIZZLE_64B, CU_TENSOR_MAP_L2_PROMOTION_L2_128B, CU_TENSOR_MAP_FLOAT_OOB_FILL_NONE);
    encode(&tm_xq, CU_TENSOR_MAP_DATA_TYPE_BFLOAT16, 5, d_in[0], dims, strides, boxq, es, CU_TENSOR_MAP_INTERLEAVE_NONE,
           CU_TENSOR_MAP_SWIZZLE_64B, CU_TENSOR_MAP_L2_PROMOTION_L2_128B, CU_TENSOR_MAP_FLOAT_OOB_FILL_NONE);
    cuuint64_t qd[3] = {64, 96, 3}, qs[2] = {576, 128}, vd[3] = {32, 96, 3}, vs[2] = {576, 64};
    cuuint32_t qb[3] = {64, 96, 3}, vb[3] = {32, 96, 3};
    encode(&tm_wqk, CU_TENSOR_MAP_DATA_TYPE_BFLOAT16, 3, d_in[1], qd, qs, qb, es, CU_TENSOR_MAP_INTERLEAVE_NONE,
           CU_TENSOR_MAP_SWIZZLE_128B, CU_TENSOR_MAP_L2_PROMOTION_L2_256B, CU_TENSOR_MAP_FLOAT_OOB_FILL_NONE);
    encode(&tm_wv, CU_TENSOR_MAP_DATA_TYPE_BFLOAT16, 3, (char*)d_in[1] + 384, vd, vs, vb, es, CU_TENSOR_MAP_INTERLEAVE_NONE,
           CU_TENSOR_MAP_SWIZZLE_64B, CU_TENSOR_MAP_L2_PROMOTION_L2_256B, CU_TENSOR_MAP_FLOAT_OOB_FILL_NONE);
  }
  swin_kernel<<<sms, 384, SM_TOTAL>>>(
      (const __nv_bfloat16*)d_in[3], (const __nv_bfloat16*)d_in[4], (const __nv_bfloat16*)d_in[5], (const __nv_bfloat16*)d_in[6],
      (const int*)d_in[7], (const __nv_bfloat16*)d_in[2], (const __nv_bfloat16*)d_in[8], (__nv_bfloat16*)d_out,
      tm_wqk, tm_x, tm_wv, tm_xq);
}
```

```cpp
#include <cuda_runtime.h>
#include <cuda.h>
#include <cuda_bf16.h>
#include <stdint.h>
#include <type_traits>

#define TOKEN 4
namespace {

constexpr int IMG   = 384;
constexpr int NWX   = 48;
constexpr int NWIN  = NWX * NWX;
constexpr int PIXB  = 192;
constexpr int ROWB  = IMG * PIXB;
constexpr float LOG2E = 1.4426950408889634f;
constexpr float TAU_FAST_MAX = 50.f;

constexpr int SM_W    = 0;
constexpr int SM_WV   = 3 * 12288;
constexpr int SM_WO   = SM_W + 9 * 6144;
constexpr int SM_EB   = SM_WO + 12 * 1536;
constexpr int SM_WG   = SM_EB + 32768;
constexpr int WG_X    = 0;
constexpr int WG_K    = 12288;
constexpr int WG_V    = WG_K + 14336;
constexpr int WG_SZ   = WG_V + 14336;
constexpr int SM_TAB  = SM_WG + WG_SZ + WG_V + 4096;
constexpr int SM_WOR  = SM_WG + 2 * WG_SZ + WG_K;
constexpr int SM_SEL  = SM_WG + 3 * WG_SZ;
constexpr int SM_MISC = SM_SEL + 256;
constexpr int SM_BAR  = SM_MISC + 16;
constexpr int SM_SLOW = SM_BAR + 104;
constexpr int SM_PAR  = SM_BAR + 160;
constexpr int NENT    = 10;
constexpr int SM_WIN  = SM_PAR + 192;
constexpr int SM_GEN  = SM_WIN + 3 * NENT * 4;
constexpr int SM_TOTAL = SM_GEN + 3 * NENT * 4;
static_assert((SM_WIN & 7) == 0 && (NENT & 1) == 0, "list parity");

template <int SD> __device__ __forceinline__ void wgmma_ss_n192_t1(float (&d)[96], uint64_t da, uint64_t db) {
  if constexpr (SD) {
    asm volatile("{\n.reg .pred p;\nsetp.ne.b32 p, 1, 0;\n"
      "wgmma.mma_async.sync.aligned.m64n192k16.f32.bf16.bf16 {%0, %1, %2, %3, %4, %5, %6, %7, %8, %9, %10, %11, %12, %13, %14, %15, %16, %17, %18, %19, %20, %21, %22, %23, %24, %25, %26, %27, %28, %29, %30, %31, %32, %33, %34, %35, %36, %37, %38, %39, %40, %41, %42, %43, %44, %45, %46, %47, %48, %49, %50, %51, %52, %53, %54, %55, %56, %57, %58, %59, %60, %61, %62, %63, %64, %65, %66, %67, %68, %69, %70, %71, %72, %73, %74, %75, %76, %77, %78, %79, %80, %81, %82, %83, %84, %85, %86, %87, %88, %89, %90, %91, %92, %93, %94, %95}, %96, %97, p, 1, 1, 0, 1;\n}\n"
      : "+f"(d[0]), "+f"(d[1]), "+f"(d[2]), "+f"(d[3]), "+f"(d[4]), "+f"(d[5]), "+f"(d[6]), "+f"(d[7]), "+f"(d[8]), "+f"(d[9]), "+f"(d[10]), "+f"(d[11]), "+f"(d[12]), "+f"(d[13]), "+f"(d[14]), "+f"(d[15]), "+f"(d[16]), "+f"(d[17]), "+f"(d[18]), "+f"(d[19]), "+f"(d[20]), "+f"(d[21]), "+f"(d[22]), "+f"(d[23]), "+f"(d[24]), "+f"(d[25]), "+f"(d[26]), "+f"(d[27]), "+f"(d[28]), "+f"(d[29]), "+f"(d[30]), "+f"(d[31]), "+f"(d[32]), "+f"(d[33]), "+f"(d[34]), "+f"(d[35]), "+f"(d[36]), "+f"(d[37]), "+f"(d[38]), "+f"(d[39]), "+f"(d[40]), "+f"(d[41]), "+f"(d[42]), "+f"(d[43]), "+f"(d[44]), "+f"(d[45]), "+f"(d[46]), "+f"(d[47]), "+f"(d[48]), "+f"(d[49]), "+f"(d[50]), "+f"(d[51]), "+f"(d[52]), "+f"(d[53]), "+f"(d[54]), "+f"(d[55]), "+f"(d[56]), "+f"(d[57]), "+f"(d[58]), "+f"(d[59]), "+f"(d[60]), "+f"(d[61]), "+f"(d[62]), "+f"(d[63]), "+f"(d[64]), "+f"(d[65]), "+f"(d[66]), "+f"(d[67]), "+f"(d[68]), "+f"(d[69]), "+f"(d[70]), "+f"(d[71]), "+f"(d[72]), "+f"(d[73]), "+f"(d[74]), "+f"(d[75]), "+f"(d[76]), "+f"(d[77]), "+f"(d[78]), "+f"(d[79]), "+f"(d[80]), "+f"(d[81]), "+f"(d[82]), "+f"(d[83]), "+f"(d[84]), "+f"(d[85]), "+f"(d[86]), "+f"(d[87]), "+f"(d[88]), "+f"(d[89]), "+f"(d[90]), "+f"(d[91]), "+f"(d[92]), "+f"(d[93]), "+f"(d[94]), "+f"(d[95])
      : "l"(da), "l"(db));
  } else {
    asm volatile("{\n.reg .pred p;\nsetp.ne.b32 p, 0, 0;\n"
      "wgmma.mma_async.sync.aligned.m64n192k16.f32.bf16.bf16 {%0, %1, %2, %3, %4, %5, %6, %7, %8, %9, %10, %11, %12, %13, %14, %15, %16, %17, %18, %19, %20, %21, %22, %23, %24, %25, %26, %27, %28, %29, %30, %31, %32, %33, %34, %35, %36, %37, %38, %39, %40, %41, %42, %43, %44, %45, %46, %47, %48, %49, %50, %51, %52, %53, %54, %55, %56, %57, %58, %59, %60, %61, %62, %63, %64, %65, %66, %67, %68, %69, %70, %71, %72, %73, %74, %75, %76, %77, %78, %79, %80, %81, %82, %83, %84, %85, %86, %87, %88, %89, %90, %91, %92, %93, %94, %95}, %96, %97, p, 1, 1, 0, 1;\n}\n"
      : "=f"(d[0]), "=f"(d[1]), "=f"(d[2]), "=f"(d[3]), "=f"(d[4]), "=f"(d[5]), "=f"(d[6]), "=f"(d[7]), "=f"(d[8]), "=f"(d[9]), "=f"(d[10]), "=f"(d[11]), "=f"(d[12]), "=f"(d[13]), "=f"(d[14]), "=f"(d[15]), "=f"(d[16]), "=f"(d[17]), "=f"(d[18]), "=f"(d[19]), "=f"(d[20]), "=f"(d[21]), "=f"(d[22]), "=f"(d[23]), "=f"(d[24]), "=f"(d[25]), "=f"(d[26]), "=f"(d[27]), "=f"(d[28]), "=f"(d[29]), "=f"(d[30]), "=f"(d[31]), "=f"(d[32]), "=f"(d[33]), "=f"(d[34]), "=f"(d[35]), "=f"(d[36]), "=f"(d[37]), "=f"(d[38]), "=f"(d[39]), "=f"(d[40]), "=f"(d[41]), "=f"(d[42]), "=f"(d[43]), "=f"(d[44]), "=f"(d[45]), "=f"(d[46]), "=f"(d[47]), "=f"(d[48]), "=f"(d[49]), "=f"(d[50]), "=f"(d[51]), "=f"(d[52]), "=f"(d[53]), "=f"(d[54]), "=f"(d[55]), "=f"(d[56]), "=f"(d[57]), "=f"(d[58]), "=f"(d[59]), "=f"(d[60]), "=f"(d[61]), "=f"(d[62]), "=f"(d[63]), "=f"(d[64]), "=f"(d[65]), "=f"(d[66]), "=f"(d[67]), "=f"(d[68]), "=f"(d[69]), "=f"(d[70]), "=f"(d[71]), "=f"(d[72]), "=f"(d[73]), "=f"(d[74]), "=f"(d[75]), "=f"(d[76]), "=f"(d[77]), "=f"(d[78]), "=f"(d[79]), "=f"(d[80]), "=f"(d[81]), "=f"(d[82]), "=f"(d[83]), "=f"(d[84]), "=f"(d[85]), "=f"(d[86]), "=f"(d[87]), "=f"(d[88]), "=f"(d[89]), "=f"(d[90]), "=f"(d[91]), "=f"(d[92]), "=f"(d[93]), "=f"(d[94]), "=f"(d[95])
      : "l"(da), "l"(db));
  }
}
template <int SD> __device__ __forceinline__ void wgmma_ss_n96_t1(float (&d)[48], uint64_t da, uint64_t db) {
  if constexpr (SD) {
    asm volatile("{\n.reg .pred p;\nsetp.ne.b32 p, 1, 0;\n"
      "wgmma.mma_async.sync.aligned.m64n96k16.f32.bf16.bf16 {%0, %1, %2, %3, %4, %5, %6, %7, %8, %9, %10, %11, %12, %13, %14, %15, %16, %17, %18, %19, %20, %21, %22, %23, %24, %25, %26, %27, %28, %29, %30, %31, %32, %33, %34, %35, %36, %37, %38, %39, %40, %41, %42, %43, %44, %45, %46, %47}, %48, %49, p, 1, 1, 0, 1;\n}\n"
      : "+f"(d[0]), "+f"(d[1]), "+f"(d[2]), "+f"(d[3]), "+f"(d[4]), "+f"(d[5]), "+f"(d[6]), "+f"(d[7]), "+f"(d[8]), "+f"(d[9]), "+f"(d[10]), "+f"(d[11]), "+f"(d[12]), "+f"(d[13]), "+f"(d[14]), "+f"(d[15]), "+f"(d[16]), "+f"(d[17]), "+f"(d[18]), "+f"(d[19]), "+f"(d[20]), "+f"(d[21]), "+f"(d[22]), "+f"(d[23]), "+f"(d[24]), "+f"(d[25]), "+f"(d[26]), "+f"(d[27]), "+f"(d[28]), "+f"(d[29]), "+f"(d[30]), "+f"(d[31]), "+f"(d[32]), "+f"(d[33]), "+f"(d[34]), "+f"(d[35]), "+f"(d[36]), "+f"(d[37]), "+f"(d[38]), "+f"(d[39]), "+f"(d[40]), "+f"(d[41]), "+f"(d[42]), "+f"(d[43]), "+f"(d[44]), "+f"(d[45]), "+f"(d[46]), "+f"(d[47])
      : "l"(da), "l"(db));
  } else {
    asm volatile("{\n.reg .pred p;\nsetp.ne.b32 p, 0, 0;\n"
      "wgmma.mma_async.sync.aligned.m64n96k16.f32.bf16.bf16 {%0, %1, %2, %3, %4, %5, %6, %7, %8, %9, %10, %11, %12, %13, %14, %15, %16, %17, %18, %19, %20, %21, %22, %23, %24, %25, %26, %27, %28, %29, %30, %31, %32, %33, %34, %35, %36, %37, %38, %39, %40, %41, %42, %43, %44, %45, %46, %47}, %48, %49, p, 1, 1, 0, 1;\n}\n"
      : "=f"(d[0]), "=f"(d[1]), "=f"(d[2]), "=f"(d[3]), "=f"(d[4]), "=f"(d[5]), "=f"(d[6]), "=f"(d[7]), "=f"(d[8]), "=f"(d[9]), "=f"(d[10]), "=f"(d[11]), "=f"(d[12]), "=f"(d[13]), "=f"(d[14]), "=f"(d[15]), "=f"(d[16]), "=f"(d[17]), "=f"(d[18]), "=f"(d[19]), "=f"(d[20]), "=f"(d[21]), "=f"(d[22]), "=f"(d[23]), "=f"(d[24]), "=f"(d[25]), "=f"(d[26]), "=f"(d[27]), "=f"(d[28]), "=f"(d[29]), "=f"(d[30]), "=f"(d[31]), "=f"(d[32]), "=f"(d[33]), "=f"(d[34]), "=f"(d[35]), "=f"(d[36]), "=f"(d[37]), "=f"(d[38]), "=f"(d[39]), "=f"(d[40]), "=f"(d[41]), "=f"(d[42]), "=f"(d[43]), "=f"(d[44]), "=f"(d[45]), "=f"(d[46]), "=f"(d[47])
      : "l"(da), "l"(db));
  }
}
template <int SD> __device__ __forceinline__ void wgmma_rs_n96_t1(float (&d)[48], uint32_t a0, uint32_t a1, uint32_t a2, uint32_t a3, uint64_t db) {
  if constexpr (SD) {
    asm volatile("{\n.reg .pred p;\nsetp.ne.b32 p, 1, 0;\n"
      "wgmma.mma_async.sync.aligned.m64n96k16.f32.bf16.bf16 {%0, %1, %2, %3, %4, %5, %6, %7, %8, %9, %10, %11, %12, %13, %14, %15, %16, %17, %18, %19, %20, %21, %22, %23, %24, %25, %26, %27, %28, %29, %30, %31, %32, %33, %34, %35, %36, %37, %38, %39, %40, %41, %42, %43, %44, %45, %46, %47}, {%48, %49, %50, %51}, %52, p, 1, 1, 1;\n}\n"
      : "+f"(d[0]), "+f"(d[1]), "+f"(d[2]), "+f"(d[3]), "+f"(d[4]), "+f"(d[5]), "+f"(d[6]), "+f"(d[7]), "+f"(d[8]), "+f"(d[9]), "+f"(d[10]), "+f"(d[11]), "+f"(d[12]), "+f"(d[13]), "+f"(d[14]), "+f"(d[15]), "+f"(d[16]), "+f"(d[17]), "+f"(d[18]), "+f"(d[19]), "+f"(d[20]), "+f"(d[21]), "+f"(d[22]), "+f"(d[23]), "+f"(d[24]), "+f"(d[25]), "+f"(d[26]), "+f"(d[27]), "+f"(d[28]), "+f"(d[29]), "+f"(d[30]), "+f"(d[31]), "+f"(d[32]), "+f"(d[33]), "+f"(d[34]), "+f"(d[35]), "+f"(d[36]), "+f"(d[37]), "+f"(d[38]), "+f"(d[39]), "+f"(d[40]), "+f"(d[41]), "+f"(d[42]), "+f"(d[43]), "+f"(d[44]), "+f"(d[45]), "+f"(d[46]), "+f"(d[47])
      : "r"(a0), "r"(a1), "r"(a2), "r"(a3), "l"(db));
  } else {
    asm volatile("{\n.reg .pred p;\nsetp.ne.b32 p, 0, 0;\n"
      "wgmma.mma_async.sync.aligned.m64n96k16.f32.bf16.bf16 {%0, %1, %2, %3, %4, %5, %6, %7, %8, %9, %10, %11, %12, %13, %14, %15, %16, %17, %18, %19, %20, %21, %22, %23, %24, %25, %26, %27, %28, %29, %30, %31, %32, %33, %34, %35, %36, %37, %38, %39, %40, %41, %42, %43, %44, %45, %46, %47}, {%48, %49, %50, %51}, %52, p, 1, 1, 1;\n}\n"
      : "=f"(d[0]), "=f"(d[1]), "=f"(d[2]), "=f"(d[3]), "=f"(d[4]), "=f"(d[5]), "=f"(d[6]), "=f"(d[7]), "=f"(d[8]), "=f"(d[9]), "=f"(d[10]), "=f"(d[11]), "=f"(d[12]), "=f"(d[13]), "=f"(d[14]), "=f"(d[15]), "=f"(d[16]), "=f"(d[17]), "=f"(d[18]), "=f"(d[19]), "=f"(d[20]), "=f"(d[21]), "=f"(d[22]), "=f"(d[23]), "=f"(d[24]), "=f"(d[25]), "=f"(d[26]), "=f"(d[27]), "=f"(d[28]), "=f"(d[29]), "=f"(d[30]), "=f"(d[31]), "=f"(d[32]), "=f"(d[33]), "=f"(d[34]), "=f"(d[35]), "=f"(d[36]), "=f"(d[37]), "=f"(d[38]), "=f"(d[39]), "=f"(d[40]), "=f"(d[41]), "=f"(d[42]), "=f"(d[43]), "=f"(d[44]), "=f"(d[45]), "=f"(d[46]), "=f"(d[47])
      : "r"(a0), "r"(a1), "r"(a2), "r"(a3), "l"(db));
  }
}
template <int SD> __device__ __forceinline__ void wgmma_rs_n64_t0(float (&d)[32], uint32_t a0, uint32_t a1, uint32_t a2, uint32_t a3, uint64_t db) {
  if constexpr (SD) {
    asm volatile("{\n.reg .pred p;\nsetp.ne.b32 p, 1, 0;\n"
      "wgmma.mma_async.sync.aligned.m64n64k16.f32.bf16.bf16 {%0, %1, %2, %3, %4, %5, %6, %7, %8, %9, %10, %11, %12, %13, %14, %15, %16, %17, %18, %19, %20, %21, %22, %23, %24, %25, %26, %27, %28, %29, %30, %31}, {%32, %33, %34, %35}, %36, p, 1, 1, 0;\n}\n"
      : "+f"(d[0]), "+f"(d[1]), "+f"(d[2]), "+f"(d[3]), "+f"(d[4]), "+f"(d[5]), "+f"(d[6]), "+f"(d[7]), "+f"(d[8]), "+f"(d[9]), "+f"(d[10]), "+f"(d[11]), "+f"(d[12]), "+f"(d[13]), "+f"(d[14]), "+f"(d[15]), "+f"(d[16]), "+f"(d[17]), "+f"(d[18]), "+f"(d[19]), "+f"(d[20]), "+f"(d[21]), "+f"(d[22]), "+f"(d[23]), "+f"(d[24]), "+f"(d[25]), "+f"(d[26]), "+f"(d[27]), "+f"(d[28]), "+f"(d[29]), "+f"(d[30]), "+f"(d[31])
      : "r"(a0), "r"(a1), "r"(a2), "r"(a3), "l"(db));
  } else {
    asm volatile("{\n.reg .pred p;\nsetp.ne.b32 p, 0, 0;\n"
      "wgmma.mma_async.sync.aligned.m64n64k16.f32.bf16.bf16 {%0, %1, %2, %3, %4, %5, %6, %7, %8, %9, %10, %11, %12, %13, %14, %15, %16, %17, %18, %19, %20, %21, %22, %23, %24, %25, %26, %27, %28, %29, %30, %31}, {%32, %33, %34, %35}, %36, p, 1, 1, 0;\n}\n"
      : "=f"(d[0]), "=f"(d[1]), "=f"(d[2]), "=f"(d[3]), "=f"(d[4]), "=f"(d[5]), "=f"(d[6]), "=f"(d[7]), "=f"(d[8]), "=f"(d[9]), "=f"(d[10]), "=f"(d[11]), "=f"(d[12]), "=f"(d[13]), "=f"(d[14]), "=f"(d[15]), "=f"(d[16]), "=f"(d[17]), "=f"(d[18]), "=f"(d[19]), "=f"(d[20]), "=f"(d[21]), "=f"(d[22]), "=f"(d[23]), "=f"(d[24]), "=f"(d[25]), "=f"(d[26]), "=f"(d[27]), "=f"(d[28]), "=f"(d[29]), "=f"(d[30]), "=f"(d[31])
      : "r"(a0), "r"(a1), "r"(a2), "r"(a3), "l"(db));
  }
}
template <int SD> __device__ __forceinline__ void wgmma_rs_n32_t1(float (&d)[16], uint32_t a0, uint32_t a1, uint32_t a2, uint32_t a3, uint64_t db) {
  if constexpr (SD) {
    asm volatile("{\n.reg .pred p;\nsetp.ne.b32 p, 1, 0;\n"
      "wgmma.mma_async.sync.aligned.m64n32k16.f32.bf16.bf16 {%0, %1, %2, %3, %4, %5, %6, %7, %8, %9, %10, %11, %12, %13, %14, %15}, {%16, %17, %18, %19}, %20, p, 1, 1, 1;\n}\n"
      : "+f"(d[0]), "+f"(d[1]), "+f"(d[2]), "+f"(d[3]), "+f"(d[4]), "+f"(d[5]), "+f"(d[6]), "+f"(d[7]), "+f"(d[8]), "+f"(d[9]), "+f"(d[10]), "+f"(d[11]), "+f"(d[12]), "+f"(d[13]), "+f"(d[14]), "+f"(d[15])
      : "r"(a0), "r"(a1), "r"(a2), "r"(a3), "l"(db));
  } else {
    asm volatile("{\n.reg .pred p;\nsetp.ne.b32 p, 0, 0;\n"
      "wgmma.mma_async.sync.aligned.m64n32k16.f32.bf16.bf16 {%0, %1, %2, %3, %4, %5, %6, %7, %8, %9, %10, %11, %12, %13, %14, %15}, {%16, %17, %18, %19}, %20, p, 1, 1, 1;\n}\n"
      : "=f"(d[0]), "=f"(d[1]), "=f"(d[2]), "=f"(d[3]), "=f"(d[4]), "=f"(d[5]), "=f"(d[6]), "=f"(d[7]), "=f"(d[8]), "=f"(d[9]), "=f"(d[10]), "=f"(d[11]), "=f"(d[12]), "=f"(d[13]), "=f"(d[14]), "=f"(d[15])
      : "r"(a0), "r"(a1), "r"(a2), "r"(a3), "l"(db));
  }
}
template <int SD> __device__ __forceinline__ void wgmma_rs_n8_t0(float (&d)[4], uint32_t a0, uint32_t a1, uint32_t a2, uint32_t a3, uint64_t db) {
  if constexpr (SD) {
    asm volatile("{\n.reg .pred p;\nsetp.ne.b32 p, 1, 0;\n"
      "wgmma.mma_async.sync.aligned.m64n8k16.f32.bf16.bf16 {%0, %1, %2, %3}, {%4, %5, %6, %7}, %8, p, 1, 1, 0;\n}\n"
      : "+f"(d[0]), "+f"(d[1]), "+f"(d[2]), "+f"(d[3])
      : "r"(a0), "r"(a1), "r"(a2), "r"(a3), "l"(db));
  } else {
    asm volatile("{\n.reg .pred p;\nsetp.ne.b32 p, 0, 0;\n"
      "wgmma.mma_async.sync.aligned.m64n8k16.f32.bf16.bf16 {%0, %1, %2, %3}, {%4, %5, %6, %7}, %8, p, 1, 1, 0;\n}\n"
      : "=f"(d[0]), "=f"(d[1]), "=f"(d[2]), "=f"(d[3])
      : "r"(a0), "r"(a1), "r"(a2), "r"(a3), "l"(db));
  }
}

__device__ __forceinline__ void wg_fence()  { asm volatile("wgmma.fence.sync.aligned;" ::: "memory"); }
__device__ __forceinline__ void wg_commit() { asm volatile("wgmma.commit_group.sync.aligned;" ::: "memory"); }
template <int N> __device__ __forceinline__ void wg_wait() { asm volatile("wgmma.wait_group.sync.aligned %0;" :: "n"(N) : "memory"); }
template <int N> __device__ __forceinline__ void fence_regs(float (&d)[N]) {
#pragma unroll
  for (int i = 0; i < N; i++) asm volatile("" : "+f"(d[i]) :: "memory");
}
__device__ __forceinline__ constexpr uint64_t mk_desc(uint32_t addr, uint32_t lbo, uint32_t sbo, uint32_t swz) {
  return (uint64_t)(addr >> 4) | ((uint64_t)(lbo >> 4) << 16) | ((uint64_t)(sbo >> 4) << 32) | ((uint64_t)swz << 62);
}
__device__ __forceinline__ uint32_t pack_bf16(float lo, float hi) {
  uint32_t r; asm("cvt.rn.bf16x2.f32 %0, %1, %2;" : "=r"(r) : "f"(hi), "f"(lo)); return r;
}
__device__ __forceinline__ uint32_t hmul2(uint32_t a, uint32_t b) {
  uint32_t r; asm("mul.rn.bf16x2 %0, %1, %2;" : "=r"(r) : "r"(a), "r"(b)); return r;
}
template <int HI> __device__ __forceinline__ uint32_t hmul2_b(uint32_t a, uint32_t b) {
  uint32_t r;
  if (HI) asm("{\n.reg .b16 l, h;\n.reg .b32 t;\nmov.b32 {l, h}, %2;\nmov.b32 t, {h, h};\nmul.rn.bf16x2 %0, %1, t;\n}\n" : "=r"(r) : "r"(a), "r"(b));
  else    asm("{\n.reg .b16 l, h;\n.reg .b32 t;\nmov.b32 {l, h}, %2;\nmov.b32 t, {l, l};\nmul.rn.bf16x2 %0, %1, t;\n}\n" : "=r"(r) : "r"(a), "r"(b));
  return r;
}
__device__ __forceinline__ uint32_t hfma2(uint32_t a, uint32_t b, uint32_t c) {
  uint32_t r; asm("fma.rn.bf16x2 %0, %1, %2, %3;" : "=r"(r) : "r"(a), "r"(b), "r"(c)); return r;
}
__device__ __forceinline__ float ex2(float x) { float r; asm("ex2.approx.ftz.f32 %0, %1;" : "=f"(r) : "f"(x)); return r; }
__device__ __forceinline__ float rsq(float x) { float r; asm("rsqrt.approx.ftz.f32 %0, %1;" : "=f"(r) : "f"(x)); return r; }
__device__ __forceinline__ float rcp(float x) { float r; asm("rcp.approx.ftz.f32 %0, %1;" : "=f"(r) : "f"(x)); return r; }
__device__ __forceinline__ void stsm4(uint32_t addr, uint32_t r0, uint32_t r1, uint32_t r2, uint32_t r3) {
  asm volatile("stmatrix.sync.aligned.m8n8.x4.shared.b16 [%0], {%1,%2,%3,%4};" :: "r"(addr), "r"(r0), "r"(r1), "r"(r2), "r"(r3) : "memory");
}
__device__ __forceinline__ void fence_async() { asm volatile("fence.proxy.async.shared::cta;" ::: "memory"); }
__device__ __forceinline__ void bar_sync_n(int id, int n) { asm volatile("bar.sync %0, %1;" :: "r"(id), "r"(n) : "memory"); }
__device__ __forceinline__ void bar_arrive_n(int id, int n) { asm volatile("bar.arrive %0, %1;" :: "r"(id), "r"(n) : "memory"); }
__device__ __forceinline__ bool bar_wg_or(int id, bool v) {
  uint32_t r;
  asm volatile("{\n.reg .pred p, q;\nsetp.ne.u32 q, %2, 0;\nbar.red.or.pred p, %1, 128, q;\nselp.u32 %0, 0, 1, p;\n}\n"
               : "=r"(r) : "r"(id), "r"((uint32_t)v) : "memory");
  return __ballot_sync(0xffffffffu, r != 0) == 0;
}
__device__ __forceinline__ void mbar_init(uint32_t bar, uint32_t cnt) { asm volatile("mbarrier.init.shared::cta.b64 [%0], %1;" :: "r"(bar), "r"(cnt) : "memory"); }
__device__ __forceinline__ void mbar_expect(uint32_t bar, uint32_t bytes) {
  asm volatile("mbarrier.arrive.expect_tx.shared::cta.b64 _, [%0], %1;" :: "r"(bar), "r"(bytes) : "memory");
}
__device__ __forceinline__ void mbar_arrive(uint32_t bar) { asm volatile("mbarrier.arrive.shared::cta.b64 _, [%0];" :: "r"(bar) : "memory"); }
__device__ __forceinline__ void mbar_wait(uint32_t bar, uint32_t parity) {
  asm volatile("{\n.reg .pred p;\n.reg .u32 n;\nmov.u32 n, 0;\n"
               "LW_%=:\nmbarrier.try_wait.parity.shared::cta.b64 p, [%0], %1;\n@p bra.uni LD_%=;\n"
               "add.u32 n, n, 1;\nsetp.lt.u32 p, n, 4194304;\n@p bra.uni LW_%=;\ntrap;\nLD_%=:\n}\n"
               :: "r"(bar), "r"(parity) : "memory");
}
__device__ __forceinline__ void tma5(uint32_t dst, const CUtensorMap* m, uint32_t bar, int c0, int c1, int c2, int c3, int c4) {
  asm volatile("cp.async.bulk.tensor.5d.shared::cluster.global.mbarrier::complete_tx::bytes [%0], [%1, {%3, %4, %5, %6, %7}], [%2];"
               :: "r"(dst), "l"(m), "r"(bar), "r"(c0), "r"(c1), "r"(c2), "r"(c3), "r"(c4) : "memory");
}
__device__ __forceinline__ void tma3(uint32_t dst, const CUtensorMap* m, uint32_t bar, int c0, int c1, int c2) {
  asm volatile("cp.async.bulk.tensor.3d.shared::cluster.global.mbarrier::complete_tx::bytes [%0], [%1, {%3, %4, %5}], [%2];"
               :: "r"(dst), "l"(m), "r"(bar), "r"(c0), "r"(c1), "r"(c2) : "memory");
}
__device__ __forceinline__ void bulk_g2s(uint32_t dst, const void* src, uint32_t bytes, uint32_t bar) {
  asm volatile("cp.async.bulk.shared::cluster.global.mbarrier::complete_tx::bytes [%0], [%1], %2, [%3];"
               :: "r"(dst), "l"(src), "r"(bytes), "r"(bar) : "memory");
}
__device__ __forceinline__ uint32_t lds32(uint32_t addr) {
  uint32_t v; asm volatile("ld.shared.u32 %0, [%1];" : "=r"(v) : "r"(addr)); return v;
}
__device__ __forceinline__ uint64_t opaque(uint64_t v) { asm volatile("" : "+l"(v)); return v; }
__device__ __forceinline__ uint4 lds128(uint32_t addr) {
  uint4 v; asm volatile("ld.shared.v4.u32 {%0,%1,%2,%3}, [%4];" : "=r"(v.x), "=r"(v.y), "=r"(v.z), "=r"(v.w) : "r"(addr)); return v;
}
__device__ __forceinline__ uint4 ldg128_stream(const void* p) {
  uint4 v; asm volatile("ld.global.nc.L1::no_allocate.v4.u32 {%0,%1,%2,%3}, [%4];" : "=r"(v.x), "=r"(v.y), "=r"(v.z), "=r"(v.w) : "l"(p)); return v;
}
__device__ __forceinline__ void stg128(void* p, uint32_t a, uint32_t b, uint32_t c, uint32_t d) {
  asm volatile("st.global.v4.u32 [%0], {%1,%2,%3,%4};" :: "l"(p), "r"(a), "r"(b), "r"(c), "r"(d) : "memory");
}
__device__ __forceinline__ void prefetch_l2(const void* p, uint32_t bytes) {
  asm volatile("cp.async.bulk.prefetch.L2.global [%0], %1;" :: "l"(p), "r"(bytes) : "memory");
}
__device__ __forceinline__ bool elect_one() {
  uint32_t r; asm volatile("{\n.reg .pred p;\nelect.sync _|p, 0xffffffff;\nselp.u32 %0, 1, 0, p;\n}\n" : "=r"(r)); return r != 0;
}
__device__ __forceinline__ float bf_lo(uint32_t u) { return __uint_as_float(u << 16); }
__device__ __forceinline__ float bf_hi(uint32_t u) { return __uint_as_float(u & 0xFFFF0000u); }
__device__ __forceinline__ float rbf(float x) { return bf_lo(pack_bf16(x, 0.f)); }
__device__ __forceinline__ int orig_tok(int r) { return ((r & 31) >> 2) * 8 + (r >> 5) * 4 + (r & 3); }

__device__ __forceinline__ int slot_window(int s, bool g132) {
  const int A0 = g132 ? 396 + 264 + 60 : 47 * 47, A1 = A0 + 72, B0 = g132 ? 3 * 396 + 264 + 60 : A1, B1 = B0 + 23;
  const int i = s - (s >= B1 ? 95 : s >= A1 ? 72 : 0);
  const int k = s >= B0 ? s - B0 + 72 : s - A0;
  const bool border = (s >= A0 && s < A1) || (s >= B0 && s < B1);
  const int iy = (i * 2789) >> 17;
  return border ? (k < 48 ? (47 << 8 | k) : ((k - 48) << 8 | 47)) : (iy << 8 | (i - iy * 47));
}

#define EB_WORD(e, j, a) ((((a) ^ ((j) & 1)) == 0) ? (e).x : (((a) ^ ((j) & 1)) == 1) ? (e).y : (((a) ^ ((j) & 1)) == 2) ? (e).z : (e).w)

__device__ __forceinline__ void load_eb(uint32_t (&e)[16], uint32_t eb_addr) {
#pragma unroll
  for (int j = 0; j < 4; j++) {
    const uint4 v = lds128(eb_addr + j * 2048);
#pragma unroll
    for (int a = 0; a < 4; a++) e[4 * j + a] = EB_WORD(v, j, a);
  }
}
__device__ __forceinline__ void softmax_fast(const float (&s)[32], uint32_t (&p)[16]) {
#pragma unroll
  for (int i = 0; i < 16; i++) p[i] = hmul2(pack_bf16(ex2(s[2 * i]), ex2(s[2 * i + 1])), p[i]);
}
__device__ __forceinline__ uint32_t hmax2(uint32_t a, uint32_t b) {
  uint32_t r; asm("max.bf16x2 %0, %1, %2;" : "=r"(r) : "r"(a), "r"(b)); return r;
}
__device__ __forceinline__ uint32_t hmax2_nan(uint32_t a, uint32_t b) {
  uint32_t r; asm("max.NaN.bf16x2 %0, %1, %2;" : "=r"(r) : "r"(a), "r"(b)); return r;
}
__device__ __forceinline__ float quad_max(float m) {
  m = fmaxf(m, __shfl_xor_sync(0xffffffffu, m, 1));
  return fmaxf(m, __shfl_xor_sync(0xffffffffu, m, 2));
}
__device__ __forceinline__ void softmax_true_max(const float (&s)[32], uint32_t (&p)[16]) {
  float m0 = s[0], m1 = s[2];
#pragma unroll
  for (int g = 0; g < 8; g++) {
    m0 = fmaxf(m0, fmaxf(s[4 * g + 0], s[4 * g + 1]));
    m1 = fmaxf(m1, fmaxf(s[4 * g + 2], s[4 * g + 3]));
  }
  m0 = quad_max(m0); m1 = quad_max(m1);
  uint32_t n0 = 0, n1 = 0;
#pragma unroll
  for (int g = 0; g < 8; g++) {
    p[2 * g + 0] = hmul2(pack_bf16(ex2(s[4 * g + 0] - m0), ex2(s[4 * g + 1] - m0)), p[2 * g + 0]);
    p[2 * g + 1] = hmul2(pack_bf16(ex2(s[4 * g + 2] - m1), ex2(s[4 * g + 3] - m1)), p[2 * g + 1]);
    n0 = hmax2(n0, p[2 * g]); n1 = hmax2(n1, p[2 * g + 1]);
  }
  const uint32_t r = pack_bf16(rcp(quad_max(fmaxf(bf_lo(n0), bf_hi(n0)))), rcp(quad_max(fmaxf(bf_lo(n1), bf_hi(n1)))));
#pragma unroll
  for (int g = 0; g < 8; g++) { p[2 * g] = hmul2_b<0>(p[2 * g], r); p[2 * g + 1] = hmul2_b<1>(p[2 * g + 1], r); }
}
template <int H> __device__ __forceinline__ void issue_s(float (&s)[32], const uint32_t (&q)[24], uint64_t dK) {
  constexpr int Q0 = (H == 0 ? 0 : H == 1 ? 4 : H == 2 ? 12 : 16), P0 = (H == 0 ? 0 : H == 1 ? 3 : H == 2 ? 7 : 10);
  wgmma_rs_n64_t0<0>(s, q[Q0], q[Q0 + 1], q[Q0 + 2], q[Q0 + 3], dK + P0 * 64);
  wgmma_rs_n64_t0<1>(s, q[Q0 + 4], q[Q0 + 5], q[Q0 + 6], q[Q0 + 7], dK + P0 * 64 + 128);
}
template <int H> __device__ __forceinline__ void issue_pv(float (&o)[16], const uint32_t (&p)[16], uint64_t dV) {
  constexpr int P0 = (H == 0 ? 0 : H == 1 ? 3 : H == 2 ? 7 : 10);
  wgmma_rs_n32_t1<0>(o, p[0], p[1], p[2], p[3], dV + P0 * 64);
  wgmma_rs_n32_t1<1>(o, p[4], p[5], p[6], p[7], dV + P0 * 64 + 16);
  wgmma_rs_n32_t1<1>(o, p[8], p[9], p[10], p[11], dV + P0 * 64 + 32);
  wgmma_rs_n32_t1<1>(o, p[12], p[13], p[14], p[15], dV + P0 * 64 + 48);
}
__device__ __forceinline__ void issue_proj(float (&d)[48], uint64_t dX, uint64_t dW) {
#pragma unroll
  for (int s = 0; s < 6; s++) {
    const uint64_t a = dX + (s >> 1) * 256 + (s & 1) * 2, b = dW + s * 64;
    if (s == 0) wgmma_ss_n96_t1<0>(d, a, b); else wgmma_ss_n96_t1<1>(d, a, b);
  }
}
__device__ __forceinline__ void issue_qk(float (&d)[96], uint64_t dX, uint64_t dW) {
#pragma unroll
  for (int s = 0; s < 6; s++) {
    const uint64_t a = dX + (s >> 1) * 256 + (s & 1) * 2, b = dW + s * 128;
    if (s == 0) wgmma_ss_n192_t1<0>(d, a, b); else wgmma_ss_n192_t1<1>(d, a, b);
  }
}
__device__ __forceinline__ void pack_sumsq(const float* a, uint32_t (&f)[24], uint32_t (&sq)[8], uint32_t init) {
#pragma unroll
  for (int i = 0; i < 24; i++) f[i] = pack_bf16(a[2 * i], a[2 * i + 1]);
#pragma unroll
  for (int h = 0; h < 4; h++)
#pragma unroll
    for (int r = 0; r < 2; r++) {
      uint32_t u = f[6 * h + r], v = f[6 * h + 2 + r], w = f[6 * h + 4 + r];
      sq[2 * h + r] = hfma2(w, w, hfma2(v, v, hfma2(u, u, init)));
    }
}
__device__ __forceinline__ void scale_heads(uint32_t (&f)[24], const float (&r)[8]) {
#pragma unroll
  for (int h = 0; h < 4; h++) {
    const uint32_t p = pack_bf16(r[2 * h], r[2 * h + 1]);
#pragma unroll
    for (int c = 0; c < 3; c++) {
      f[6 * h + 2 * c] = hmul2_b<0>(f[6 * h + 2 * c], p);
      f[6 * h + 2 * c + 1] = hmul2_b<1>(f[6 * h + 2 * c + 1], p);
    }
  }
}
template <int ODD> __device__ __forceinline__ void norm_o(const float (&o)[16], uint32_t* of) {
  constexpr int SO = ODD ? 0 : 12, VO = ODD ? 4 : 0;
  const uint32_t p = pack_bf16(rcp(o[SO]), rcp(o[SO + 2]));
#pragma unroll
  for (int g = 0; g < 3; g++) {
    of[2 * g + 0] = hmul2_b<0>(pack_bf16(o[VO + 4 * g + 0], o[VO + 4 * g + 1]), p);
    of[2 * g + 1] = hmul2_b<1>(pack_bf16(o[VO + 4 * g + 2], o[VO + 4 * g + 3]), p);
  }
}

#define TL(i)
#define TG(i)

constexpr int BAR_KV = 1;
constexpr int BAR_AUX = 4;
constexpr int BAR_TAB = 7, BAR_SETUP = 8, BAR_PAR = 9;
constexpr int NO_TICKET = 0xFF;
#define TPOS 3
#define ORDER 2
#define BORDER_EXTRA 1
constexpr int MB_WQK = 0, MB_X = 8, MB_KV = 32, MB_WV = 56, MB_WO = 64, MB_TURN = 72, MB_RDY = 128, MB_WOC = 136;
constexpr uint32_t sb = 1024, mbar = sb + SM_BAR;
constexpr uint32_t EPS8 = 0x2A0D2A0Du;

__device__ __forceinline__ void load_x_interior(const CUtensorMap* tm_x, int w, int g) {
  mbar_expect(mbar + MB_X + 8 * g, 12288);
  tma5(sb + SM_WG + g * WG_SZ + WG_X, tm_x, mbar + MB_X + 8 * g, 0, 0, ((w >> 8) & 255) * 8 + 4, (w & 255) * 2 + 1, 0);
}
__device__ __forceinline__ void load_x(const CUtensorMap* tm_x, const CUtensorMap* tm_xq, int w, int g) {
  const uint32_t dst = sb + SM_WG + g * WG_SZ + WG_X, bar = mbar + MB_X + 8 * g;
  const int wy = (w >> 8) & 255, wx = w & 255;
  mbar_expect(bar, 12288);
  if (wy != NWX - 1 && wx != NWX - 1) {
    tma5(dst, tm_x, bar, 0, 0, wy * 8 + 4, wx * 2 + 1, 0);
  } else {
#pragma unroll 1
    for (int i = 0; i < 12; i++) {
      const int q = i & 3, c = i >> 2;
      int y = wy * 8 + 4 + (q & 1) * 4; if (y >= IMG) y -= IMG;
      int xq = wx * 2 + 1 + (q >> 1);   if (xq >= IMG / 4) xq -= IMG / 4;
      tma5(dst + i * 1024, tm_xq, bar, 0, 0, y, xq, c);
    }
  }
}
__device__ __forceinline__ uint32_t mask_off(int w) { return (uint32_t)(((w >> 8) & 255) * NWX + (w & 255)) * 8192u; }
__device__ __forceinline__ int lds_uniform(uint32_t addr) { return __shfl_sync(0xffffffffu, lds32(addr), 0); }

__device__ __forceinline__ void qkv_epilogue(float (&qk)[96], uint32_t (&qa)[24], uint64_t dX, uint64_t dWv, uint32_t k_dst) {
  uint32_t ka[24], sk[8], sq[8];
  float k01[4], k23[4], q01[4], q23[4], vv[48];
  constexpr uint64_t dSel = mk_desc(sb + SM_SEL, 128, 256, 0);
  wg_wait<0>(); fence_regs(qk);
  pack_sumsq(qk + 48, ka, sk, EPS8);
  pack_sumsq(qk, qa, sq, EPS8);
  wg_fence();
  wgmma_rs_n8_t0<0>(k01, sk[0], sk[1], sk[2], sk[3], dSel);
  wgmma_rs_n8_t0<0>(k23, sk[4], sk[5], sk[6], sk[7], dSel);
  wgmma_rs_n8_t0<0>(q01, sq[0], sq[1], sq[2], sq[3], dSel);
  wgmma_rs_n8_t0<0>(q23, sq[4], sq[5], sq[6], sq[7], dSel);
  wg_commit();
  issue_proj(vv, dX, dWv); wg_commit();
  const uint4 qs = lds128(sb + SM_MISC);
  wg_wait<1>(); fence_regs(k01); fence_regs(k23); fence_regs(q01); fence_regs(q23);
  const float rk[8] = {rsq(k01[0]), rsq(k01[2]), rsq(k01[1]), rsq(k01[3]), rsq(k23[0]), rsq(k23[2]), rsq(k23[1]), rsq(k23[3])};
  scale_heads(ka, rk);
#pragma unroll
  for (int i = 0; i < 6; i++) stsm4(k_dst + (i + (i >= 3)) * 1024, ka[2 * i], ka[2 * i + 1], ka[12 + 2 * i], ka[12 + 2 * i + 1]);
  wg_wait<0>(); fence_regs(vv);
#pragma unroll
  for (int i = 0; i < 6; i++)
    stsm4(k_dst + (WG_V - WG_K) + (i + (i >= 3)) * 1024, pack_bf16(vv[4 * i], vv[4 * i + 1]), pack_bf16(vv[4 * i + 2], vv[4 * i + 3]),
          pack_bf16(vv[24 + 4 * i], vv[24 + 4 * i + 1]), pack_bf16(vv[24 + 4 * i + 2], vv[24 + 4 * i + 3]));
  const float s0 = __uint_as_float(qs.x), s1 = __uint_as_float(qs.y), s2 = __uint_as_float(qs.z), s3 = __uint_as_float(qs.w);
  const float rq[8] = {rsq(q01[0]) * s0, rsq(q01[2]) * s0, rsq(q01[1]) * s1, rsq(q01[3]) * s1,
                       rsq(q23[0]) * s2, rsq(q23[2]) * s2, rsq(q23[1]) * s3, rsq(q23[3]) * s3};
  scale_heads(qa, rq);
  fence_async();
}
__device__ __forceinline__ void issue_out(float (&y)[48], const uint32_t (&of)[24], uint64_t dWo) {
  wg_fence();
#pragma unroll
  for (int s = 0; s < 6; s++) {
    if (s == 0) wgmma_rs_n96_t1<0>(y, of[0], of[1], of[2], of[3], dWo);
    else wgmma_rs_n96_t1<1>(y, of[4 * s], of[4 * s + 1], of[4 * s + 2], of[4 * s + 3], dWo + s * 16);
  }
  wg_commit();
}
__device__ __forceinline__ void ln_head(float (&y)[48], uint32_t (&yb)[24], float (&var)[4], uint64_t dOnes) {
  uint32_t sy[8];
  wg_wait<0>(); fence_regs(y);
  pack_sumsq(y, yb, sy, 0u);
  wg_fence();
  wgmma_rs_n8_t0<0>(var, sy[0], sy[1], sy[2], sy[3], dOnes);
  wgmma_rs_n8_t0<1>(var, sy[4], sy[5], sy[6], sy[7], dOnes);
  wg_commit();
}
__device__ __forceinline__ char* out_ptr(__nv_bfloat16* out, int win, int warp, uint32_t t16) {
  int py = ((win >> 8) & 255) * 8 + 4 + (warp & 1) * 4;  if (py >= IMG) py -= IMG;
  int px = (win & 255) * 8 + 4 + (warp >> 1) * 4;        if (px >= IMG) px -= IMG;
  return reinterpret_cast<char*>(out) + ((uint32_t)(py * IMG + px) * PIXB - warp * 512 + t16 + ((t16 & 0xC0) << 1) + (t16 & 0x100) * 287);
}
__device__ __forceinline__ uint32_t ln_tail(const uint32_t (&yb)[24], float (&var)[4], char* optr) {
  fence_regs(var);
  uint32_t last;
  const uint32_t nn = pack_bf16(rsq(fmaf(var[0], 1.f / 96.f, 1e-5f)), rsq(fmaf(var[2], 1.f / 96.f, 1e-5f)));
#pragma unroll
  for (int j = 0; j < 3; j++) {
    stg128(optr + j * 64, hmul2_b<0>(yb[8 * j], nn), hmul2_b<0>(yb[8 * j + 2], nn), hmul2_b<0>(yb[8 * j + 4], nn), hmul2_b<0>(yb[8 * j + 6], nn));
    last = hmul2_b<1>(yb[8 * j + 7], nn);
    stg128(optr + 2 * ROWB + j * 64, hmul2_b<1>(yb[8 * j + 1], nn), hmul2_b<1>(yb[8 * j + 3], nn), hmul2_b<1>(yb[8 * j + 5], nn), last);
  }
  return last;
}

__device__ __forceinline__ void load_mask_frag(uint32_t (&mk)[16], const char* tile, uint32_t t16) {
  asm volatile("" : "+r"(t16));
  const char* mrow = tile + (orig_tok(((t16 >> 9) << 4) + ((t16 >> 6) & 7)) * 128 + (t16 & 32) / 2);
  const bool odd = t16 & 16;
#pragma unroll
  for (int i = 0; i < 8; i++) {
    const uint4 v = ldg128_stream(mrow + (i & 1) * 2048 + (i >> 1) * 32);
    mk[i] = odd ? v.y : v.x; mk[8 + i] = odd ? v.w : v.z;
  }
}
__device__ __forceinline__ bool mask_unsafe(const uint32_t (&mk)[16]) {
  uint32_t x0 = mk[0], x1 = mk[1];
#pragma unroll
  for (int i = 2; i < 16; i += 2) { x0 = hmax2_nan(x0, mk[i]); x1 = hmax2_nan(x1, mk[i + 1]); }
  const bool nan_in = !(bf_lo(x0) == bf_lo(x0) && bf_hi(x0) == bf_hi(x0) && bf_lo(x1) == bf_lo(x1) && bf_hi(x1) == bf_hi(x1));
  const float r0 = quad_max(fmaxf(bf_lo(x0), bf_hi(x0))), r1 = quad_max(fmaxf(bf_lo(x1), bf_hi(x1)));
  return nan_in || !(fabsf(r0) <= 8.f && fabsf(r1) <= 8.f);
}

__device__ __forceinline__ void general_windows(const CUtensorMap* tm_x, const CUtensorMap* tm_xq, const char* mb, __nv_bfloat16* out, uint32_t xph) {
  int tid;
  asm volatile("mov.u32 %0, %%tid.x;" : "=r"(tid));
  const int lane = tid & 31;
  const int warp = __shfl_sync(0xffffffffu, (tid >> 5) & 3, 0), wg = __shfl_sync(0xffffffffu, tid >> 7, 0);
  const uint32_t t16 = (tid & 127) * 16, wgb = sb + SM_WG + wg * WG_SZ, bar_x = mbar + MB_X + 8 * wg;
  const uint32_t k_dst = wgb + WG_K + (lane >> 4) * 7168 + warp * 256 + (lane & 15) * 16;
  if (lds_uniform(sb + SM_GEN + wg * NENT * 4) < 0) return;
  mbar_wait(mbar + MB_WV, 0);
  mbar_wait(mbar + MB_RDY, 0);
  mbar_wait(mbar + MB_WOC, 0);
  const uint32_t slow_heads = lds_uniform(sb + SM_SLOW);
  const uint64_t dX = mk_desc(WG_X, 16, 512, 2) + (wgb >> 4), dK = mk_desc(WG_K, 1024, 128, 0) + (wgb >> 4), dV = mk_desc(WG_V, 128, 1024, 0) + (wgb >> 4);
#pragma unroll 1
  for (uint32_t gl = sb + SM_GEN + wg * NENT * 4;; gl += 4) {
    const int win = lds_uniform(gl);
    if (win < 0) break;
    uint32_t qa[24], of[24], mk[16];
    uint32_t tm;
    {
      load_mask_frag(mk, mb + mask_off(win), t16);
      float qk[96];
      mbar_wait(bar_x, xph); xph ^= 1;
      wg_fence();
      issue_qk(qk, dX, mk_desc(sb + SM_W, 12288, 1024, 1)); wg_commit();
      uint32_t any = 0;
#pragma unroll
      for (int i = 0; i < 16; i += 2) any |= mk[i] | mk[i + 1];
      tm = bar_wg_or(BAR_KV + wg, (any & 0x7FFF7FFFu) != 0) ? 0x1Fu : slow_heads;
      qkv_epilogue(qk, qa, dX, mk_desc(sb + SM_WV, 6144, 512, 2), k_dst);
    }
    bar_sync_n(BAR_AUX + wg, 128);
    if (warp == 0 && elect_one()) {
      const int nxt = lds32(gl + 4);
      if (nxt >= 0) { load_x(tm_x, tm_xq, nxt, wg); prefetch_l2(mb + mask_off(nxt), 8192); }
    }
    __syncwarp();
    auto head = [&](float (&sc)[32], uint32_t (&p)[16], bool tmax) {
      if (tmax) {
        if (tm & 16) {
#pragma unroll
          for (int i = 0; i < 16; i++) {
            sc[2 * i] = fmaf(bf_lo(mk[i]), LOG2E, sc[2 * i]); sc[2 * i + 1] = fmaf(bf_hi(mk[i]), LOG2E, sc[2 * i + 1]);
          }
        }
        softmax_true_max(sc, p);
      } else {
        softmax_fast(sc, p);
      }
    };
#pragma unroll
    for (int i = 0; i < 24; i++) of[i] = 0;
#pragma unroll 1
    for (int hp = 0; hp < 2; hp++) {
      float sA[32], sB[32], oA[16], oB[16]; uint32_t p[16];
      const uint32_t po = hp * 7 * 64;
      wg_fence();
      issue_s<0>(sA, qa, dK + po);
      issue_s<1>(sB, qa, dK + po); wg_commit();
      load_eb(p, sb + SM_EB + t16 + hp * 16384);
      wg_wait<0>(); fence_regs(sA); fence_regs(sB);
#pragma unroll
      for (int i = 0; i < 12; i++) { qa[i] = qa[i + 12]; of[i] = of[i + 12]; }
      head(sA, p, (tm >> (2 * hp)) & 1);
      wg_fence(); issue_pv<0>(oA, p, dV + po); wg_commit();
      uint32_t p2[16];
      load_eb(p2, sb + SM_EB + t16 + hp * 16384 + 8192);
      head(sB, p2, (tm >> (2 * hp + 1)) & 1);
      wg_fence(); issue_pv<1>(oB, p2, dV + po); wg_commit();
      wg_wait<1>(); fence_regs(oA);
      norm_o<0>(oA, of + 12);
      wg_wait<0>(); fence_regs(oB);
      norm_o<1>(oB, of + 18);
    }
    float y[48], var[4]; uint32_t yb[24];
    issue_out(y, of, mk_desc(sb + SM_WO, 128, 1536, 0));
    ln_head(y, yb, var, dV + 3 * 64);
    wg_wait<0>();
    ln_tail(yb, var, out_ptr(out, win, warp, t16));
  }
}

__global__ void __launch_bounds__(384, 1)
swin_kernel(const __nv_bfloat16* __restrict__ logit_scale, const __nv_bfloat16* __restrict__ w1, const __nv_bfloat16* __restrict__ w2,
            const __nv_bfloat16* __restrict__ coords, const int* __restrict__ rel_idx, const __nv_bfloat16* __restrict__ wo,
            const __nv_bfloat16* __restrict__ mask, __nv_bfloat16* __restrict__ out,
            const __grid_constant__ CUtensorMap tm_wqk, const __grid_constant__ CUtensorMap tm_x,
            const __grid_constant__ CUtensorMap tm_wv, const __grid_constant__ CUtensorMap tm_xq) {
  extern __shared__ __align__(1024) uint8_t smem[];
  const int tid = threadIdx.x, lane = tid & 31;
  const int warp = __shfl_sync(0xffffffffu, (tid >> 5) & 3, 0), wg = __shfl_sync(0xffffffffu, tid >> 7, 0);
  const int G = gridDim.x;
  const char* mb = reinterpret_cast<const char*>(mask);
  TL(0); TG(14);

  const bool g132 = G == 132;
  uint32_t cw = 0;
  uint4 rid[4];
  if (tid >= 128) {
    const int i = tid - 128;
    if (i < 225) cw = __ldg(reinterpret_cast<const uint32_t*>(coords) + i);
  } else if (tid >= 64 && tid < 96) {
    if (lane < 12) *reinterpret_cast<uint4*>(smem + SM_PAR + 16 * lane) =
        ldg128_stream(lane < 4 ? reinterpret_cast<const uint4*>(w1) + lane : reinterpret_cast<const uint4*>(w2) + (lane - 4));
    __syncwarp();
    bar_arrive_n(BAR_PAR, 288);
  }
  const uint2 lsw = __ldg(reinterpret_cast<const uint2*>(logit_scale));
  if (tid >= 128) {
#pragma unroll
    for (int c = 0; c < 4; c++) rid[c] = ldg128_stream(reinterpret_cast<const int4*>(rel_idx) + c * 256 + (tid - 128));
  } else if (tid < 32) {
    if (elect_one()) {
#pragma unroll
      for (int i = 0; i < 13; i++) mbar_init(mbar + 8 * i, ((i >= 4 && i < 7) || i >= 9) ? 4 : 1);
      mbar_init(mbar + MB_RDY, 8); mbar_init(mbar + MB_WOC, 4);
      fence_async();
      auto first = [&](int g) { const int i = blockIdx.x + g * G, iy = (i * 2789) >> 17; return iy << 8 | (i - iy * 47); };
      mbar_expect(mbar + MB_WQK, 3 * 12288);
      tma3(sb + SM_W, &tm_wqk, mbar + MB_WQK, 0, 0, 0);
      load_x_interior(&tm_x, first(0), 0);
      mbar_expect(mbar + MB_WV, 3 * 6144);
      tma3(sb + SM_WV, &tm_wv, mbar + MB_WV, 0, 0, 0);
      mbar_expect(mbar + MB_WO, 18432);
      bulk_g2s(sb + SM_WOR, wo, 18432, mbar + MB_WO);
      load_x_interior(&tm_x, first(1), 1);
      prefetch_l2(mb + mask_off(first(0)), 8192);
    }
    __syncwarp();
  }
  if ((uint32_t)__cvta_generic_to_shared(smem) != sb) __trap();
  auto const_tiles = [&]() {
    const int i = tid & 127;
    uint8_t* vt = smem + SM_WG + wg * WG_SZ + WG_V + (i < 64 ? 3 : 10) * 1024 + (i & 63) * 16;
    *reinterpret_cast<uint4*>(vt) = make_uint4(0x3F803F80u, 0x3F803F80u, 0x3F803F80u, 0x3F803F80u);
    *reinterpret_cast<uint4*>(vt - (WG_V - WG_K)) = make_uint4(0u, 0u, 0u, 0u);
  };
  if (wg != 2) const_tiles();
  float tau[4]; uint32_t slow_heads = 0;
  auto head_scales = [&]() {
    const float ls[4] = {bf_lo(lsw.x), bf_hi(lsw.x), bf_lo(lsw.y), bf_hi(lsw.y)};
#pragma unroll
    for (int h = 0; h < 4; h++) {
      float c;
      asm("max.NaN.f32 %0, %1, 0fC2C80000;" : "=f"(c) : "f"(ls[h]));
      asm("min.NaN.f32 %0, %0, 0f40930000;" : "+f"(c));
      tau[h] = rbf(ex2(c * LOG2E)) * LOG2E;
      if (!(tau[h] <= TAU_FAST_MAX)) slow_heads |= 1u << h;
    }
    slow_heads = __shfl_sync(0xffffffffu, slow_heads, 0);
  };
  if (wg == 0) head_scales();
  if (wg == 0 && warp == 1) {
    const int eg = lane / NENT, ei = lane - eg * NENT, sl = blockIdx.x + eg * G + ei * 3 * G;
    const int w = (sl < NWIN && eg < 3) ? slot_window(sl, g132) : -1;
    const bool queues = w >= 0 && (w >> 8) != NWX - 1 && (w & 255) != NWX - 1;
    const uint32_t qmask = __ballot_sync(0xffffffffu, queues);
    const int key = (eg + 3 * ei + BORDER_EXTRA * __popc((~qmask >> (eg * NENT)) & ((1u << ei) - 1))) * 3 + eg;
    const uint32_t k0 = __reduce_or_sync(0xffffffffu, queues && key < 32 ? 1u << key : 0u), k1 = __reduce_or_sync(0xffffffffu, queues && (key >> 5) == 1 ? 1u << (key & 31) : 0u);
    const uint32_t k2 = __reduce_or_sync(0xffffffffu, queues && (key >> 5) == 2 ? 1u << (key & 31) : 0u), k3 = __reduce_or_sync(0xffffffffu, queues && (key >> 5) == 3 ? 1u << (key & 31) : 0u);
    const uint32_t lo = (1u << (key & 31)) - 1;
    const int kw = key >> 5;
    const int ticket = __popc(kw > 0 ? k0 : k0 & lo) + (kw >= 1 ? __popc(kw > 1 ? k1 : k1 & lo) : 0) + (kw >= 2 ? __popc(kw > 2 ? k2 : k2 & lo) : 0) + (kw >= 3 ? __popc(k3 & lo) : 0);
    const int ent = w | (queues ? ticket : NO_TICKET) << 16;
    if (eg < 3) {
      *reinterpret_cast<int*>(smem + SM_WIN + lane * 4) = slow_heads ? -1 : ent;
      *reinterpret_cast<int*>(smem + SM_GEN + lane * 4) = slow_heads ? ent : -1;
    }
  }
  if (wg == 0 && warp == 3 && lane < 16) {
    const uint32_t v = (((lane >> 3) ^ lane) & 1) ? 0u : 0x3F803F80u;
    *reinterpret_cast<uint4*>(smem + SM_SEL + lane * 16) = make_uint4(v, v, v, v);
  }
  TL(3);
  if (wg == 0) {
    if (tid == 0) {
      *reinterpret_cast<float4*>(smem + SM_MISC) = make_float4(tau[0], tau[1], tau[2], tau[3]);
      *reinterpret_cast<uint32_t*>(smem + SM_SLOW) = slow_heads;
    }
    fence_async();
    bar_arrive_n(BAR_SETUP, 384);
    bar_sync_n(BAR_AUX, 128);
  } else {
    const int i = tid - 128;
    bar_sync_n(BAR_PAR, 288);
    TL(4);
    head_scales();
    if (i < 225) {
      const float c0 = bf_lo(cw), c1 = bf_hi(cw);
      float z[4] = {0.f, 0.f, 0.f, 0.f};
#pragma unroll
      for (int jj = 0; jj < 2; jj++) {
        const uint4 ua4 = lds128(sb + SM_PAR + 16 * jj), ub4 = lds128(sb + SM_PAR + 32 + 16 * jj);
        const uint32_t ua[4] = {ua4.x, ua4.y, ua4.z, ua4.w}, ub[4] = {ub4.x, ub4.y, ub4.z, ub4.w};
#pragma unroll
        for (int j = 0; j < 4; j++) {
          const uint4 wb = lds128(sb + SM_PAR + 64 + 64 * jj + 16 * j);
          const uint32_t hp = pack_bf16(fmaf(c1, bf_lo(ub[j]), c0 * bf_lo(ua[j])), fmaf(c1, bf_hi(ub[j]), c0 * bf_hi(ua[j])));
          float h0 = bf_lo(hp), h1 = bf_hi(hp);
          h0 = h0 > 0.f ? h0 : h0 * 0.f; h1 = h1 > 0.f ? h1 : h1 * 0.f;
          z[0] = fmaf(h0, bf_lo(wb.x), z[0]); z[1] = fmaf(h0, bf_hi(wb.x), z[1]); z[2] = fmaf(h0, bf_lo(wb.y), z[2]); z[3] = fmaf(h0, bf_hi(wb.y), z[3]);
          z[0] = fmaf(h1, bf_lo(wb.z), z[0]); z[1] = fmaf(h1, bf_hi(wb.z), z[1]); z[2] = fmaf(h1, bf_lo(wb.w), z[2]); z[3] = fmaf(h1, bf_hi(wb.w), z[3]);
        }
      }
      float e[4];
#pragma unroll
      for (int q = 0; q < 4; q++) {
        const float sh = ((slow_heads >> q) & 1) ? 0.f : fminf(0.f, 25.f - 1.02f * tau[q]);
        e[q] = ex2(fmaf(16.f * LOG2E, rbf(rcp(1.f + ex2(-LOG2E * rbf(z[q])))), sh));
      }
      *reinterpret_cast<uint2*>(smem + SM_TAB + 8 * i) = make_uint2(pack_bf16(e[0], e[1]), pack_bf16(e[2], e[3]));
    }
    TL(5);
    bar_sync_n(BAR_SETUP, 384);
#pragma unroll
    for (int c = 0; c < 4; c++) asm volatile("" : "+r"(rid[c].x), "+r"(rid[c].y), "+r"(rid[c].z), "+r"(rid[c].w));
    {
      const int y = (i & 15) >> 1, xh = i & 1, j = 2 * xh + (y >> 2);
      const int X = (i >> 4) & 7, Yl = (i >> 7) & 1;
      uint8_t* dst = smem + SM_EB + j * 2048 + ((X >> 2) * 64 + (Yl * 4 + (X & 3)) * 4 + 2 * (y & 1)) * 16 + ((y >> 1) & 1) * 8;
      uint2 e[16];
#pragma unroll
      for (int c = 0; c < 4; c++) {
        const uint32_t id[4] = {xh ? rid[c].z : rid[c].x, xh ? rid[c].w : rid[c].y, xh ? rid[c].x : rid[c].z, xh ? rid[c].y : rid[c].w};
#pragma unroll
        for (int q = 0; q < 4; q++) e[4 * c + q] = *reinterpret_cast<const uint2*>(smem + SM_TAB + 8 * id[q]);
      }
#pragma unroll
      for (int c = 0; c < 4; c++) {
        const uint2 a0 = e[4 * c], a1 = e[4 * c + 1], b0 = e[4 * c + 2], b1 = e[4 * c + 3];
        uint8_t* d0 = dst + (c >> 1) * 512 + (((c & 1) ^ (j & 1)) * 4) + xh * 16;
        uint8_t* d1 = dst + (c >> 1) * 512 + (((c & 1) ^ (j & 1)) * 4) + (xh ^ 1) * 16;
        *reinterpret_cast<uint32_t*>(d0)         = __byte_perm(a0.x, a1.x, 0x5410); *reinterpret_cast<uint32_t*>(d1)         = __byte_perm(b0.x, b1.x, 0x5410);
        *reinterpret_cast<uint32_t*>(d0 + 8192)  = __byte_perm(a0.x, a1.x, 0x7632); *reinterpret_cast<uint32_t*>(d1 + 8192)  = __byte_perm(b0.x, b1.x, 0x7632);
        *reinterpret_cast<uint32_t*>(d0 + 16384) = __byte_perm(a0.y, a1.y, 0x5410); *reinterpret_cast<uint32_t*>(d1 + 16384) = __byte_perm(b0.y, b1.y, 0x5410);
        *reinterpret_cast<uint32_t*>(d0 + 24576) = __byte_perm(a0.y, a1.y, 0x7632); *reinterpret_cast<uint32_t*>(d1 + 24576) = __byte_perm(b0.y, b1.y, 0x7632);
      }
    }
    TL(6);
    if (tid == 256) {
      load_x_interior(&tm_x, slot_window(blockIdx.x + 2 * G, g132), 2);
      prefetch_l2(mb + mask_off(slot_window(blockIdx.x + G, g132)), 8192);
      prefetch_l2(mb + mask_off(slot_window(blockIdx.x + 2 * G, g132)), 8192);
    }
    __syncwarp();
    fence_async();
    if (elect_one()) mbar_arrive(mbar + MB_RDY);
    __syncwarp();
    bar_sync_n(BAR_TAB, 256);
    if (wg == 2) {
      mbar_wait(mbar + MB_WO, 0);
      uint4 v[9];
#pragma unroll
      for (int c = 0; c < 9; c++) v[c] = lds128(sb + SM_WOR + ((c / 3) * 32 + ((tid & 127) >> 2)) * 192 + (c % 3) * 64 + (lane & 3) * 16);
      bar_sync_n(BAR_AUX + 2, 128);
      const_tiles();
#pragma unroll
      for (int r = 0; r < 3; r++) {
        float sum = 0.f;
#pragma unroll
        for (int c = 3 * r; c < 3 * r + 3; c++)
          sum += (bf_lo(v[c].x) + bf_hi(v[c].x)) + (bf_lo(v[c].y) + bf_hi(v[c].y)) + (bf_lo(v[c].z) + bf_hi(v[c].z)) + (bf_lo(v[c].w) + bf_hi(v[c].w));
        sum += __shfl_xor_sync(0xffffffffu, sum, 1);
        sum += __shfl_xor_sync(0xffffffffu, sum, 2);
        const float mu = sum * (1.f / 96.f);
        auto cen = [&](uint32_t u) { return pack_bf16(bf_lo(u) - mu, bf_hi(u) - mu); };
        uint8_t* dst = smem + SM_WO + (r * 4 + warp) * 128 + lane * 4;
#pragma unroll
        for (int j = 0; j < 3; j++) {
          *reinterpret_cast<uint32_t*>(dst + (4 * j + 0) * 1536) = cen(v[3 * r + j].x);
          *reinterpret_cast<uint32_t*>(dst + (4 * j + 1) * 1536) = cen(v[3 * r + j].y);
          *reinterpret_cast<uint32_t*>(dst + (4 * j + 2) * 1536) = cen(v[3 * r + j].z);
          *reinterpret_cast<uint32_t*>(dst + (4 * j + 3) * 1536) = cen(v[3 * r + j].w);
        }
      }
      fence_async();
      __syncwarp();
      if (elect_one()) { mbar_arrive(mbar + MB_TURN); mbar_arrive(mbar + MB_WOC); }
      __syncwarp();
    }
  }
  TL(1);
  mbar_wait(mbar + MB_WQK, 0);
  uint32_t xpar = 0;

  uint32_t wl = sb + SM_WIN + wg * NENT * 4;
  int win = lds_uniform(wl), nxt = lds_uniform(wl + 4);
  if (win >= 0) {
    const uint32_t wgb = sb + SM_WG + wg * WG_SZ, bar_x = mbar + MB_X + 8 * wg;
    const uint32_t t16 = (tid & 127) * 16;
    const uint32_t k_dst = wgb + WG_K + (tid & 16) * 448 + warp * 256 + (tid & 15) * 16;
    const uint32_t eb_base = sb + SM_EB + t16;
    float qk[96];
    mbar_wait(bar_x, 0);
    TL(2);
    wg_fence();
    issue_qk(qk, mk_desc(WG_X, 16, 512, 2) + (wgb >> 4), mk_desc(sb + SM_W, 12288, 1024, 1)); wg_commit();
    bool first = true;
    mbar_wait(mbar + MB_WV, 0);
    TL(8);
    while (true) {
      const int nxt2 = lds_uniform(wl + 8);
      const int tk = win >> 16;
      const bool more = nxt >= 0;
      const uint32_t z0 = wl >> 20, zw = z0 + (wgb >> 4);
      const uint64_t dX = opaque(mk_desc(WG_X, 16, 512, 2) + zw);
      TL(0);
      uint32_t qa[24];
      qkv_epilogue(qk, qa, dX, opaque(mk_desc(sb + SM_WV, 6144, 512, 2) + z0), k_dst);
      TL(5);
      if (__builtin_expect(first, 0)) {
        mbar_wait(mbar + MB_RDY, 0);
        first = false;
      }
      uint32_t pA[16], pB[16];
      load_eb(pA, eb_base);
      load_eb(pB, eb_base + 8192);
      bar_sync_n(BAR_KV + wg, 128);
      const bool masked = tk == NO_TICKET;
      TL(6);
      const uint64_t dK = opaque(mk_desc(WG_K, 1024, 128, 0) + zw), dV = opaque(mk_desc(WG_V, 128, 1024, 0) + zw);
      auto prefetch_next = [&]() {
        if (warp == 0 && more) {
          if (elect_one()) {
            load_x(&tm_x, &tm_xq, nxt, wg);
            prefetch_l2(mb + mask_off(nxt), 8192);
          }
          __syncwarp();
        }
      };
      auto redo = [&](int w) {
        if (elect_one()) {
          uint32_t gl = sb + SM_GEN + wg * NENT * 4, old;
          do {
            asm volatile("atom.shared.cas.b32 %0, [%1], %2, %3;" : "=r"(old) : "r"(gl), "r"(-1), "r"(w) : "memory");
            gl += 4;
          } while (old != 0xFFFFFFFFu && old != (uint32_t)w);
        }
        __syncwarp();
      };
      auto wait_turn = [&]() { mbar_wait(mbar + MB_TURN + (tk & 3) * 8, (tk >> 2) & 1); };
      auto pass_turn = [&](uint32_t after = 0) {
        asm volatile("{\n.reg .pred p, q;\nelect.sync _|p, 0xffffffff;\nsetp.ne.and.s32 q, %1, 255, p;\nsetp.ne.and.s32 q, %2, -1, q;\n"
                     "@q mbarrier.arrive.shared::cta.b64 _, [%0];\n}\n"
                     :: "r"(mbar + MB_TURN + ((tk + 1) & 3) * 8), "r"(tk), "r"(after) : "memory");
      };
      auto next_qk = [&]() { issue_qk(qk, dX, opaque(mk_desc(sb + SM_W, 12288, 1024, 1) + z0)); wg_commit(); };
      auto tiles_ready = [&]() {
        if (elect_one()) mbar_arrive(bar_x + (MB_KV - MB_X));
        __syncwarp();
        const uint32_t par = (wl >> 2) & 1;
        mbar_wait(bar_x, par ^ 1);
        mbar_wait(bar_x + (MB_KV - MB_X), par);
      };
      uint32_t of[24];
      uint4 mw[4];
      {
        float sA[32], sB[32], oA[16], oB[16], oC[16], oD[16];
        uint32_t pC[16], pD[16];
        wg_fence();
        issue_s<0>(sA, qa, dK);
        issue_s<1>(sB, qa, dK); wg_commit();
        uint32_t eb_hi = sb + SM_EB + 16384;
        if (__builtin_expect(!masked, 1)) {
          prefetch_next();
          wait_turn();
        } else {
          uint32_t mk[16];
          load_mask_frag(mk, mb + mask_off(win), t16);
          if (t16 == 0 && more)
            asm volatile("cp.async.bulk.prefetch.tensor.5d.L2.global.tile [%0, {%1, %1, %2, %3, %1}];"
                         :: "l"(&tm_x), "r"(0), "r"(((nxt >> 8) & 255) * 8 + 4), "r"((nxt & 255) * 2 + 1) : "memory");
          __syncwarp();
          wg_wait<0>();
          if (__any_sync(0xffffffffu, mask_unsafe(mk))) redo(win);
          bar_sync_n(BAR_AUX + wg, 128);
#pragma unroll
          for (int i = 0; i < 16; i++) {
            mk[i] = pack_bf16(ex2(bf_lo(mk[i]) * LOG2E), ex2(bf_hi(mk[i]) * LOG2E));
            pA[i] = hmul2(pA[i], mk[i]); pB[i] = hmul2(pB[i], mk[i]);
          }
#pragma unroll
          for (int h = 0; h < 2; h++) {
            uint4 e[4];
#pragma unroll
            for (int j = 0; j < 4; j++) e[j] = lds128(eb_base + 16384 + h * 8192 + j * 2048);
#pragma unroll
            for (int j = 0; j < 4; j++) {
              const int m = 4 * j, x = j & 1;
              asm volatile("st.shared.v4.u32 [%0], {%1,%2,%3,%4};" :: "r"(wgb + WG_X + t16 + h * 8192 + j * 2048), "r"(hmul2(e[j].x, mk[m + x])),
                           "r"(hmul2(e[j].y, mk[m + (1 ^ x)])), "r"(hmul2(e[j].z, mk[m + (2 ^ x)])), "r"(hmul2(e[j].w, mk[m + (3 ^ x)])) : "memory");
            }
          }
          eb_hi = wgb + WG_X;
        }
        wg_wait<0>(); fence_regs(sA); fence_regs(sB);
        TL(7);
        softmax_fast(sA, pA);
        wg_fence();
        issue_s<2>(sA, qa, dK); wg_commit();
        issue_pv<0>(oA, pA, dV); wg_commit();
        TL(8);
        softmax_fast(sB, pB);
        load_eb(pC, eb_hi + t16);
        wg_wait<1>(); fence_regs(sA);
        wg_fence();
        issue_s<3>(sB, qa, dK); wg_commit();
        issue_pv<1>(oB, pB, dV); wg_commit();
        TL(9);
        softmax_fast(sA, pC);
        load_eb(pD, eb_hi + t16 + 8192);
        wg_wait<1>(); fence_regs(sB); fence_regs(oA);
        wg_fence();
        issue_pv<2>(oC, pC, dV); wg_commit();
        TL(10);
        norm_o<0>(oA, of);
        softmax_fast(sB, pD);
        pass_turn(pD[TPOS]);
        wg_fence();
        issue_pv<3>(oD, pD, dV); wg_commit();
        {
          const char* src = mb + (mask_off(win) + (warp & 1) * 4096 + (warp >> 1) * 512 + (t16 & 511));
#pragma unroll
          for (int i = 0; i < 4; i++) mw[i] = ldg128_stream(src + i * 1024);
        }
        wg_wait<1>(); fence_regs(oB); fence_regs(oC);
        norm_o<1>(oB, of + 6);
        norm_o<0>(oC, of + 12);
        wg_wait<0>(); fence_regs(oD);
        norm_o<1>(oD, of + 18);
      }
      TL(11);
      float y[48], var[4]; uint32_t yb[24];
      issue_out(y, of, opaque(mk_desc(sb + SM_WO, 128, 1536, 0) + z0));
      if (__builtin_expect(masked, 0)) {
        if (t16 >= 1024) asm volatile("st.shared.v4.u32 [%0], {%1,%1,%1,%1};" :: "r"(wgb + WG_K + 2048 + t16), "r"(0) : "memory");
        fence_async();
        bar_sync_n(BAR_AUX + wg, 128);
        prefetch_next();
      }
      char* const optr = out_ptr(out, win, warp, t16);
      auto verify = [&](uint32_t seed) {
        uint32_t r = seed & 0x80008000u;
#pragma unroll
        for (int i = 0; i < 4; i++) {
          asm("lop3.b32 %0, %0, %1, %2, 0xFE;" : "+r"(r) : "r"(mw[i].x), "r"(mw[i].y));
          asm("lop3.b32 %0, %0, %1, %2, 0xFE;" : "+r"(r) : "r"(mw[i].z), "r"(mw[i].w));
        }
        if (__builtin_expect(__any_sync(0xffffffffu, (r & 0x7FFF7FFFu) != 0u) && !masked, 0)) redo(win);
      };
      if (!more) { ln_head(y, yb, var, dV + 3 * 64); wg_wait<0>(); verify(ln_tail(yb, var, optr)); TL(14); break; }
      tiles_ready();
      ln_head(y, yb, var, dV + 3 * 64);
      TL(12);
      next_qk();
      wg_wait<1>();
      TL(13);
      verify(ln_tail(yb, var, optr));
      TL(14);
      wl += 4;
      win = nxt; nxt = nxt2;
    }
    xpar = ((wl >> 2) & 1) ^ 1;
    bar_sync_n(BAR_AUX + wg, 128);
    if (warp == 0 && elect_one()) {
      const int w = lds32(sb + SM_GEN + wg * NENT * 4);
      if (w >= 0) load_x(&tm_x, &tm_xq, w, wg);
    }
    __syncwarp();
  }
  general_windows(&tm_x, &tm_xq, mb, out, xpar);
  TG(15);
}

typedef CUresult (*EncodeFn)(CUtensorMap*, CUtensorMapDataType, cuuint32_t, void*, const cuuint64_t*, const cuuint64_t*,
                             const cuuint32_t*, const cuuint32_t*, CUtensorMapInterleave, CUtensorMapSwizzle,
                             CUtensorMapL2promotion, CUtensorMapFloatOOBfill);

}

extern "C" void kernel_launch(void* const* d_in, const int* in_sizes, int n_in, void* d_out, int out_size) {
  static int sms = 0;
  static EncodeFn encode = nullptr;
  if (sms == 0) {
    int dev = 0;
    cudaGetDevice(&dev);
    cudaDeviceGetAttribute(&sms, cudaDevAttrMultiProcessorCount, dev);
    if (sms < 96) sms = 96;
    cudaFuncSetAttribute(swin_kernel, cudaFuncAttributeMaxDynamicSharedMemorySize, SM_TOTAL);
    cudaDriverEntryPointQueryResult qr;
    void* fn = nullptr;
    cudaGetDriverEntryPoint("cuTensorMapEncodeTiled", &fn, cudaEnableDefault, &qr);
    encode = (EncodeFn)fn;
  }
  CUtensorMap tm_x, tm_xq, tm_wqk, tm_wv;
  {
    cuuint64_t dims[5] = {32, 4, IMG, IMG / 4, 3};
    cuuint64_t strides[4] = {PIXB, ROWB, 4 * PIXB, 64};
    cuuint32_t es[5] = {1, 1, 1, 1, 1};
    cuuint32_t box[5] = {32, 4, 8, 2, 3}, boxq[5] = {32, 4, 4, 1, 1};
    encode(&tm_x, CU_TENSOR_MAP_DATA_TYPE_BFLOAT16, 5, d_in[0], dims, strides, box, es, CU_TENSOR_MAP_INTERLEAVE_NONE,
           CU_TENSOR_MAP_SWIZZLE_64B, CU_TENSOR_MAP_L2_PROMOTION_L2_128B, CU_TENSOR_MAP_FLOAT_OOB_FILL_NONE);
    encode(&tm_xq, CU_TENSOR_MAP_DATA_TYPE_BFLOAT16, 5, d_in[0], dims, strides, boxq, es, CU_TENSOR_MAP_INTERLEAVE_NONE,
           CU_TENSOR_MAP_SWIZZLE_64B, CU_TENSOR_MAP_L2_PROMOTION_L2_128B, CU_TENSOR_MAP_FLOAT_OOB_FILL_NONE);
    cuuint64_t qd[3] = {64, 96, 3}, qs[2] = {576, 128}, vd[3] = {32, 96, 3}, vs[2] = {576, 64};
    cuuint32_t qb[3] = {64, 96, 3}, vb[3] = {32, 96, 3};
    encode(&tm_wqk, CU_TENSOR_MAP_DATA_TYPE_BFLOAT16, 3, d_in[1], qd, qs, qb, es, CU_TENSOR_MAP_INTERLEAVE_NONE,
           CU_TENSOR_MAP_SWIZZLE_128B, CU_TENSOR_MAP_L2_PROMOTION_L2_256B, CU_TENSOR_MAP_FLOAT_OOB_FILL_NONE);
    encode(&tm_wv, CU_TENSOR_MAP_DATA_TYPE_BFLOAT16, 3, (char*)d_in[1] + 384, vd, vs, vb, es, CU_TENSOR_MAP_INTERLEAVE_NONE,
           CU_TENSOR_MAP_SWIZZLE_64B, CU_TENSOR_MAP_L2_PROMOTION_L2_256B, CU_TENSOR_MAP_FLOAT_OOB_FILL_NONE);
  }
  swin_kernel<<<sms, 384, SM_TOTAL>>>(
      (const __nv_bfloat16*)d_in[3], (const __nv_bfloat16*)d_in[4], (const __nv_bfloat16*)d_in[5], (const __nv_bfloat16*)d_in[6],
      (const int*)d_in[7], (const __nv_bfloat16*)d_in[2], (const __nv_bfloat16*)d_in[8], (__nv_bfloat16*)d_out,
      tm_wqk, tm_x, tm_wv, tm_xq);
}
```

```cpp
#include <cuda_runtime.h>
#include <cuda.h>
#include <cuda_bf16.h>
#include <stdint.h>
#include <type_traits>

#define WOGATE 0
#define TIE 2
#define TOKEN 4
namespace {

constexpr int IMG   = 384;
constexpr int NWX   = 48;
constexpr int NWIN  = NWX * NWX;
constexpr int PIXB  = 192;
constexpr int ROWB  = IMG * PIXB;
constexpr float LOG2E = 1.4426950408889634f;
constexpr float TAU_FAST_MAX = 50.f;

constexpr int SM_W    = 0;
constexpr int SM_WV   = 3 * 12288;
constexpr int SM_WO   = SM_W + 9 * 6144;
constexpr int SM_EB   = SM_WO + 12 * 1536;
constexpr int SM_WG   = SM_EB + 32768;
constexpr int WG_X    = 0;
constexpr int WG_K    = 12288;
constexpr int WG_V    = WG_K + 14336;
constexpr int WG_SZ   = WG_V + 14336;
constexpr int SM_TAB  = SM_WG + WG_SZ + WG_V + 4096;
constexpr int SM_WOR  = SM_WG + 2 * WG_SZ + WG_K;
constexpr int SM_SEL  = SM_WG + 3 * WG_SZ;
constexpr int SM_MISC = SM_SEL + 256;
constexpr int SM_BAR  = SM_MISC + 16;
constexpr int SM_SLOW = SM_BAR + 104;
constexpr int SM_PAR  = SM_BAR + 160;
constexpr int NENT    = 10;
constexpr int SM_WIN  = SM_PAR + 192;
constexpr int SM_GEN  = SM_WIN + 3 * NENT * 4;
constexpr int SM_TOTAL = SM_GEN + 3 * NENT * 4;
static_assert((SM_WIN & 7) == 0 && (NENT & 1) == 0, "list parity");

template <int SD> __device__ __forceinline__ void wgmma_ss_n192_t1(float (&d)[96], uint64_t da, uint64_t db) {
  if constexpr (SD == 1) {
    asm volatile("{\n.reg .pred p;\nsetp.ne.b32 p, 1, 0;\n"
      "wgmma.mma_async.sync.aligned.m64n192k16.f32.bf16.bf16 {%0, %1, %2, %3, %4, %5, %6, %7, %8, %9, %10, %11, %12, %13, %14, %15, %16, %17, %18, %19, %20, %21, %22, %23, %24, %25, %26, %27, %28, %29, %30, %31, %32, %33, %34, %35, %36, %37, %38, %39, %40, %41, %42, %43, %44, %45, %46, %47, %48, %49, %50, %51, %52, %53, %54, %55, %56, %57, %58, %59, %60, %61, %62, %63, %64, %65, %66, %67, %68, %69, %70, %71, %72, %73, %74, %75, %76, %77, %78, %79, %80, %81, %82, %83, %84, %85, %86, %87, %88, %89, %90, %91, %92, %93, %94, %95}, %96, %97, p, 1, 1, 0, 1;\n}\n"
      : "+f"(d[0]), "+f"(d[1]), "+f"(d[2]), "+f"(d[3]), "+f"(d[4]), "+f"(d[5]), "+f"(d[6]), "+f"(d[7]), "+f"(d[8]), "+f"(d[9]), "+f"(d[10]), "+f"(d[11]), "+f"(d[12]), "+f"(d[13]), "+f"(d[14]), "+f"(d[15]), "+f"(d[16]), "+f"(d[17]), "+f"(d[18]), "+f"(d[19]), "+f"(d[20]), "+f"(d[21]), "+f"(d[22]), "+f"(d[23]), "+f"(d[24]), "+f"(d[25]), "+f"(d[26]), "+f"(d[27]), "+f"(d[28]), "+f"(d[29]), "+f"(d[30]), "+f"(d[31]), "+f"(d[32]), "+f"(d[33]), "+f"(d[34]), "+f"(d[35]), "+f"(d[36]), "+f"(d[37]), "+f"(d[38]), "+f"(d[39]), "+f"(d[40]), "+f"(d[41]), "+f"(d[42]), "+f"(d[43]), "+f"(d[44]), "+f"(d[45]), "+f"(d[46]), "+f"(d[47]), "+f"(d[48]), "+f"(d[49]), "+f"(d[50]), "+f"(d[51]), "+f"(d[52]), "+f"(d[53]), "+f"(d[54]), "+f"(d[55]), "+f"(d[56]), "+f"(d[57]), "+f"(d[58]), "+f"(d[59]), "+f"(d[60]), "+f"(d[61]), "+f"(d[62]), "+f"(d[63]), "+f"(d[64]), "+f"(d[65]), "+f"(d[66]), "+f"(d[67]), "+f"(d[68]), "+f"(d[69]), "+f"(d[70]), "+f"(d[71]), "+f"(d[72]), "+f"(d[73]), "+f"(d[74]), "+f"(d[75]), "+f"(d[76]), "+f"(d[77]), "+f"(d[78]), "+f"(d[79]), "+f"(d[80]), "+f"(d[81]), "+f"(d[82]), "+f"(d[83]), "+f"(d[84]), "+f"(d[85]), "+f"(d[86]), "+f"(d[87]), "+f"(d[88]), "+f"(d[89]), "+f"(d[90]), "+f"(d[91]), "+f"(d[92]), "+f"(d[93]), "+f"(d[94]), "+f"(d[95])
      : "l"(da), "l"(db));
  } else if constexpr (SD == 2) {
    asm volatile("{\n.reg .pred p;\nsetp.ne.b32 p, 0, 0;\n"
      "wgmma.mma_async.sync.aligned.m64n192k16.f32.bf16.bf16 {%0, %1, %2, %3, %4, %5, %6, %7, %8, %9, %10, %11, %12, %13, %14, %15, %16, %17, %18, %19, %20, %21, %22, %23, %24, %25, %26, %27, %28, %29, %30, %31, %32, %33, %34, %35, %36, %37, %38, %39, %40, %41, %42, %43, %44, %45, %46, %47, %48, %49, %50, %51, %52, %53, %54, %55, %56, %57, %58, %59, %60, %61, %62, %63, %64, %65, %66, %67, %68, %69, %70, %71, %72, %73, %74, %75, %76, %77, %78, %79, %80, %81, %82, %83, %84, %85, %86, %87, %88, %89, %90, %91, %92, %93, %94, %95}, %96, %97, p, 1, 1, 0, 1;\n}\n"
      : "+f"(d[0]), "+f"(d[1]), "+f"(d[2]), "+f"(d[3]), "+f"(d[4]), "+f"(d[5]), "+f"(d[6]), "+f"(d[7]), "+f"(d[8]), "+f"(d[9]), "+f"(d[10]), "+f"(d[11]), "+f"(d[12]), "+f"(d[13]), "+f"(d[14]), "+f"(d[15]), "+f"(d[16]), "+f"(d[17]), "+f"(d[18]), "+f"(d[19]), "+f"(d[20]), "+f"(d[21]), "+f"(d[22]), "+f"(d[23]), "+f"(d[24]), "+f"(d[25]), "+f"(d[26]), "+f"(d[27]), "+f"(d[28]), "+f"(d[29]), "+f"(d[30]), "+f"(d[31]), "+f"(d[32]), "+f"(d[33]), "+f"(d[34]), "+f"(d[35]), "+f"(d[36]), "+f"(d[37]), "+f"(d[38]), "+f"(d[39]), "+f"(d[40]), "+f"(d[41]), "+f"(d[42]), "+f"(d[43]), "+f"(d[44]), "+f"(d[45]), "+f"(d[46]), "+f"(d[47]), "+f"(d[48]), "+f"(d[49]), "+f"(d[50]), "+f"(d[51]), "+f"(d[52]), "+f"(d[53]), "+f"(d[54]), "+f"(d[55]), "+f"(d[56]), "+f"(d[57]), "+f"(d[58]), "+f"(d[59]), "+f"(d[60]), "+f"(d[61]), "+f"(d[62]), "+f"(d[63]), "+f"(d[64]), "+f"(d[65]), "+f"(d[66]), "+f"(d[67]), "+f"(d[68]), "+f"(d[69]), "+f"(d[70]), "+f"(d[71]), "+f"(d[72]), "+f"(d[73]), "+f"(d[74]), "+f"(d[75]), "+f"(d[76]), "+f"(d[77]), "+f"(d[78]), "+f"(d[79]), "+f"(d[80]), "+f"(d[81]), "+f"(d[82]), "+f"(d[83]), "+f"(d[84]), "+f"(d[85]), "+f"(d[86]), "+f"(d[87]), "+f"(d[88]), "+f"(d[89]), "+f"(d[90]), "+f"(d[91]), "+f"(d[92]), "+f"(d[93]), "+f"(d[94]), "+f"(d[95])
      : "l"(da), "l"(db));
  } else {
    asm volatile("{\n.reg .pred p;\nsetp.ne.b32 p, 0, 0;\n"
      "wgmma.mma_async.sync.aligned.m64n192k16.f32.bf16.bf16 {%0, %1, %2, %3, %4, %5, %6, %7, %8, %9, %10, %11, %12, %13, %14, %15, %16, %17, %18, %19, %20, %21, %22, %23, %24, %25, %26, %27, %28, %29, %30, %31, %32, %33, %34, %35, %36, %37, %38, %39, %40, %41, %42, %43, %44, %45, %46, %47, %48, %49, %50, %51, %52, %53, %54, %55, %56, %57, %58, %59, %60, %61, %62, %63, %64, %65, %66, %67, %68, %69, %70, %71, %72, %73, %74, %75, %76, %77, %78, %79, %80, %81, %82, %83, %84, %85, %86, %87, %88, %89, %90, %91, %92, %93, %94, %95}, %96, %97, p, 1, 1, 0, 1;\n}\n"
      : "=f"(d[0]), "=f"(d[1]), "=f"(d[2]), "=f"(d[3]), "=f"(d[4]), "=f"(d[5]), "=f"(d[6]), "=f"(d[7]), "=f"(d[8]), "=f"(d[9]), "=f"(d[10]), "=f"(d[11]), "=f"(d[12]), "=f"(d[13]), "=f"(d[14]), "=f"(d[15]), "=f"(d[16]), "=f"(d[17]), "=f"(d[18]), "=f"(d[19]), "=f"(d[20]), "=f"(d[21]), "=f"(d[22]), "=f"(d[23]), "=f"(d[24]), "=f"(d[25]), "=f"(d[26]), "=f"(d[27]), "=f"(d[28]), "=f"(d[29]), "=f"(d[30]), "=f"(d[31]), "=f"(d[32]), "=f"(d[33]), "=f"(d[34]), "=f"(d[35]), "=f"(d[36]), "=f"(d[37]), "=f"(d[38]), "=f"(d[39]), "=f"(d[40]), "=f"(d[41]), "=f"(d[42]), "=f"(d[43]), "=f"(d[44]), "=f"(d[45]), "=f"(d[46]), "=f"(d[47]), "=f"(d[48]), "=f"(d[49]), "=f"(d[50]), "=f"(d[51]), "=f"(d[52]), "=f"(d[53]), "=f"(d[54]), "=f"(d[55]), "=f"(d[56]), "=f"(d[57]), "=f"(d[58]), "=f"(d[59]), "=f"(d[60]), "=f"(d[61]), "=f"(d[62]), "=f"(d[63]), "=f"(d[64]), "=f"(d[65]), "=f"(d[66]), "=f"(d[67]), "=f"(d[68]), "=f"(d[69]), "=f"(d[70]), "=f"(d[71]), "=f"(d[72]), "=f"(d[73]), "=f"(d[74]), "=f"(d[75]), "=f"(d[76]), "=f"(d[77]), "=f"(d[78]), "=f"(d[79]), "=f"(d[80]), "=f"(d[81]), "=f"(d[82]), "=f"(d[83]), "=f"(d[84]), "=f"(d[85]), "=f"(d[86]), "=f"(d[87]), "=f"(d[88]), "=f"(d[89]), "=f"(d[90]), "=f"(d[91]), "=f"(d[92]), "=f"(d[93]), "=f"(d[94]), "=f"(d[95])
      : "l"(da), "l"(db));
  }
}
template <int SD> __device__ __forceinline__ void wgmma_ss_n96_t1(float (&d)[48], uint64_t da, uint64_t db) {
  if constexpr (SD == 1) {
    asm volatile("{\n.reg .pred p;\nsetp.ne.b32 p, 1, 0;\n"
      "wgmma.mma_async.sync.aligned.m64n96k16.f32.bf16.bf16 {%0, %1, %2, %3, %4, %5, %6, %7, %8, %9, %10, %11, %12, %13, %14, %15, %16, %17, %18, %19, %20, %21, %22, %23, %24, %25, %26, %27, %28, %29, %30, %31, %32, %33, %34, %35, %36, %37, %38, %39, %40, %41, %42, %43, %44, %45, %46, %47}, %48, %49, p, 1, 1, 0, 1;\n}\n"
      : "+f"(d[0]), "+f"(d[1]), "+f"(d[2]), "+f"(d[3]), "+f"(d[4]), "+f"(d[5]), "+f"(d[6]), "+f"(d[7]), "+f"(d[8]), "+f"(d[9]), "+f"(d[10]), "+f"(d[11]), "+f"(d[12]), "+f"(d[13]), "+f"(d[14]), "+f"(d[15]), "+f"(d[16]), "+f"(d[17]), "+f"(d[18]), "+f"(d[19]), "+f"(d[20]), "+f"(d[21]), "+f"(d[22]), "+f"(d[23]), "+f"(d[24]), "+f"(d[25]), "+f"(d[26]), "+f"(d[27]), "+f"(d[28]), "+f"(d[29]), "+f"(d[30]), "+f"(d[31]), "+f"(d[32]), "+f"(d[33]), "+f"(d[34]), "+f"(d[35]), "+f"(d[36]), "+f"(d[37]), "+f"(d[38]), "+f"(d[39]), "+f"(d[40]), "+f"(d[41]), "+f"(d[42]), "+f"(d[43]), "+f"(d[44]), "+f"(d[45]), "+f"(d[46]), "+f"(d[47])
      : "l"(da), "l"(db));
  } else if constexpr (SD == 2) {
    asm volatile("{\n.reg .pred p;\nsetp.ne.b32 p, 0, 0;\n"
      "wgmma.mma_async.sync.aligned.m64n96k16.f32.bf16.bf16 {%0, %1, %2, %3, %4, %5, %6, %7, %8, %9, %10, %11, %12, %13, %14, %15, %16, %17, %18, %19, %20, %21, %22, %23, %24, %25, %26, %27, %28, %29, %30, %31, %32, %33, %34, %35, %36, %37, %38, %39, %40, %41, %42, %43, %44, %45, %46, %47}, %48, %49, p, 1, 1, 0, 1;\n}\n"
      : "+f"(d[0]), "+f"(d[1]), "+f"(d[2]), "+f"(d[3]), "+f"(d[4]), "+f"(d[5]), "+f"(d[6]), "+f"(d[7]), "+f"(d[8]), "+f"(d[9]), "+f"(d[10]), "+f"(d[11]), "+f"(d[12]), "+f"(d[13]), "+f"(d[14]), "+f"(d[15]), "+f"(d[16]), "+f"(d[17]), "+f"(d[18]), "+f"(d[19]), "+f"(d[20]), "+f"(d[21]), "+f"(d[22]), "+f"(d[23]), "+f"(d[24]), "+f"(d[25]), "+f"(d[26]), "+f"(d[27]), "+f"(d[28]), "+f"(d[29]), "+f"(d[30]), "+f"(d[31]), "+f"(d[32]), "+f"(d[33]), "+f"(d[34]), "+f"(d[35]), "+f"(d[36]), "+f"(d[37]), "+f"(d[38]), "+f"(d[39]), "+f"(d[40]), "+f"(d[41]), "+f"(d[42]), "+f"(d[43]), "+f"(d[44]), "+f"(d[45]), "+f"(d[46]), "+f"(d[47])
      : "l"(da), "l"(db));
  } else {
    asm volatile("{\n.reg .pred p;\nsetp.ne.b32 p, 0, 0;\n"
      "wgmma.mma_async.sync.aligned.m64n96k16.f32.bf16.bf16 {%0, %1, %2, %3, %4, %5, %6, %7, %8, %9, %10, %11, %12, %13, %14, %15, %16, %17, %18, %19, %20, %21, %22, %23, %24, %25, %26, %27, %28, %29, %30, %31, %32, %33, %34, %35, %36, %37, %38, %39, %40, %41, %42, %43, %44, %45, %46, %47}, %48, %49, p, 1, 1, 0, 1;\n}\n"
      : "=f"(d[0]), "=f"(d[1]), "=f"(d[2]), "=f"(d[3]), "=f"(d[4]), "=f"(d[5]), "=f"(d[6]), "=f"(d[7]), "=f"(d[8]), "=f"(d[9]), "=f"(d[10]), "=f"(d[11]), "=f"(d[12]), "=f"(d[13]), "=f"(d[14]), "=f"(d[15]), "=f"(d[16]), "=f"(d[17]), "=f"(d[18]), "=f"(d[19]), "=f"(d[20]), "=f"(d[21]), "=f"(d[22]), "=f"(d[23]), "=f"(d[24]), "=f"(d[25]), "=f"(d[26]), "=f"(d[27]), "=f"(d[28]), "=f"(d[29]), "=f"(d[30]), "=f"(d[31]), "=f"(d[32]), "=f"(d[33]), "=f"(d[34]), "=f"(d[35]), "=f"(d[36]), "=f"(d[37]), "=f"(d[38]), "=f"(d[39]), "=f"(d[40]), "=f"(d[41]), "=f"(d[42]), "=f"(d[43]), "=f"(d[44]), "=f"(d[45]), "=f"(d[46]), "=f"(d[47])
      : "l"(da), "l"(db));
  }
}
template <int SD> __device__ __forceinline__ void wgmma_rs_n96_t1(float (&d)[48], uint32_t a0, uint32_t a1, uint32_t a2, uint32_t a3, uint64_t db) {
  if constexpr (SD == 1) {
    asm volatile("{\n.reg .pred p;\nsetp.ne.b32 p, 1, 0;\n"
      "wgmma.mma_async.sync.aligned.m64n96k16.f32.bf16.bf16 {%0, %1, %2, %3, %4, %5, %6, %7, %8, %9, %10, %11, %12, %13, %14, %15, %16, %17, %18, %19, %20, %21, %22, %23, %24, %25, %26, %27, %28, %29, %30, %31, %32, %33, %34, %35, %36, %37, %38, %39, %40, %41, %42, %43, %44, %45, %46, %47}, {%48, %49, %50, %51}, %52, p, 1, 1, 1;\n}\n"
      : "+f"(d[0]), "+f"(d[1]), "+f"(d[2]), "+f"(d[3]), "+f"(d[4]), "+f"(d[5]), "+f"(d[6]), "+f"(d[7]), "+f"(d[8]), "+f"(d[9]), "+f"(d[10]), "+f"(d[11]), "+f"(d[12]), "+f"(d[13]), "+f"(d[14]), "+f"(d[15]), "+f"(d[16]), "+f"(d[17]), "+f"(d[18]), "+f"(d[19]), "+f"(d[20]), "+f"(d[21]), "+f"(d[22]), "+f"(d[23]), "+f"(d[24]), "+f"(d[25]), "+f"(d[26]), "+f"(d[27]), "+f"(d[28]), "+f"(d[29]), "+f"(d[30]), "+f"(d[31]), "+f"(d[32]), "+f"(d[33]), "+f"(d[34]), "+f"(d[35]), "+f"(d[36]), "+f"(d[37]), "+f"(d[38]), "+f"(d[39]), "+f"(d[40]), "+f"(d[41]), "+f"(d[42]), "+f"(d[43]), "+f"(d[44]), "+f"(d[45]), "+f"(d[46]), "+f"(d[47])
      : "r"(a0), "r"(a1), "r"(a2), "r"(a3), "l"(db));
  } else if constexpr (SD == 2) {
    asm volatile("{\n.reg .pred p;\nsetp.ne.b32 p, 0, 0;\n"
      "wgmma.mma_async.sync.aligned.m64n96k16.f32.bf16.bf16 {%0, %1, %2, %3, %4, %5, %6, %7, %8, %9, %10, %11, %12, %13, %14, %15, %16, %17, %18, %19, %20, %21, %22, %23, %24, %25, %26, %27, %28, %29, %30, %31, %32, %33, %34, %35, %36, %37, %38, %39, %40, %41, %42, %43, %44, %45, %46, %47}, {%48, %49, %50, %51}, %52, p, 1, 1, 1;\n}\n"
      : "+f"(d[0]), "+f"(d[1]), "+f"(d[2]), "+f"(d[3]), "+f"(d[4]), "+f"(d[5]), "+f"(d[6]), "+f"(d[7]), "+f"(d[8]), "+f"(d[9]), "+f"(d[10]), "+f"(d[11]), "+f"(d[12]), "+f"(d[13]), "+f"(d[14]), "+f"(d[15]), "+f"(d[16]), "+f"(d[17]), "+f"(d[18]), "+f"(d[19]), "+f"(d[20]), "+f"(d[21]), "+f"(d[22]), "+f"(d[23]), "+f"(d[24]), "+f"(d[25]), "+f"(d[26]), "+f"(d[27]), "+f"(d[28]), "+f"(d[29]), "+f"(d[30]), "+f"(d[31]), "+f"(d[32]), "+f"(d[33]), "+f"(d[34]), "+f"(d[35]), "+f"(d[36]), "+f"(d[37]), "+f"(d[38]), "+f"(d[39]), "+f"(d[40]), "+f"(d[41]), "+f"(d[42]), "+f"(d[43]), "+f"(d[44]), "+f"(d[45]), "+f"(d[46]), "+f"(d[47])
      : "r"(a0), "r"(a1), "r"(a2), "r"(a3), "l"(db));
  } else {
    asm volatile("{\n.reg .pred p;\nsetp.ne.b32 p, 0, 0;\n"
      "wgmma.mma_async.sync.aligned.m64n96k16.f32.bf16.bf16 {%0, %1, %2, %3, %4, %5, %6, %7, %8, %9, %10, %11, %12, %13, %14, %15, %16, %17, %18, %19, %20, %21, %22, %23, %24, %25, %26, %27, %28, %29, %30, %31, %32, %33, %34, %35, %36, %37, %38, %39, %40, %41, %42, %43, %44, %45, %46, %47}, {%48, %49, %50, %51}, %52, p, 1, 1, 1;\n}\n"
      : "=f"(d[0]), "=f"(d[1]), "=f"(d[2]), "=f"(d[3]), "=f"(d[4]), "=f"(d[5]), "=f"(d[6]), "=f"(d[7]), "=f"(d[8]), "=f"(d[9]), "=f"(d[10]), "=f"(d[11]), "=f"(d[12]), "=f"(d[13]), "=f"(d[14]), "=f"(d[15]), "=f"(d[16]), "=f"(d[17]), "=f"(d[18]), "=f"(d[19]), "=f"(d[20]), "=f"(d[21]), "=f"(d[22]), "=f"(d[23]), "=f"(d[24]), "=f"(d[25]), "=f"(d[26]), "=f"(d[27]), "=f"(d[28]), "=f"(d[29]), "=f"(d[30]), "=f"(d[31]), "=f"(d[32]), "=f"(d[33]), "=f"(d[34]), "=f"(d[35]), "=f"(d[36]), "=f"(d[37]), "=f"(d[38]), "=f"(d[39]), "=f"(d[40]), "=f"(d[41]), "=f"(d[42]), "=f"(d[43]), "=f"(d[44]), "=f"(d[45]), "=f"(d[46]), "=f"(d[47])
      : "r"(a0), "r"(a1), "r"(a2), "r"(a3), "l"(db));
  }
}
template <int SD> __device__ __forceinline__ void wgmma_rs_n64_t0(float (&d)[32], uint32_t a0, uint32_t a1, uint32_t a2, uint32_t a3, uint64_t db) {
  if constexpr (SD == 1) {
    asm volatile("{\n.reg .pred p;\nsetp.ne.b32 p, 1, 0;\n"
      "wgmma.mma_async.sync.aligned.m64n64k16.f32.bf16.bf16 {%0, %1, %2, %3, %4, %5, %6, %7, %8, %9, %10, %11, %12, %13, %14, %15, %16, %17, %18, %19, %20, %21, %22, %23, %24, %25, %26, %27, %28, %29, %30, %31}, {%32, %33, %34, %35}, %36, p, 1, 1, 0;\n}\n"
      : "+f"(d[0]), "+f"(d[1]), "+f"(d[2]), "+f"(d[3]), "+f"(d[4]), "+f"(d[5]), "+f"(d[6]), "+f"(d[7]), "+f"(d[8]), "+f"(d[9]), "+f"(d[10]), "+f"(d[11]), "+f"(d[12]), "+f"(d[13]), "+f"(d[14]), "+f"(d[15]), "+f"(d[16]), "+f"(d[17]), "+f"(d[18]), "+f"(d[19]), "+f"(d[20]), "+f"(d[21]), "+f"(d[22]), "+f"(d[23]), "+f"(d[24]), "+f"(d[25]), "+f"(d[26]), "+f"(d[27]), "+f"(d[28]), "+f"(d[29]), "+f"(d[30]), "+f"(d[31])
      : "r"(a0), "r"(a1), "r"(a2), "r"(a3), "l"(db));
  } else if constexpr (SD == 2) {
    asm volatile("{\n.reg .pred p;\nsetp.ne.b32 p, 0, 0;\n"
      "wgmma.mma_async.sync.aligned.m64n64k16.f32.bf16.bf16 {%0, %1, %2, %3, %4, %5, %6, %7, %8, %9, %10, %11, %12, %13, %14, %15, %16, %17, %18, %19, %20, %21, %22, %23, %24, %25, %26, %27, %28, %29, %30, %31}, {%32, %33, %34, %35}, %36, p, 1, 1, 0;\n}\n"
      : "+f"(d[0]), "+f"(d[1]), "+f"(d[2]), "+f"(d[3]), "+f"(d[4]), "+f"(d[5]), "+f"(d[6]), "+f"(d[7]), "+f"(d[8]), "+f"(d[9]), "+f"(d[10]), "+f"(d[11]), "+f"(d[12]), "+f"(d[13]), "+f"(d[14]), "+f"(d[15]), "+f"(d[16]), "+f"(d[17]), "+f"(d[18]), "+f"(d[19]), "+f"(d[20]), "+f"(d[21]), "+f"(d[22]), "+f"(d[23]), "+f"(d[24]), "+f"(d[25]), "+f"(d[26]), "+f"(d[27]), "+f"(d[28]), "+f"(d[29]), "+f"(d[30]), "+f"(d[31])
      : "r"(a0), "r"(a1), "r"(a2), "r"(a3), "l"(db));
  } else {
    asm volatile("{\n.reg .pred p;\nsetp.ne.b32 p, 0, 0;\n"
      "wgmma.mma_async.sync.aligned.m64n64k16.f32.bf16.bf16 {%0, %1, %2, %3, %4, %5, %6, %7, %8, %9, %10, %11, %12, %13, %14, %15, %16, %17, %18, %19, %20, %21, %22, %23, %24, %25, %26, %27, %28, %29, %30, %31}, {%32, %33, %34, %35}, %36, p, 1, 1, 0;\n}\n"
      : "=f"(d[0]), "=f"(d[1]), "=f"(d[2]), "=f"(d[3]), "=f"(d[4]), "=f"(d[5]), "=f"(d[6]), "=f"(d[7]), "=f"(d[8]), "=f"(d[9]), "=f"(d[10]), "=f"(d[11]), "=f"(d[12]), "=f"(d[13]), "=f"(d[14]), "=f"(d[15]), "=f"(d[16]), "=f"(d[17]), "=f"(d[18]), "=f"(d[19]), "=f"(d[20]), "=f"(d[21]), "=f"(d[22]), "=f"(d[23]), "=f"(d[24]), "=f"(d[25]), "=f"(d[26]), "=f"(d[27]), "=f"(d[28]), "=f"(d[29]), "=f"(d[30]), "=f"(d[31])
      : "r"(a0), "r"(a1), "r"(a2), "r"(a3), "l"(db));
  }
}
template <int SD> __device__ __forceinline__ void wgmma_rs_n32_t1(float (&d)[16], uint32_t a0, uint32_t a1, uint32_t a2, uint32_t a3, uint64_t db) {
  if constexpr (SD == 1) {
    asm volatile("{\n.reg .pred p;\nsetp.ne.b32 p, 1, 0;\n"
      "wgmma.mma_async.sync.aligned.m64n32k16.f32.bf16.bf16 {%0, %1, %2, %3, %4, %5, %6, %7, %8, %9, %10, %11, %12, %13, %14, %15}, {%16, %17, %18, %19}, %20, p, 1, 1, 1;\n}\n"
      : "+f"(d[0]), "+f"(d[1]), "+f"(d[2]), "+f"(d[3]), "+f"(d[4]), "+f"(d[5]), "+f"(d[6]), "+f"(d[7]), "+f"(d[8]), "+f"(d[9]), "+f"(d[10]), "+f"(d[11]), "+f"(d[12]), "+f"(d[13]), "+f"(d[14]), "+f"(d[15])
      : "r"(a0), "r"(a1), "r"(a2), "r"(a3), "l"(db));
  } else if constexpr (SD == 2) {
    asm volatile("{\n.reg .pred p;\nsetp.ne.b32 p, 0, 0;\n"
      "wgmma.mma_async.sync.aligned.m64n32k16.f32.bf16.bf16 {%0, %1, %2, %3, %4, %5, %6, %7, %8, %9, %10, %11, %12, %13, %14, %15}, {%16, %17, %18, %19}, %20, p, 1, 1, 1;\n}\n"
      : "+f"(d[0]), "+f"(d[1]), "+f"(d[2]), "+f"(d[3]), "+f"(d[4]), "+f"(d[5]), "+f"(d[6]), "+f"(d[7]), "+f"(d[8]), "+f"(d[9]), "+f"(d[10]), "+f"(d[11]), "+f"(d[12]), "+f"(d[13]), "+f"(d[14]), "+f"(d[15])
      : "r"(a0), "r"(a1), "r"(a2), "r"(a3), "l"(db));
  } else {
    asm volatile("{\n.reg .pred p;\nsetp.ne.b32 p, 0, 0;\n"
      "wgmma.mma_async.sync.aligned.m64n32k16.f32.bf16.bf16 {%0, %1, %2, %3, %4, %5, %6, %7, %8, %9, %10, %11, %12, %13, %14, %15}, {%16, %17, %18, %19}, %20, p, 1, 1, 1;\n}\n"
      : "=f"(d[0]), "=f"(d[1]), "=f"(d[2]), "=f"(d[3]), "=f"(d[4]), "=f"(d[5]), "=f"(d[6]), "=f"(d[7]), "=f"(d[8]), "=f"(d[9]), "=f"(d[10]), "=f"(d[11]), "=f"(d[12]), "=f"(d[13]), "=f"(d[14]), "=f"(d[15])
      : "r"(a0), "r"(a1), "r"(a2), "r"(a3), "l"(db));
  }
}
template <int SD> __device__ __forceinline__ void wgmma_rs_n8_t0(float (&d)[4], uint32_t a0, uint32_t a1, uint32_t a2, uint32_t a3, uint64_t db) {
  if constexpr (SD == 1) {
    asm volatile("{\n.reg .pred p;\nsetp.ne.b32 p, 1, 0;\n"
      "wgmma.mma_async.sync.aligned.m64n8k16.f32.bf16.bf16 {%0, %1, %2, %3}, {%4, %5, %6, %7}, %8, p, 1, 1, 0;\n}\n"
      : "+f"(d[0]), "+f"(d[1]), "+f"(d[2]), "+f"(d[3])
      : "r"(a0), "r"(a1), "r"(a2), "r"(a3), "l"(db));
  } else if constexpr (SD == 2) {
    asm volatile("{\n.reg .pred p;\nsetp.ne.b32 p, 0, 0;\n"
      "wgmma.mma_async.sync.aligned.m64n8k16.f32.bf16.bf16 {%0, %1, %2, %3}, {%4, %5, %6, %7}, %8, p, 1, 1, 0;\n}\n"
      : "+f"(d[0]), "+f"(d[1]), "+f"(d[2]), "+f"(d[3])
      : "r"(a0), "r"(a1), "r"(a2), "r"(a3), "l"(db));
  } else {
    asm volatile("{\n.reg .pred p;\nsetp.ne.b32 p, 0, 0;\n"
      "wgmma.mma_async.sync.aligned.m64n8k16.f32.bf16.bf16 {%0, %1, %2, %3}, {%4, %5, %6, %7}, %8, p, 1, 1, 0;\n}\n"
      : "=f"(d[0]), "=f"(d[1]), "=f"(d[2]), "=f"(d[3])
      : "r"(a0), "r"(a1), "r"(a2), "r"(a3), "l"(db));
  }
}

__device__ __forceinline__ void wg_fence()  { asm volatile("wgmma.fence.sync.aligned;" ::: "memory"); }
__device__ __forceinline__ void wg_commit() { asm volatile("wgmma.commit_group.sync.aligned;" ::: "memory"); }
template <int N> __device__ __forceinline__ void wg_wait() { asm volatile("wgmma.wait_group.sync.aligned %0;" :: "n"(N) : "memory"); }
template <int N> __device__ __forceinline__ void fence_regs(float (&d)[N]) {
#pragma unroll
  for (int i = 0; i < N; i++) asm volatile("" : "+f"(d[i]) :: "memory");
}
__device__ __forceinline__ constexpr uint64_t mk_desc(uint32_t addr, uint32_t lbo, uint32_t sbo, uint32_t swz) {
  return (uint64_t)(addr >> 4) | ((uint64_t)(lbo >> 4) << 16) | ((uint64_t)(sbo >> 4) << 32) | ((uint64_t)swz << 62);
}
__device__ __forceinline__ uint32_t pack_bf16(float lo, float hi) {
  uint32_t r; asm("cvt.rn.bf16x2.f32 %0, %1, %2;" : "=r"(r) : "f"(hi), "f"(lo)); return r;
}
__device__ __forceinline__ uint32_t hmul2(uint32_t a, uint32_t b) {
  uint32_t r; asm("mul.rn.bf16x2 %0, %1, %2;" : "=r"(r) : "r"(a), "r"(b)); return r;
}
template <int HI> __device__ __forceinline__ uint32_t hmul2_b(uint32_t a, uint32_t b) {
  uint32_t r;
  if (HI) asm("{\n.reg .b16 l, h;\n.reg .b32 t;\nmov.b32 {l, h}, %2;\nmov.b32 t, {h, h};\nmul.rn.bf16x2 %0, %1, t;\n}\n" : "=r"(r) : "r"(a), "r"(b));
  else    asm("{\n.reg .b16 l, h;\n.reg .b32 t;\nmov.b32 {l, h}, %2;\nmov.b32 t, {l, l};\nmul.rn.bf16x2 %0, %1, t;\n}\n" : "=r"(r) : "r"(a), "r"(b));
  return r;
}
__device__ __forceinline__ uint32_t hfma2(uint32_t a, uint32_t b, uint32_t c) {
  uint32_t r; asm("fma.rn.bf16x2 %0, %1, %2, %3;" : "=r"(r) : "r"(a), "r"(b), "r"(c)); return r;
}
__device__ __forceinline__ float ex2(float x) { float r; asm("ex2.approx.ftz.f32 %0, %1;" : "=f"(r) : "f"(x)); return r; }
__device__ __forceinline__ float rsq(float x) { float r; asm("rsqrt.approx.ftz.f32 %0, %1;" : "=f"(r) : "f"(x)); return r; }
__device__ __forceinline__ float rcp(float x) { float r; asm("rcp.approx.ftz.f32 %0, %1;" : "=f"(r) : "f"(x)); return r; }
__device__ __forceinline__ void stsm4(uint32_t addr, uint32_t r0, uint32_t r1, uint32_t r2, uint32_t r3) {
  asm volatile("stmatrix.sync.aligned.m8n8.x4.shared.b16 [%0], {%1,%2,%3,%4};" :: "r"(addr), "r"(r0), "r"(r1), "r"(r2), "r"(r3) : "memory");
}
__device__ __forceinline__ void fence_async() { asm volatile("fence.proxy.async.shared::cta;" ::: "memory"); }
__device__ __forceinline__ void bar_sync_n(int id, int n) { asm volatile("bar.sync %0, %1;" :: "r"(id), "r"(n) : "memory"); }
__device__ __forceinline__ void bar_arrive_n(int id, int n) { asm volatile("bar.arrive %0, %1;" :: "r"(id), "r"(n) : "memory"); }
__device__ __forceinline__ bool bar_wg_or(int id, bool v) {
  uint32_t r;
  asm volatile("{\n.reg .pred p, q;\nsetp.ne.u32 q, %2, 0;\nbar.red.or.pred p, %1, 128, q;\nselp.u32 %0, 0, 1, p;\n}\n"
               : "=r"(r) : "r"(id), "r"((uint32_t)v) : "memory");
  return __ballot_sync(0xffffffffu, r != 0) == 0;
}
__device__ __forceinline__ void mbar_init(uint32_t bar, uint32_t cnt) { asm volatile("mbarrier.init.shared::cta.b64 [%0], %1;" :: "r"(bar), "r"(cnt) : "memory"); }
__device__ __forceinline__ void mbar_expect(uint32_t bar, uint32_t bytes) {
  asm volatile("mbarrier.arrive.expect_tx.shared::cta.b64 _, [%0], %1;" :: "r"(bar), "r"(bytes) : "memory");
}
__device__ __forceinline__ void mbar_arrive(uint32_t bar) { asm volatile("mbarrier.arrive.shared::cta.b64 _, [%0];" :: "r"(bar) : "memory"); }
__device__ __forceinline__ void mbar_wait(uint32_t bar, uint32_t parity) {
  asm volatile("{\n.reg .pred p;\n.reg .u32 n;\nmov.u32 n, 0;\n"
               "LW_%=:\nmbarrier.try_wait.parity.shared::cta.b64 p, [%0], %1;\n@p bra.uni LD_%=;\n"
               "add.u32 n, n, 1;\nsetp.lt.u32 p, n, 4194304;\n@p bra.uni LW_%=;\ntrap;\nLD_%=:\n}\n"
               :: "r"(bar), "r"(parity) : "memory");
}
__device__ __forceinline__ void tma5(uint32_t dst, const CUtensorMap* m, uint32_t bar, int c0, int c1, int c2, int c3, int c4) {
  asm volatile("cp.async.bulk.tensor.5d.shared::cluster.global.mbarrier::complete_tx::bytes [%0], [%1, {%3, %4, %5, %6, %7}], [%2];"
               :: "r"(dst), "l"(m), "r"(bar), "r"(c0), "r"(c1), "r"(c2), "r"(c3), "r"(c4) : "memory");
}
__device__ __forceinline__ void tma3(uint32_t dst, const CUtensorMap* m, uint32_t bar, int c0, int c1, int c2) {
  asm volatile("cp.async.bulk.tensor.3d.shared::cluster.global.mbarrier::complete_tx::bytes [%0], [%1, {%3, %4, %5}], [%2];"
               :: "r"(dst), "l"(m), "r"(bar), "r"(c0), "r"(c1), "r"(c2) : "memory");
}
__device__ __forceinline__ void bulk_g2s(uint32_t dst, const void* src, uint32_t bytes, uint32_t bar) {
  asm volatile("cp.async.bulk.shared::cluster.global.mbarrier::complete_tx::bytes [%0], [%1], %2, [%3];"
               :: "r"(dst), "l"(src), "r"(bytes), "r"(bar) : "memory");
}
__device__ __forceinline__ uint32_t lds32(uint32_t addr) {
  uint32_t v; asm volatile("ld.shared.u32 %0, [%1];" : "=r"(v) : "r"(addr)); return v;
}
__device__ __forceinline__ uint64_t opaque(uint64_t v) { asm volatile("" : "+l"(v)); return v; }
__device__ __forceinline__ uint4 lds128(uint32_t addr) {
  uint4 v; asm volatile("ld.shared.v4.u32 {%0,%1,%2,%3}, [%4];" : "=r"(v.x), "=r"(v.y), "=r"(v.z), "=r"(v.w) : "r"(addr)); return v;
}
__device__ __forceinline__ void sts128(uint32_t addr, uint4 v) {
  asm volatile("st.shared.v4.u32 [%0], {%1,%2,%3,%4};" :: "r"(addr), "r"(v.x), "r"(v.y), "r"(v.z), "r"(v.w) : "memory");
}
__device__ __forceinline__ uint4 ldg128_stream(const void* p) {
  uint4 v; asm volatile("ld.global.nc.L1::no_allocate.v4.u32 {%0,%1,%2,%3}, [%4];" : "=r"(v.x), "=r"(v.y), "=r"(v.z), "=r"(v.w) : "l"(p)); return v;
}
__device__ __forceinline__ void stg128(void* p, uint32_t a, uint32_t b, uint32_t c, uint32_t d) {
  asm volatile("st.global.v4.u32 [%0], {%1,%2,%3,%4};" :: "l"(p), "r"(a), "r"(b), "r"(c), "r"(d) : "memory");
}
__device__ __forceinline__ void prefetch_l2(const void* p, uint32_t bytes) {
  asm volatile("cp.async.bulk.prefetch.L2.global [%0], %1;" :: "l"(p), "r"(bytes) : "memory");
}
__device__ __forceinline__ bool elect_one() {
  uint32_t r; asm volatile("{\n.reg .pred p;\nelect.sync _|p, 0xffffffff;\nselp.u32 %0, 1, 0, p;\n}\n" : "=r"(r)); return r != 0;
}
__device__ __forceinline__ float bf_lo(uint32_t u) { return __uint_as_float(u << 16); }
__device__ __forceinline__ float bf_hi(uint32_t u) { return __uint_as_float(u & 0xFFFF0000u); }
__device__ __forceinline__ float rbf(float x) { return bf_lo(pack_bf16(x, 0.f)); }
__device__ __forceinline__ int orig_tok(int r) { return ((r & 31) >> 2) * 8 + (r >> 5) * 4 + (r & 3); }

__device__ __forceinline__ int slot_window(int s, bool g132) {
  const int A0 = g132 ? 396 + 264 + 60 : 47 * 47, A1 = A0 + 72, B0 = g132 ? 3 * 396 + 264 + 60 : A1, B1 = B0 + 23;
  const int i = s - (s >= B1 ? 95 : s >= A1 ? 72 : 0);
  const int k = s >= B0 ? s - B0 + 72 : s - A0;
  const bool border = (s >= A0 && s < A1) || (s >= B0 && s < B1);
  const int iy = (i * 2789) >> 17;
  return border ? (k < 48 ? (47 << 8 | k) : ((k - 48) << 8 | 47)) : (iy << 8 | (i - iy * 47));
}

__device__ __forceinline__ void load_eb(uint32_t (&e)[16], uint32_t eb_addr) {
#pragma unroll
  for (int j = 0; j < 4; j++) {
    const uint4 v = lds128(eb_addr + j * 2048);
    e[4 * j] = v.x; e[4 * j + 1] = v.y; e[4 * j + 2] = v.z; e[4 * j + 3] = v.w;
  }
}
__device__ __forceinline__ void softmax_fast(const float (&s)[32], uint32_t (&p)[16]) {
#pragma unroll
  for (int i = 0; i < 16; i++) p[i] = hmul2(pack_bf16(ex2(s[2 * i]), ex2(s[2 * i + 1])), p[i]);
}
__device__ __forceinline__ uint32_t hmax2(uint32_t a, uint32_t b) {
  uint32_t r; asm("max.bf16x2 %0, %1, %2;" : "=r"(r) : "r"(a), "r"(b)); return r;
}
__device__ __forceinline__ uint32_t hmax2_nan(uint32_t a, uint32_t b) {
  uint32_t r; asm("max.NaN.bf16x2 %0, %1, %2;" : "=r"(r) : "r"(a), "r"(b)); return r;
}
__device__ __forceinline__ float quad_max(float m) {
  m = fmaxf(m, __shfl_xor_sync(0xffffffffu, m, 1));
  return fmaxf(m, __shfl_xor_sync(0xffffffffu, m, 2));
}
__device__ __forceinline__ void softmax_true_max(const float (&s)[32], uint32_t (&p)[16]) {
  float m0 = s[0], m1 = s[2];
#pragma unroll
  for (int g = 0; g < 8; g++) {
    m0 = fmaxf(m0, fmaxf(s[4 * g + 0], s[4 * g + 1]));
    m1 = fmaxf(m1, fmaxf(s[4 * g + 2], s[4 * g + 3]));
  }
  m0 = quad_max(m0); m1 = quad_max(m1);
  uint32_t n0 = 0, n1 = 0;
#pragma unroll
  for (int g = 0; g < 8; g++) {
    p[2 * g + 0] = hmul2(pack_bf16(ex2(s[4 * g + 0] - m0), ex2(s[4 * g + 1] - m0)), p[2 * g + 0]);
    p[2 * g + 1] = hmul2(pack_bf16(ex2(s[4 * g + 2] - m1), ex2(s[4 * g + 3] - m1)), p[2 * g + 1]);
    n0 = hmax2(n0, p[2 * g]); n1 = hmax2(n1, p[2 * g + 1]);
  }
  const uint32_t r = pack_bf16(rcp(quad_max(fmaxf(bf_lo(n0), bf_hi(n0)))), rcp(quad_max(fmaxf(bf_lo(n1), bf_hi(n1)))));
#pragma unroll
  for (int g = 0; g < 8; g++) { p[2 * g] = hmul2_b<0>(p[2 * g], r); p[2 * g + 1] = hmul2_b<1>(p[2 * g + 1], r); }
}
template <int H> __device__ __forceinline__ void issue_s(float (&s)[32], const uint32_t (&q)[24], uint64_t dK) {
  constexpr int Q0 = (H == 0 ? 0 : H == 1 ? 4 : H == 2 ? 12 : 16), P0 = (H == 0 ? 0 : H == 1 ? 3 : H == 2 ? 7 : 10);
  wgmma_rs_n64_t0<(H >= 2 ? TIE : 0)>(s, q[Q0], q[Q0 + 1], q[Q0 + 2], q[Q0 + 3], dK + P0 * 64);
  wgmma_rs_n64_t0<1>(s, q[Q0 + 4], q[Q0 + 5], q[Q0 + 6], q[Q0 + 7], dK + P0 * 64 + 128);
}
template <int H> __device__ __forceinline__ void issue_pv(float (&o)[16], const uint32_t (&p)[16], uint64_t dV) {
  constexpr int P0 = (H == 0 ? 0 : H == 1 ? 3 : H == 2 ? 7 : 10);
  wgmma_rs_n32_t1<0>(o, p[0], p[1], p[2], p[3], dV + P0 * 64);
  wgmma_rs_n32_t1<1>(o, p[4], p[5], p[6], p[7], dV + P0 * 64 + 16);
  wgmma_rs_n32_t1<1>(o, p[8], p[9], p[10], p[11], dV + P0 * 64 + 32);
  wgmma_rs_n32_t1<1>(o, p[12], p[13], p[14], p[15], dV + P0 * 64 + 48);
}
__device__ __forceinline__ void issue_proj(float (&d)[48], uint64_t dX, uint64_t dW) {
#pragma unroll
  for (int s = 0; s < 6; s++) {
    const uint64_t a = dX + (s >> 1) * 256 + (s & 1) * 2, b = dW + s * 64;
    if (s == 0) wgmma_ss_n96_t1<0>(d, a, b); else wgmma_ss_n96_t1<1>(d, a, b);
  }
}
__device__ __forceinline__ void issue_qk(float (&d)[96], uint64_t dX, uint64_t dW) {
#pragma unroll
  for (int s = 0; s < 6; s++) {
    const uint64_t a = dX + (s >> 1) * 256 + (s & 1) * 2, b = dW + s * 128;
    if (s == 0) wgmma_ss_n192_t1<0>(d, a, b); else wgmma_ss_n192_t1<1>(d, a, b);
  }
}
__device__ __forceinline__ void pack_sumsq(const float* a, uint32_t (&f)[24], uint32_t (&sq)[8], uint32_t init) {
#pragma unroll
  for (int i = 0; i < 24; i++) f[i] = pack_bf16(a[2 * i], a[2 * i + 1]);
#pragma unroll
  for (int h = 0; h < 4; h++)
#pragma unroll
    for (int r = 0; r < 2; r++) {
      uint32_t u = f[6 * h + r], v = f[6 * h + 2 + r], w = f[6 * h + 4 + r];
      sq[2 * h + r] = hfma2(w, w, hfma2(v, v, hfma2(u, u, init)));
    }
}
__device__ __forceinline__ void scale_heads(uint32_t (&f)[24], const float (&r)[8]) {
#pragma unroll
  for (int h = 0; h < 4; h++) {
    const uint32_t p = pack_bf16(r[2 * h], r[2 * h + 1]);
#pragma unroll
    for (int c = 0; c < 3; c++) {
      f[6 * h + 2 * c] = hmul2_b<0>(f[6 * h + 2 * c], p);
      f[6 * h + 2 * c + 1] = hmul2_b<1>(f[6 * h + 2 * c + 1], p);
    }
  }
}
template <int ODD> __device__ __forceinline__ void norm_o(const float (&o)[16], uint32_t* of) {
  constexpr int SO = ODD ? 0 : 12, VO = ODD ? 4 : 0;
  const uint32_t p = pack_bf16(rcp(o[SO]), rcp(o[SO + 2]));
#pragma unroll
  for (int g = 0; g < 3; g++) {
    of[2 * g + 0] = hmul2_b<0>(pack_bf16(o[VO + 4 * g + 0], o[VO + 4 * g + 1]), p);
    of[2 * g + 1] = hmul2_b<1>(pack_bf16(o[VO + 4 * g + 2], o[VO + 4 * g + 3]), p);
  }
}

#define TL(i)
#define TG(i)

constexpr int BAR_KV = 1;
constexpr int BAR_AUX = 4;
constexpr int BAR_TAB = 7, BAR_SETUP = 8, BAR_PAR = 9;
constexpr int NO_TICKET = 0xFF;
#define MPOS 15
#define EPOS 8
#define TPOS 3
#define ORDER 1
#define BORDER_EXTRA 1
constexpr int MB_WQK = 0, MB_X = 8, MB_KV = 32, MB_WV = 56, MB_WO = 64, MB_TURN = 72, MB_RDY = 128, MB_WOC = 136;
constexpr uint32_t sb = 1024, mbar = sb + SM_BAR;
constexpr uint32_t EPS8 = 0x2A0D2A0Du;

__device__ __forceinline__ void load_x_interior(const CUtensorMap* tm_x, int w, int g) {
  mbar_expect(mbar + MB_X + 8 * g, 12288);
  tma5(sb + SM_WG + g * WG_SZ + WG_X, tm_x, mbar + MB_X + 8 * g, 0, 0, ((w >> 8) & 255) * 8 + 4, (w & 255) * 2 + 1, 0);
}
__device__ __forceinline__ void load_x(const CUtensorMap* tm_x, const CUtensorMap* tm_xq, int w, int g) {
  const uint32_t dst = sb + SM_WG + g * WG_SZ + WG_X, bar = mbar + MB_X + 8 * g;
  const int wy = (w >> 8) & 255, wx = w & 255;
  mbar_expect(bar, 12288);
  if (wy != NWX - 1 && wx != NWX - 1) {
    tma5(dst, tm_x, bar, 0, 0, wy * 8 + 4, wx * 2 + 1, 0);
  } else {
#pragma unroll 1
    for (int i = 0; i < 12; i++) {
      const int q = i & 3, c = i >> 2;
      int y = wy * 8 + 4 + (q & 1) * 4; if (y >= IMG) y -= IMG;
      int xq = wx * 2 + 1 + (q >> 1);   if (xq >= IMG / 4) xq -= IMG / 4;
      tma5(dst + i * 1024, tm_xq, bar, 0, 0, y, xq, c);
    }
  }
}
__device__ __forceinline__ uint32_t mask_off(int w) { return (uint32_t)(((w >> 8) & 255) * NWX + (w & 255)) * 8192u; }
__device__ __forceinline__ int lds_uniform(uint32_t addr) { return __shfl_sync(0xffffffffu, lds32(addr), 0); }

__device__ __forceinline__ void qkv_epilogue(float (&qk)[96], uint32_t (&qa)[24], uint64_t dX, uint64_t dWv, uint32_t k_dst) {
  uint32_t ka[24], sk[8], sq[8];
  float k01[4], k23[4], q01[4], q23[4], vv[48];
  constexpr uint64_t dSel = mk_desc(sb + SM_SEL, 128, 256, 0);
  wg_wait<0>(); fence_regs(qk);
  pack_sumsq(qk + 48, ka, sk, EPS8);
  pack_sumsq(qk, qa, sq, EPS8);
  wg_fence();
  wgmma_rs_n8_t0<0>(k01, sk[0], sk[1], sk[2], sk[3], dSel);
  wgmma_rs_n8_t0<0>(k23, sk[4], sk[5], sk[6], sk[7], dSel);
  wgmma_rs_n8_t0<0>(q01, sq[0], sq[1], sq[2], sq[3], dSel);
  wgmma_rs_n8_t0<0>(q23, sq[4], sq[5], sq[6], sq[7], dSel);
  wg_commit();
  issue_proj(vv, dX, dWv); wg_commit();
  const uint4 qs = lds128(sb + SM_MISC);
  wg_wait<1>(); fence_regs(k01); fence_regs(k23); fence_regs(q01); fence_regs(q23);
  const float rk[8] = {rsq(k01[0]), rsq(k01[2]), rsq(k01[1]), rsq(k01[3]), rsq(k23[0]), rsq(k23[2]), rsq(k23[1]), rsq(k23[3])};
  scale_heads(ka, rk);
#pragma unroll
  for (int i = 0; i < 6; i++) stsm4(k_dst + (i + (i >= 3)) * 1024, ka[2 * i], ka[2 * i + 1], ka[12 + 2 * i], ka[12 + 2 * i + 1]);
  wg_wait<0>(); fence_regs(vv);
#pragma unroll
  for (int i = 0; i < 6; i++)
    stsm4(k_dst + (WG_V - WG_K) + (i + (i >= 3)) * 1024, pack_bf16(vv[4 * i], vv[4 * i + 1]), pack_bf16(vv[4 * i + 2], vv[4 * i + 3]),
          pack_bf16(vv[24 + 4 * i], vv[24 + 4 * i + 1]), pack_bf16(vv[24 + 4 * i + 2], vv[24 + 4 * i + 3]));
  const float s0 = __uint_as_float(qs.x), s1 = __uint_as_float(qs.y), s2 = __uint_as_float(qs.z), s3 = __uint_as_float(qs.w);
  const float rq[8] = {rsq(q01[0]) * s0, rsq(q01[2]) * s0, rsq(q01[1]) * s1, rsq(q01[3]) * s1,
                       rsq(q23[0]) * s2, rsq(q23[2]) * s2, rsq(q23[1]) * s3, rsq(q23[3]) * s3};
  scale_heads(qa, rq);
  fence_async();
}
__device__ __forceinline__ void issue_out(float (&y)[48], const uint32_t (&of)[24], uint64_t dWo) {
  wg_fence();
#pragma unroll
  for (int s = 0; s < 6; s++) {
    if (s == 0) wgmma_rs_n96_t1<0>(y, of[0], of[1], of[2], of[3], dWo);
    else wgmma_rs_n96_t1<1>(y, of[4 * s], of[4 * s + 1], of[4 * s + 2], of[4 * s + 3], dWo + s * 16);
  }
  wg_commit();
}
__device__ __forceinline__ void ln_head(float (&y)[48], uint32_t (&yb)[24], float (&var)[4], uint64_t dOnes) {
  uint32_t sy[8];
  wg_wait<0>(); fence_regs(y);
  pack_sumsq(y, yb, sy, 0u);
  wg_fence();
  wgmma_rs_n8_t0<0>(var, sy[0], sy[1], sy[2], sy[3], dOnes);
  wgmma_rs_n8_t0<1>(var, sy[4], sy[5], sy[6], sy[7], dOnes);
  wg_commit();
}
__device__ __forceinline__ char* out_ptr(__nv_bfloat16* out, int win, int warp, uint32_t t16) {
  int py = ((win >> 8) & 255) * 8 + 4 + (warp & 1) * 4;  if (py >= IMG) py -= IMG;
  int px = (win & 255) * 8 + 4 + (warp >> 1) * 4;        if (px >= IMG) px -= IMG;
  return reinterpret_cast<char*>(out) + ((uint32_t)(py * IMG + px) * PIXB - warp * 512 + t16 + ((t16 & 0xC0) << 1) + (t16 & 0x100) * 287);
}
__device__ __forceinline__ uint32_t ln_tail(const uint32_t (&yb)[24], float (&var)[4], char* optr) {
  fence_regs(var);
  uint32_t last;
  const uint32_t nn = pack_bf16(rsq(fmaf(var[0], 1.f / 96.f, 1e-5f)), rsq(fmaf(var[2], 1.f / 96.f, 1e-5f)));
#pragma unroll
  for (int j = 0; j < 3; j++) {
    stg128(optr + j * 64, hmul2_b<0>(yb[8 * j], nn), hmul2_b<0>(yb[8 * j + 2], nn), hmul2_b<0>(yb[8 * j + 4], nn), hmul2_b<0>(yb[8 * j + 6], nn));
    last = hmul2_b<1>(yb[8 * j + 7], nn);
    stg128(optr + 2 * ROWB + j * 64, hmul2_b<1>(yb[8 * j + 1], nn), hmul2_b<1>(yb[8 * j + 3], nn), hmul2_b<1>(yb[8 * j + 5], nn), last);
  }
  return last;
}

__device__ __forceinline__ void load_mask_frag(uint32_t (&mk)[16], const char* tile, uint32_t t16) {
  asm volatile("" : "+r"(t16));
  const char* mrow = tile + (orig_tok(((t16 >> 9) << 4) + ((t16 >> 6) & 7)) * 128 + (t16 & 32) / 2);
  const bool odd = t16 & 16;
#pragma unroll
  for (int i = 0; i < 8; i++) {
    const uint4 v = ldg128_stream(mrow + (i & 1) * 2048 + (i >> 1) * 32);
    mk[i] = odd ? v.y : v.x; mk[8 + i] = odd ? v.w : v.z;
  }
}
__device__ __forceinline__ bool mask_unsafe(const uint32_t (&mk)[16]) {
  uint32_t x0 = mk[0], x1 = mk[1];
#pragma unroll
  for (int i = 2; i < 16; i += 2) { x0 = hmax2_nan(x0, mk[i]); x1 = hmax2_nan(x1, mk[i + 1]); }
  const bool nan_in = !(bf_lo(x0) == bf_lo(x0) && bf_hi(x0) == bf_hi(x0) && bf_lo(x1) == bf_lo(x1) && bf_hi(x1) == bf_hi(x1));
  const float r0 = quad_max(fmaxf(bf_lo(x0), bf_hi(x0))), r1 = quad_max(fmaxf(bf_lo(x1), bf_hi(x1)));
  return nan_in || !(fabsf(r0) <= 8.f && fabsf(r1) <= 8.f);
}

__device__ __forceinline__ void general_windows(const CUtensorMap* tm_x, const CUtensorMap* tm_xq, const char* mb, __nv_bfloat16* out, uint32_t xph) {
  int tid;
  asm volatile("mov.u32 %0, %%tid.x;" : "=r"(tid));
  const int lane = tid & 31;
  const int warp = __shfl_sync(0xffffffffu, (tid >> 5) & 3, 0), wg = __shfl_sync(0xffffffffu, tid >> 7, 0);
  const uint32_t t16 = (tid & 127) * 16, wgb = sb + SM_WG + wg * WG_SZ, bar_x = mbar + MB_X + 8 * wg;
  const uint32_t k_dst = wgb + WG_K + (lane >> 4) * 7168 + warp * 256 + (lane & 15) * 16;
  if (lds_uniform(sb + SM_GEN + wg * NENT * 4) < 0) return;
  mbar_wait(mbar + MB_WV, 0);
  mbar_wait(mbar + MB_RDY, 0);
  mbar_wait(mbar + MB_WOC, 0);
  const uint32_t slow_heads = lds_uniform(sb + SM_SLOW);
  const uint64_t dX = mk_desc(WG_X, 16, 512, 2) + (wgb >> 4), dK = mk_desc(WG_K, 1024, 128, 0) + (wgb >> 4), dV = mk_desc(WG_V, 128, 1024, 0) + (wgb >> 4);
#pragma unroll 1
  for (uint32_t gl = sb + SM_GEN + wg * NENT * 4;; gl += 4) {
    const int win = lds_uniform(gl);
    if (win < 0) break;
    uint32_t qa[24], of[24], mk[16];
    uint32_t tm;
    {
      load_mask_frag(mk, mb + mask_off(win), t16);
      float qk[96];
      mbar_wait(bar_x, xph); xph ^= 1;
      wg_fence();
      issue_qk(qk, dX, mk_desc(sb + SM_W, 12288, 1024, 1)); wg_commit();
      uint32_t any = 0;
#pragma unroll
      for (int i = 0; i < 16; i += 2) any |= mk[i] | mk[i + 1];
      tm = bar_wg_or(BAR_KV + wg, (any & 0x7FFF7FFFu) != 0) ? 0x1Fu : slow_heads;
      qkv_epilogue(qk, qa, dX, mk_desc(sb + SM_WV, 6144, 512, 2), k_dst);
    }
    bar_sync_n(BAR_AUX + wg, 128);
    if (warp == 0 && elect_one()) {
      const int nxt = lds32(gl + 4);
      if (nxt >= 0) { load_x(tm_x, tm_xq, nxt, wg); prefetch_l2(mb + mask_off(nxt), 8192); }
    }
    __syncwarp();
    auto head = [&](float (&sc)[32], uint32_t (&p)[16], bool tmax) {
      if (tmax) {
        if (tm & 16) {
#pragma unroll
          for (int i = 0; i < 16; i++) {
            sc[2 * i] = fmaf(bf_lo(mk[i]), LOG2E, sc[2 * i]); sc[2 * i + 1] = fmaf(bf_hi(mk[i]), LOG2E, sc[2 * i + 1]);
          }
        }
        softmax_true_max(sc, p);
      } else {
        softmax_fast(sc, p);
      }
    };
#pragma unroll
    for (int i = 0; i < 24; i++) of[i] = 0;
#pragma unroll 1
    for (int hp = 0; hp < 2; hp++) {
      float sA[32], sB[32], oA[16], oB[16]; uint32_t p[16];
      const uint32_t po = hp * 7 * 64;
      wg_fence();
      issue_s<0>(sA, qa, dK + po);
      issue_s<1>(sB, qa, dK + po); wg_commit();
      load_eb(p, sb + SM_EB + t16 + hp * 16384);
      wg_wait<0>(); fence_regs(sA); fence_regs(sB);
#pragma unroll
      for (int i = 0; i < 12; i++) { qa[i] = qa[i + 12]; of[i] = of[i + 12]; }
      head(sA, p, (tm >> (2 * hp)) & 1);
      wg_fence(); issue_pv<0>(oA, p, dV + po); wg_commit();
      uint32_t p2[16];
      load_eb(p2, sb + SM_EB + t16 + hp * 16384 + 8192);
      head(sB, p2, (tm >> (2 * hp + 1)) & 1);
      wg_fence(); issue_pv<1>(oB, p2, dV + po); wg_commit();
      wg_wait<1>(); fence_regs(oA);
      norm_o<0>(oA, of + 12);
      wg_wait<0>(); fence_regs(oB);
      norm_o<1>(oB, of + 18);
    }
    float y[48], var[4]; uint32_t yb[24];
    issue_out(y, of, mk_desc(sb + SM_WO, 128, 1536, 0));
    ln_head(y, yb, var, dV + 3 * 64);
    wg_wait<0>();
    ln_tail(yb, var, out_ptr(out, win, warp, t16));
  }
}

__global__ void __launch_bounds__(384, 1)
swin_kernel(const __nv_bfloat16* __restrict__ logit_scale, const __nv_bfloat16* __restrict__ w1, const __nv_bfloat16* __restrict__ w2,
            const __nv_bfloat16* __restrict__ coords, const int* __restrict__ rel_idx, const __nv_bfloat16* __restrict__ wo,
            const __nv_bfloat16* __restrict__ mask, __nv_bfloat16* __restrict__ out,
            const __grid_constant__ CUtensorMap tm_wqk, const __grid_constant__ CUtensorMap tm_x,
            const __grid_constant__ CUtensorMap tm_wv, const __grid_constant__ CUtensorMap tm_xq) {
  extern __shared__ __align__(1024) uint8_t smem[];
  const int tid = threadIdx.x, lane = tid & 31;
  const int warp = __shfl_sync(0xffffffffu, (tid >> 5) & 3, 0), wg = __shfl_sync(0xffffffffu, tid >> 7, 0);
  const int G = gridDim.x;
  auto first_window = [&](int g) { const int i = blockIdx.x + g * G, iy = (i * 2789) >> 17; return iy << 8 | (i - iy * 47); };
  if (tid < 32) {
    if (elect_one()) {
      mbar_init(mbar + MB_WQK, 1); mbar_init(mbar + MB_X, 1);
      fence_async();
      mbar_expect(mbar + MB_WQK, 3 * 12288);
      tma3(sb + SM_W, &tm_wqk, mbar + MB_WQK, 0, 0, 0);
      load_x_interior(&tm_x, first_window(0), 0);
#pragma unroll
      for (int i = 2; i < 13; i++) mbar_init(mbar + 8 * i, ((i >= 4 && i < 7) || i >= 9) ? 4 : 1);
      mbar_init(mbar + MB_RDY, 8); mbar_init(mbar + MB_WOC, 4);
      fence_async();
      mbar_expect(mbar + MB_WV, 3 * 6144);
      tma3(sb + SM_WV, &tm_wv, mbar + MB_WV, 0, 0, 0);
      mbar_expect(mbar + MB_WO, 18432);
      bulk_g2s(sb + SM_WOR, wo, 18432, mbar + MB_WO);
      load_x_interior(&tm_x, first_window(1), 1);
      load_x_interior(&tm_x, first_window(2), 2);
    }
    __syncwarp();
  }
  const char* mb = reinterpret_cast<const char*>(mask);
  TL(0); TG(14);

  const bool g132 = G == 132;
  uint32_t cw = 0;
  uint4 rid[4];
  if (tid >= 128) {
    const int i = tid - 128;
    if (i < 225) cw = __ldg(reinterpret_cast<const uint32_t*>(coords) + i);
  } else if (tid >= 64 && tid < 96) {
    if (lane < 12) *reinterpret_cast<uint4*>(smem + SM_PAR + 16 * lane) =
        ldg128_stream(lane < 4 ? reinterpret_cast<const uint4*>(w1) + lane : reinterpret_cast<const uint4*>(w2) + (lane - 4));
    __syncwarp();
    bar_arrive_n(BAR_PAR, 288);
  }
  const uint2 lsw = __ldg(reinterpret_cast<const uint2*>(logit_scale));
  if (tid >= 128) {
#pragma unroll
    for (int c = 0; c < 4; c++) rid[c] = ldg128_stream(reinterpret_cast<const int4*>(rel_idx) + c * 256 + (tid - 128));
  }
  if ((uint32_t)__cvta_generic_to_shared(smem) != sb) __trap();
  auto const_tiles = [&]() {
    const int i = tid & 127;
    uint8_t* vt = smem + SM_WG + wg * WG_SZ + WG_V + (i < 64 ? 3 : 10) * 1024 + (i & 63) * 16;
    *reinterpret_cast<uint4*>(vt) = make_uint4(0x3F803F80u, 0x3F803F80u, 0x3F803F80u, 0x3F803F80u);
    *reinterpret_cast<uint4*>(vt - (WG_V - WG_K)) = make_uint4(0u, 0u, 0u, 0u);
  };
  if (wg != 2) const_tiles();
  float tau[4]; uint32_t slow_heads = 0;
  auto head_scales = [&]() {
    const float ls[4] = {bf_lo(lsw.x), bf_hi(lsw.x), bf_lo(lsw.y), bf_hi(lsw.y)};
#pragma unroll
    for (int h = 0; h < 4; h++) {
      float c;
      asm("max.NaN.f32 %0, %1, 0fC2C80000;" : "=f"(c) : "f"(ls[h]));
      asm("min.NaN.f32 %0, %0, 0f40930000;" : "+f"(c));
      tau[h] = rbf(ex2(c * LOG2E)) * LOG2E;
      if (!(tau[h] <= TAU_FAST_MAX)) slow_heads |= 1u << h;
    }
    slow_heads = __shfl_sync(0xffffffffu, slow_heads, 0);
  };
  if (wg == 0) head_scales();
  if (wg == 0 && warp == 1) {
    const int eg = lane / NENT, ei = lane - eg * NENT, sl = blockIdx.x + eg * G + ei * 3 * G;
    const int w = (sl < NWIN && eg < 3) ? slot_window(sl, g132) : -1;
    const bool queues = w >= 0 && (w >> 8) != NWX - 1 && (w & 255) != NWX - 1;
    const uint32_t qmask = __ballot_sync(0xffffffffu, queues);
    const int key = (eg + 3 * ei + BORDER_EXTRA * __popc((~qmask >> (eg * NENT)) & ((1u << ei) - 1))) * 3 + eg;
    const uint32_t k0 = __reduce_or_sync(0xffffffffu, queues && key < 32 ? 1u << key : 0u), k1 = __reduce_or_sync(0xffffffffu, queues && (key >> 5) == 1 ? 1u << (key & 31) : 0u);
    const uint32_t k2 = __reduce_or_sync(0xffffffffu, queues && (key >> 5) == 2 ? 1u << (key & 31) : 0u), k3 = __reduce_or_sync(0xffffffffu, queues && (key >> 5) == 3 ? 1u << (key & 31) : 0u);
    const uint32_t lo = (1u << (key & 31)) - 1;
    const int kw = key >> 5;
    const int ticket = __popc(kw > 0 ? k0 : k0 & lo) + (kw >= 1 ? __popc(kw > 1 ? k1 : k1 & lo) : 0) + (kw >= 2 ? __popc(kw > 2 ? k2 : k2 & lo) : 0) + (kw >= 3 ? __popc(k3 & lo) : 0);
    const int ent = w | (queues ? ticket : NO_TICKET) << 16;
    if (eg < 3) {
      *reinterpret_cast<int*>(smem + SM_WIN + lane * 4) = slow_heads ? -1 : ent;
      *reinterpret_cast<int*>(smem + SM_GEN + lane * 4) = slow_heads ? ent : -1;
    }
  }
  if (wg == 0 && warp == 3 && lane < 16) {
    const uint32_t v = (((lane >> 3) ^ lane) & 1) ? 0u : 0x3F803F80u;
    *reinterpret_cast<uint4*>(smem + SM_SEL + lane * 16) = make_uint4(v, v, v, v);
  }
  TL(3);
  if (wg == 0) {
    if (tid == 0) {
      *reinterpret_cast<float4*>(smem + SM_MISC) = make_float4(tau[0], tau[1], tau[2], tau[3]);
      *reinterpret_cast<uint32_t*>(smem + SM_SLOW) = slow_heads;
    }
    fence_async();
    bar_arrive_n(BAR_SETUP, 384);
    bar_sync_n(BAR_AUX, 128);
  } else {
    const int i = tid - 128;
    bar_sync_n(BAR_PAR, 288);
    TL(4);
    head_scales();

    if (i < 225) {
      const float c0 = bf_lo(cw), c1 = bf_hi(cw);
      float z[4] = {0.f, 0.f, 0.f, 0.f};
#pragma unroll
      for (int jj = 0; jj < 2; jj++) {
        const uint4 ua4 = lds128(sb + SM_PAR + 16 * jj), ub4 = lds128(sb + SM_PAR + 32 + 16 * jj);
        const uint32_t ua[4] = {ua4.x, ua4.y, ua4.z, ua4.w}, ub[4] = {ub4.x, ub4.y, ub4.z, ub4.w};
#pragma unroll
        for (int j = 0; j < 4; j++) {
          const uint4 wb = lds128(sb + SM_PAR + 64 + 64 * jj + 16 * j);
          const uint32_t hp = pack_bf16(fmaf(c1, bf_lo(ub[j]), c0 * bf_lo(ua[j])), fmaf(c1, bf_hi(ub[j]), c0 * bf_hi(ua[j])));
          float h0 = bf_lo(hp), h1 = bf_hi(hp);
          h0 = h0 > 0.f ? h0 : h0 * 0.f; h1 = h1 > 0.f ? h1 : h1 * 0.f;
          z[0] = fmaf(h0, bf_lo(wb.x), z[0]); z[1] = fmaf(h0, bf_hi(wb.x), z[1]); z[2] = fmaf(h0, bf_lo(wb.y), z[2]); z[3] = fmaf(h0, bf_hi(wb.y), z[3]);
          z[0] = fmaf(h1, bf_lo(wb.z), z[0]); z[1] = fmaf(h1, bf_hi(wb.z), z[1]); z[2] = fmaf(h1, bf_lo(wb.w), z[2]); z[3] = fmaf(h1, bf_hi(wb.w), z[3]);
        }
      }
      float e[4];
#pragma unroll
      for (int q = 0; q < 4; q++) {
        const float sh = ((slow_heads >> q) & 1) ? 0.f : fminf(0.f, 25.f - 1.02f * tau[q]);
        e[q] = ex2(fmaf(16.f * LOG2E, rbf(rcp(1.f + ex2(-LOG2E * rbf(z[q])))), sh));
      }
      *reinterpret_cast<uint2*>(smem + SM_TAB + 8 * i) = make_uint2(pack_bf16(e[0], e[1]), pack_bf16(e[2], e[3]));
    }
    TL(5);
    bar_sync_n(BAR_SETUP, 384);
#pragma unroll
    for (int c = 0; c < 4; c++) asm volatile("" : "+r"(rid[c].x), "+r"(rid[c].y), "+r"(rid[c].z), "+r"(rid[c].w));
    {
      const int y = (i & 15) >> 1, xh = i & 1, j = 2 * xh + (y >> 2);
      const int X = (i >> 4) & 7, Yl = (i >> 7) & 1;
      uint8_t* dst = smem + SM_EB + j * 2048 + ((X >> 2) * 64 + (Yl * 4 + (X & 3)) * 4 + 2 * (y & 1)) * 16 + ((y >> 1) & 1) * 8;
      uint2 e[16];
#pragma unroll
      for (int c = 0; c < 4; c++) {
        const uint32_t id[4] = {xh ? rid[c].z : rid[c].x, xh ? rid[c].w : rid[c].y, xh ? rid[c].x : rid[c].z, xh ? rid[c].y : rid[c].w};
#pragma unroll
        for (int q = 0; q < 4; q++) e[4 * c + q] = *reinterpret_cast<const uint2*>(smem + SM_TAB + 8 * id[q]);
      }
#pragma unroll
      for (int c = 0; c < 4; c++) {
        const uint2 a0 = e[4 * c], a1 = e[4 * c + 1], b0 = e[4 * c + 2], b1 = e[4 * c + 3];
        uint8_t* d0 = dst + (c >> 1) * 512 + (c & 1) * 4 + xh * 16;
        uint8_t* d1 = dst + (c >> 1) * 512 + (c & 1) * 4 + (xh ^ 1) * 16;
        *reinterpret_cast<uint32_t*>(d0)         = __byte_perm(a0.x, a1.x, 0x5410); *reinterpret_cast<uint32_t*>(d1)         = __byte_perm(b0.x, b1.x, 0x5410);
        *reinterpret_cast<uint32_t*>(d0 + 8192)  = __byte_perm(a0.x, a1.x, 0x7632); *reinterpret_cast<uint32_t*>(d1 + 8192)  = __byte_perm(b0.x, b1.x, 0x7632);
        *reinterpret_cast<uint32_t*>(d0 + 16384) = __byte_perm(a0.y, a1.y, 0x5410); *reinterpret_cast<uint32_t*>(d1 + 16384) = __byte_perm(b0.y, b1.y, 0x5410);
        *reinterpret_cast<uint32_t*>(d0 + 24576) = __byte_perm(a0.y, a1.y, 0x7632); *reinterpret_cast<uint32_t*>(d1 + 24576) = __byte_perm(b0.y, b1.y, 0x7632);
      }
    }
    TL(6);
    __syncwarp();
    fence_async();
    if (elect_one()) mbar_arrive(mbar + MB_RDY);
    __syncwarp();
    bar_sync_n(BAR_TAB, 256);
    if (wg == 2) {
      mbar_wait(mbar + MB_WO, 0);
      uint4 v[9];
#pragma unroll
      for (int c = 0; c < 9; c++) v[c] = lds128(sb + SM_WOR + ((c / 3) * 32 + ((tid & 127) >> 2)) * 192 + (c % 3) * 64 + (lane & 3) * 16);
      bar_sync_n(BAR_AUX + 2, 128);
      const_tiles();
#pragma unroll
      for (int r = 0; r < 3; r++) {
        float sum = 0.f;
#pragma unroll
        for (int c = 3 * r; c < 3 * r + 3; c++)
          sum += (bf_lo(v[c].x) + bf_hi(v[c].x)) + (bf_lo(v[c].y) + bf_hi(v[c].y)) + (bf_lo(v[c].z) + bf_hi(v[c].z)) + (bf_lo(v[c].w) + bf_hi(v[c].w));
        sum += __shfl_xor_sync(0xffffffffu, sum, 1);
        sum += __shfl_xor_sync(0xffffffffu, sum, 2);
        const float mu = sum * (1.f / 96.f);
        auto cen = [&](uint32_t u) { return pack_bf16(bf_lo(u) - mu, bf_hi(u) - mu); };
        uint8_t* dst = smem + SM_WO + (r * 4 + warp) * 128 + lane * 4;
#pragma unroll
        for (int j = 0; j < 3; j++) {
          *reinterpret_cast<uint32_t*>(dst + (4 * j + 0) * 1536) = cen(v[3 * r + j].x);
          *reinterpret_cast<uint32_t*>(dst + (4 * j + 1) * 1536) = cen(v[3 * r + j].y);
          *reinterpret_cast<uint32_t*>(dst + (4 * j + 2) * 1536) = cen(v[3 * r + j].z);
          *reinterpret_cast<uint32_t*>(dst + (4 * j + 3) * 1536) = cen(v[3 * r + j].w);
        }
      }
      fence_async();
      __syncwarp();
      if (elect_one()) { mbar_arrive(mbar + MB_TURN); mbar_arrive(mbar + MB_WOC); }
      __syncwarp();
    }
  }
  TL(1);
  mbar_wait(mbar + MB_WQK, 0);
  uint32_t xpar = 0;

  uint32_t wl = sb + SM_WIN + wg * NENT * 4;
  int win = lds_uniform(wl), nxt = lds_uniform(wl + 4);
  if (win >= 0) {
    const uint32_t wgb = sb + SM_WG + wg * WG_SZ, bar_x = mbar + MB_X + 8 * wg;
    const uint32_t t16 = (tid & 127) * 16;
    const uint32_t k_dst = wgb + WG_K + (tid & 16) * 448 + warp * 256 + (tid & 15) * 16;
    const uint32_t eb_base = sb + SM_EB + t16;
    float qk[96];
    mbar_wait(bar_x, 0);
    TL(2);
    wg_fence();
    issue_qk(qk, mk_desc(WG_X, 16, 512, 2) + (wgb >> 4), mk_desc(sb + SM_W, 12288, 1024, 1)); wg_commit();
    bool first = true;
    if (t16 == 0) prefetch_l2(mb + mask_off(win), 8192);
    __syncwarp();
    mbar_wait(mbar + MB_WV, 0);
    TL(8);
    while (true) {
      const int nxt2 = lds_uniform(wl + 8);
      const int tk = win >> 16;
      const bool more = nxt >= 0;
      const uint32_t z0 = wl >> 20, zw = z0 + (wgb >> 4);
      const uint64_t dX = opaque(mk_desc(WG_X, 16, 512, 2) + zw);
      TL(0);
      uint32_t qa[24];
      qkv_epilogue(qk, qa, dX, opaque(mk_desc(sb + SM_WV, 6144, 512, 2) + z0), k_dst);
      TL(5);
      if (__builtin_expect(first, 0)) {
        mbar_wait(mbar + MB_RDY, 0);
        first = false;
      }
      uint32_t pA[16], pB[16];
      load_eb(pA, eb_base);
      load_eb(pB, eb_base + 8192);
      bar_sync_n(BAR_KV + wg, 128);
      const bool masked = tk == NO_TICKET;
      TL(6);
      const uint64_t dK = opaque(mk_desc(WG_K, 1024, 128, 0) + zw), dV = opaque(mk_desc(WG_V, 128, 1024, 0) + zw);
      auto prefetch_next = [&]() {
        if (warp == 0 && more) {
          if (elect_one()) {
            load_x(&tm_x, &tm_xq, nxt, wg);
            prefetch_l2(mb + mask_off(nxt), 8192);
          }
          __syncwarp();
        }
      };
      auto redo = [&](int w) {
        if (elect_one()) {
          uint32_t gl = sb + SM_GEN + wg * NENT * 4, old;
          do {
            asm volatile("atom.shared.cas.b32 %0, [%1], %2, %3;" : "=r"(old) : "r"(gl), "r"(-1), "r"(w) : "memory");
            gl += 4;
          } while (old != 0xFFFFFFFFu && old != (uint32_t)w);
        }
        __syncwarp();
      };
      auto wait_turn = [&]() { mbar_wait(mbar + MB_TURN + (tk & 3) * 8, (tk >> 2) & 1); };
      auto pass_turn = [&](uint32_t after = 0) {
        asm volatile("{\n.reg .pred p, q;\nelect.sync _|p, 0xffffffff;\nsetp.ne.and.s32 q, %1, 255, p;\nsetp.ne.and.s32 q, %2, -1, q;\n"
                     "@q mbarrier.arrive.shared::cta.b64 _, [%0];\n}\n"
                     :: "r"(mbar + MB_TURN + ((tk + 1) & 3) * 8), "r"(tk), "r"(after) : "memory");
      };
      auto next_qk = [&]() { issue_qk(qk, dX, opaque(mk_desc(sb + SM_W, 12288, 1024, 1) + z0)); wg_commit(); };
      auto tiles_ready = [&]() {
        if (elect_one()) mbar_arrive(bar_x + (MB_KV - MB_X));
        __syncwarp();
        const uint32_t par = (wl >> 2) & 1;
        mbar_wait(bar_x, par ^ 1);
        mbar_wait(bar_x + (MB_KV - MB_X), par);
      };
      uint32_t of[24];
      uint4 mw[4];
      {
        float sA[32], sB[32], oA[16], oB[16], oC[16], oD[16];
        uint32_t pC[16], pD[16];
        uint32_t eb_hi = sb + SM_EB + 16384;
        uint4 late[2];
        if (__builtin_expect(masked, 0)) {
          uint32_t mk[16];
          load_mask_frag(mk, mb + mask_off(win), t16);
          if (t16 == 0 && more)
            asm volatile("cp.async.bulk.prefetch.tensor.5d.L2.global.tile [%0, {%1, %1, %2, %3, %1}];"
                         :: "l"(&tm_x), "r"(0), "r"(((nxt >> 8) & 255) * 8 + 4), "r"((nxt & 255) * 2 + 1) : "memory");
          __syncwarp();
          uint4 e[8];
#pragma unroll
          for (int j = 0; j < 8; j++) e[j] = lds128(eb_base + 16384 + j * 2048);
          if (__any_sync(0xffffffffu, mask_unsafe(mk))) redo(win);
#pragma unroll
          for (int i = 0; i < 16; i++) {
            mk[i] = pack_bf16(ex2(bf_lo(mk[i]) * LOG2E), ex2(bf_hi(mk[i]) * LOG2E));
            pA[i] = hmul2(pA[i], mk[i]); pB[i] = hmul2(pB[i], mk[i]);
          }
#pragma unroll
          for (int j = 0; j < 8; j++) {
            const int m = 4 * (j & 3);
            e[j] = make_uint4(hmul2(e[j].x, mk[m]), hmul2(e[j].y, mk[m + 1]), hmul2(e[j].z, mk[m + 2]), hmul2(e[j].w, mk[m + 3]));
            if (j < 6) sts128(wgb + WG_X + t16 + j * 2048, e[j]);
          }
          late[0] = e[6]; late[1] = e[7];
          eb_hi = wgb + WG_X;
        }
        wg_fence();
        issue_s<0>(sA, qa, dK);
        issue_s<1>(sB, qa, dK); wg_commit();
        if (__builtin_expect(!masked, 1)) {
          prefetch_next();
          wait_turn();
        } else {
          wg_wait<0>();
          bar_sync_n(BAR_AUX + wg, 128);
          sts128(wgb + WG_X + t16 + 6 * 2048, late[0]);
          sts128(wgb + WG_X + t16 + 7 * 2048, late[1]);
        }
        wg_wait<0>(); fence_regs(sA); fence_regs(sB);
        TL(7);
        softmax_fast(sA, pA);
        wg_fence();
        issue_s<2>(sA, qa, dK); wg_commit();
        issue_pv<0>(oA, pA, dV); wg_commit();
        TL(8);
        softmax_fast(sB, pB);
        load_eb(pC, eb_hi + t16);
        wg_wait<1>(); fence_regs(sA);
        wg_fence();
        issue_s<3>(sB, qa, dK); wg_commit();
        issue_pv<1>(oB, pB, dV); wg_commit();
        TL(9);
        softmax_fast(sA, pC);
        load_eb(pD, eb_hi + t16 + 8192);
        wg_wait<1>(); fence_regs(sB); fence_regs(oA);
        wg_fence();
        issue_pv<2>(oC, pC, dV); wg_commit();
        TL(10);
        norm_o<0>(oA, of);
        softmax_fast(sB, pD);
        pass_turn(pD[TPOS]);
        wg_fence();
        issue_pv<3>(oD, pD, dV); wg_commit();
        {
          const char* src = mb + (mask_off(win) + (warp & 1) * 3584 - (warp >> 1) * 512 + (t16 ^ (pD[MPOS] >> 31 << 4)));
#pragma unroll
          for (int i = 0; i < 4; i++) mw[i] = ldg128_stream(src + i * 1024);
        }
        wg_wait<1>(); fence_regs(oB); fence_regs(oC);
        norm_o<1>(oB, of + 6);
        norm_o<0>(oC, of + 12);
        wg_wait<0>(); fence_regs(oD);
        norm_o<1>(oD, of + 18);
      }
      TL(11);
      float y[48], var[4]; uint32_t yb[24];
      issue_out(y, of, opaque(mk_desc(sb + SM_WO, 128, 1536, 0) + z0));
      if (__builtin_expect(masked, 0)) {
        if (t16 >= 1024) asm volatile("st.shared.v4.u32 [%0], {%1,%1,%1,%1};" :: "r"(wgb + WG_K + 2048 + t16), "r"(0) : "memory");
        fence_async();
        bar_sync_n(BAR_AUX + wg, 128);
        prefetch_next();
      }
      char* const optr = out_ptr(out, win, warp, t16);
      auto verify = [&](uint32_t seed) {
        uint32_t r = seed & 0x80008000u;
#pragma unroll
        for (int i = 0; i < 4; i++) {
          asm("lop3.b32 %0, %0, %1, %2, 0xFE;" : "+r"(r) : "r"(mw[i].x), "r"(mw[i].y));
          asm("lop3.b32 %0, %0, %1, %2, 0xFE;" : "+r"(r) : "r"(mw[i].z), "r"(mw[i].w));
        }
        if (__builtin_expect(__any_sync(0xffffffffu, (r & 0x7FFF7FFFu) != 0u) && !masked, 0)) redo(win);
      };
      if (!more) { ln_head(y, yb, var, dV + 3 * 64); wg_wait<0>(); verify(ln_tail(yb, var, optr)); TL(14); break; }
      tiles_ready();
      ln_head(y, yb, var, dV + 3 * 64);
      TL(12);
      next_qk();
      wg_wait<1>();
      TL(13);
      verify(ln_tail(yb, var, optr));
      TL(14);
      wl += 4;
      win = nxt; nxt = nxt2;
    }
    xpar = ((wl >> 2) & 1) ^ 1;
    bar_sync_n(BAR_AUX + wg, 128);
    if (warp == 0 && elect_one()) {
      const int w = lds32(sb + SM_GEN + wg * NENT * 4);
      if (w >= 0) load_x(&tm_x, &tm_xq, w, wg);
    }
    __syncwarp();
  }
  general_windows(&tm_x, &tm_xq, mb, out, xpar);
  TG(15);
}

typedef CUresult (*EncodeFn)(CUtensorMap*, CUtensorMapDataType, cuuint32_t, void*, const cuuint64_t*, const cuuint64_t*,
                             const cuuint32_t*, const cuuint32_t*, CUtensorMapInterleave, CUtensorMapSwizzle,
                             CUtensorMapL2promotion, CUtensorMapFloatOOBfill);

}

extern "C" void kernel_launch(void* const* d_in, const int* in_sizes, int n_in, void* d_out, int out_size) {
  static int sms = 0;
  static EncodeFn encode = nullptr;
  if (sms == 0) {
    int dev = 0;
    cudaGetDevice(&dev);
    cudaDeviceGetAttribute(&sms, cudaDevAttrMultiProcessorCount, dev);
    if (sms < 96) sms = 96;
    cudaFuncSetAttribute(swin_kernel, cudaFuncAttributeMaxDynamicSharedMemorySize, SM_TOTAL);
    cudaDriverEntryPointQueryResult qr;
    void* fn = nullptr;
    cudaGetDriverEntryPoint("cuTensorMapEncodeTiled", &fn, cudaEnableDefault, &qr);
    encode = (EncodeFn)fn;
  }
  CUtensorMap tm_x, tm_xq, tm_wqk, tm_wv;
  {
    cuuint64_t dims[5] = {32, 4, IMG, IMG / 4, 3};
    cuuint64_t strides[4] = {PIXB, ROWB, 4 * PIXB, 64};
    cuuint32_t es[5] = {1, 1, 1, 1, 1};
    cuuint32_t box[5] = {32, 4, 8, 2, 3}, boxq[5] = {32, 4, 4, 1, 1};
    encode(&tm_x, CU_TENSOR_MAP_DATA_TYPE_BFLOAT16, 5, d_in[0], dims, strides, box, es, CU_TENSOR_MAP_INTERLEAVE_NONE,
           CU_TENSOR_MAP_SWIZZLE_64B, CU_TENSOR_MAP_L2_PROMOTION_L2_128B, CU_TENSOR_MAP_FLOAT_OOB_FILL_NONE);
    encode(&tm_xq, CU_TENSOR_MAP_DATA_TYPE_BFLOAT16, 5, d_in[0], dims, strides, boxq, es, CU_TENSOR_MAP_INTERLEAVE_NONE,
           CU_TENSOR_MAP_SWIZZLE_64B, CU_TENSOR_MAP_L2_PROMOTION_L2_128B, CU_TENSOR_MAP_FLOAT_OOB_FILL_NONE);
    cuuint64_t qd[3] = {64, 96, 3}, qs[2] = {576, 128}, vd[3] = {32, 96, 3}, vs[2] = {576, 64};
    cuuint32_t qb[3] = {64, 96, 3}, vb[3] = {32, 96, 3};
    encode(&tm_wqk, CU_TENSOR_MAP_DATA_TYPE_BFLOAT16, 3, d_in[1], qd, qs, qb, es, CU_TENSOR_MAP_INTERLEAVE_NONE,
           CU_TENSOR_MAP_SWIZZLE_128B, CU_TENSOR_MAP_L2_PROMOTION_L2_256B, CU_TENSOR_MAP_FLOAT_OOB_FILL_NONE);
    encode(&tm_wv, CU_TENSOR_MAP_DATA_TYPE_BFLOAT16, 3, (char*)d_in[1] + 384, vd, vs, vb, es, CU_TENSOR_MAP_INTERLEAVE_NONE,
           CU_TENSOR_MAP_SWIZZLE_64B, CU_TENSOR_MAP_L2_PROMOTION_L2_256B, CU_TENSOR_MAP_FLOAT_OOB_FILL_NONE);
  }
  swin_kernel<<<sms, 384, SM_TOTAL>>>(
      (const __nv_bfloat16*)d_in[3], (const __nv_bfloat16*)d_in[4], (const __nv_bfloat16*)d_in[5], (const __nv_bfloat16*)d_in[6],
      (const int*)d_in[7], (const __nv_bfloat16*)d_in[2], (const __nv_bfloat16*)d_in[8], (__nv_bfloat16*)d_out,
      tm_wqk, tm_x, tm_wv, tm_xq);
}
```

```cpp
#include <cuda_runtime.h>
#include <cuda.h>
#include <cuda_bf16.h>
#include <stdint.h>

namespace {

constexpr int IMG   = 384;
constexpr int NWX   = 48;
constexpr int NWIN  = NWX * NWX;
constexpr int PIXB  = 192;
constexpr int ROWB  = IMG * PIXB;
constexpr float LOG2E = 1.4426950408889634f;

constexpr int SM_W    = 0;
constexpr int SM_WV   = 3 * 12288;
constexpr int SM_WO   = SM_W + 9 * 6144;
constexpr int SM_EB   = SM_WO + 12 * 1536;
constexpr int SM_WG   = SM_EB + 32768;
constexpr int WG_X    = 0;
constexpr int WG_K    = 12288;
constexpr int WG_V    = WG_K + 14336;
constexpr int WG_SZ   = WG_V + 14336;
constexpr int SM_TAB  = SM_WG + WG_SZ + WG_V + 4096;
constexpr int SM_WOR  = SM_WG + 2 * WG_SZ + WG_K;
constexpr int SM_SEL  = SM_WG + 3 * WG_SZ;
constexpr int SM_MISC = SM_SEL + 256;
constexpr int SM_BAR  = SM_MISC + 16;
constexpr int SM_REQ  = SM_BAR + 104;
constexpr int SM_PAR  = SM_BAR + 160;
constexpr int NENT    = 10;
constexpr int SM_WIN  = SM_PAR + 192;
constexpr int SM_GEN  = SM_WIN + 3 * NENT * 4;
constexpr int SM_TOTAL = SM_GEN + 3 * NENT * 4;
static_assert((SM_WIN & 7) == 0 && (NENT & 1) == 0, "list parity");

template <int SD> __device__ __forceinline__ void wgmma_ss_n192_t1(float (&d)[96], uint64_t da, uint64_t db) {
  if constexpr (SD == 1) {
    asm volatile("{\n.reg .pred p;\nsetp.ne.b32 p, 1, 0;\n"
      "wgmma.mma_async.sync.aligned.m64n192k16.f32.bf16.bf16 {%0, %1, %2, %3, %4, %5, %6, %7, %8, %9, %10, %11, %12, %13, %14, %15, %16, %17, %18, %19, %20, %21, %22, %23, %24, %25, %26, %27, %28, %29, %30, %31, %32, %33, %34, %35, %36, %37, %38, %39, %40, %41, %42, %43, %44, %45, %46, %47, %48, %49, %50, %51, %52, %53, %54, %55, %56, %57, %58, %59, %60, %61, %62, %63, %64, %65, %66, %67, %68, %69, %70, %71, %72, %73, %74, %75, %76, %77, %78, %79, %80, %81, %82, %83, %84, %85, %86, %87, %88, %89, %90, %91, %92, %93, %94, %95}, %96, %97, p, 1, 1, 0, 1;\n}\n"
      : "+f"(d[0]), "+f"(d[1]), "+f"(d[2]), "+f"(d[3]), "+f"(d[4]), "+f"(d[5]), "+f"(d[6]), "+f"(d[7]), "+f"(d[8]), "+f"(d[9]), "+f"(d[10]), "+f"(d[11]), "+f"(d[12]), "+f"(d[13]), "+f"(d[14]), "+f"(d[15]), "+f"(d[16]), "+f"(d[17]), "+f"(d[18]), "+f"(d[19]), "+f"(d[20]), "+f"(d[21]), "+f"(d[22]), "+f"(d[23]), "+f"(d[24]), "+f"(d[25]), "+f"(d[26]), "+f"(d[27]), "+f"(d[28]), "+f"(d[29]), "+f"(d[30]), "+f"(d[31]), "+f"(d[32]), "+f"(d[33]), "+f"(d[34]), "+f"(d[35]), "+f"(d[36]), "+f"(d[37]), "+f"(d[38]), "+f"(d[39]), "+f"(d[40]), "+f"(d[41]), "+f"(d[42]), "+f"(d[43]), "+f"(d[44]), "+f"(d[45]), "+f"(d[46]), "+f"(d[47]), "+f"(d[48]), "+f"(d[49]), "+f"(d[50]), "+f"(d[51]), "+f"(d[52]), "+f"(d[53]), "+f"(d[54]), "+f"(d[55]), "+f"(d[56]), "+f"(d[57]), "+f"(d[58]), "+f"(d[59]), "+f"(d[60]), "+f"(d[61]), "+f"(d[62]), "+f"(d[63]), "+f"(d[64]), "+f"(d[65]), "+f"(d[66]), "+f"(d[67]), "+f"(d[68]), "+f"(d[69]), "+f"(d[70]), "+f"(d[71]), "+f"(d[72]), "+f"(d[73]), "+f"(d[74]), "+f"(d[75]), "+f"(d[76]), "+f"(d[77]), "+f"(d[78]), "+f"(d[79]), "+f"(d[80]), "+f"(d[81]), "+f"(d[82]), "+f"(d[83]), "+f"(d[84]), "+f"(d[85]), "+f"(d[86]), "+f"(d[87]), "+f"(d[88]), "+f"(d[89]), "+f"(d[90]), "+f"(d[91]), "+f"(d[92]), "+f"(d[93]), "+f"(d[94]), "+f"(d[95])
      : "l"(da), "l"(db));
  } else if constexpr (SD == 2) {
    asm volatile("{\n.reg .pred p;\nsetp.ne.b32 p, 0, 0;\n"
      "wgmma.mma_async.sync.aligned.m64n192k16.f32.bf16.bf16 {%0, %1, %2, %3, %4, %5, %6, %7, %8, %9, %10, %11, %12, %13, %14, %15, %16, %17, %18, %19, %20, %21, %22, %23, %24, %25, %26, %27, %28, %29, %30, %31, %32, %33, %34, %35, %36, %37, %38, %39, %40, %41, %42, %43, %44, %45, %46, %47, %48, %49, %50, %51, %52, %53, %54, %55, %56, %57, %58, %59, %60, %61, %62, %63, %64, %65, %66, %67, %68, %69, %70, %71, %72, %73, %74, %75, %76, %77, %78, %79, %80, %81, %82, %83, %84, %85, %86, %87, %88, %89, %90, %91, %92, %93, %94, %95}, %96, %97, p, 1, 1, 0, 1;\n}\n"
      : "+f"(d[0]), "+f"(d[1]), "+f"(d[2]), "+f"(d[3]), "+f"(d[4]), "+f"(d[5]), "+f"(d[6]), "+f"(d[7]), "+f"(d[8]), "+f"(d[9]), "+f"(d[10]), "+f"(d[11]), "+f"(d[12]), "+f"(d[13]), "+f"(d[14]), "+f"(d[15]), "+f"(d[16]), "+f"(d[17]), "+f"(d[18]), "+f"(d[19]), "+f"(d[20]), "+f"(d[21]), "+f"(d[22]), "+f"(d[23]), "+f"(d[24]), "+f"(d[25]), "+f"(d[26]), "+f"(d[27]), "+f"(d[28]), "+f"(d[29]), "+f"(d[30]), "+f"(d[31]), "+f"(d[32]), "+f"(d[33]), "+f"(d[34]), "+f"(d[35]), "+f"(d[36]), "+f"(d[37]), "+f"(d[38]), "+f"(d[39]), "+f"(d[40]), "+f"(d[41]), "+f"(d[42]), "+f"(d[43]), "+f"(d[44]), "+f"(d[45]), "+f"(d[46]), "+f"(d[47]), "+f"(d[48]), "+f"(d[49]), "+f"(d[50]), "+f"(d[51]), "+f"(d[52]), "+f"(d[53]), "+f"(d[54]), "+f"(d[55]), "+f"(d[56]), "+f"(d[57]), "+f"(d[58]), "+f"(d[59]), "+f"(d[60]), "+f"(d[61]), "+f"(d[62]), "+f"(d[63]), "+f"(d[64]), "+f"(d[65]), "+f"(d[66]), "+f"(d[67]), "+f"(d[68]), "+f"(d[69]), "+f"(d[70]), "+f"(d[71]), "+f"(d[72]), "+f"(d[73]), "+f"(d[74]), "+f"(d[75]), "+f"(d[76]), "+f"(d[77]), "+f"(d[78]), "+f"(d[79]), "+f"(d[80]), "+f"(d[81]), "+f"(d[82]), "+f"(d[83]), "+f"(d[84]), "+f"(d[85]), "+f"(d[86]), "+f"(d[87]), "+f"(d[88]), "+f"(d[89]), "+f"(d[90]), "+f"(d[91]), "+f"(d[92]), "+f"(d[93]), "+f"(d[94]), "+f"(d[95])
      : "l"(da), "l"(db));
  } else {
    asm volatile("{\n.reg .pred p;\nsetp.ne.b32 p, 0, 0;\n"
      "wgmma.mma_async.sync.aligned.m64n192k16.f32.bf16.bf16 {%0, %1, %2, %3, %4, %5, %6, %7, %8, %9, %10, %11, %12, %13, %14, %15, %16, %17, %18, %19, %20, %21, %22, %23, %24, %25, %26, %27, %28, %29, %30, %31, %32, %33, %34, %35, %36, %37, %38, %39, %40, %41, %42, %43, %44, %45, %46, %47, %48, %49, %50, %51, %52, %53, %54, %55, %56, %57, %58, %59, %60, %61, %62, %63, %64, %65, %66, %67, %68, %69, %70, %71, %72, %73, %74, %75, %76, %77, %78, %79, %80, %81, %82, %83, %84, %85, %86, %87, %88, %89, %90, %91, %92, %93, %94, %95}, %96, %97, p, 1, 1, 0, 1;\n}\n"
      : "=f"(d[0]), "=f"(d[1]), "=f"(d[2]), "=f"(d[3]), "=f"(d[4]), "=f"(d[5]), "=f"(d[6]), "=f"(d[7]), "=f"(d[8]), "=f"(d[9]), "=f"(d[10]), "=f"(d[11]), "=f"(d[12]), "=f"(d[13]), "=f"(d[14]), "=f"(d[15]), "=f"(d[16]), "=f"(d[17]), "=f"(d[18]), "=f"(d[19]), "=f"(d[20]), "=f"(d[21]), "=f"(d[22]), "=f"(d[23]), "=f"(d[24]), "=f"(d[25]), "=f"(d[26]), "=f"(d[27]), "=f"(d[28]), "=f"(d[29]), "=f"(d[30]), "=f"(d[31]), "=f"(d[32]), "=f"(d[33]), "=f"(d[34]), "=f"(d[35]), "=f"(d[36]), "=f"(d[37]), "=f"(d[38]), "=f"(d[39]), "=f"(d[40]), "=f"(d[41]), "=f"(d[42]), "=f"(d[43]), "=f"(d[44]), "=f"(d[45]), "=f"(d[46]), "=f"(d[47]), "=f"(d[48]), "=f"(d[49]), "=f"(d[50]), "=f"(d[51]), "=f"(d[52]), "=f"(d[53]), "=f"(d[54]), "=f"(d[55]), "=f"(d[56]), "=f"(d[57]), "=f"(d[58]), "=f"(d[59]), "=f"(d[60]), "=f"(d[61]), "=f"(d[62]), "=f"(d[63]), "=f"(d[64]), "=f"(d[65]), "=f"(d[66]), "=f"(d[67]), "=f"(d[68]), "=f"(d[69]), "=f"(d[70]), "=f"(d[71]), "=f"(d[72]), "=f"(d[73]), "=f"(d[74]), "=f"(d[75]), "=f"(d[76]), "=f"(d[77]), "=f"(d[78]), "=f"(d[79]), "=f"(d[80]), "=f"(d[81]), "=f"(d[82]), "=f"(d[83]), "=f"(d[84]), "=f"(d[85]), "=f"(d[86]), "=f"(d[87]), "=f"(d[88]), "=f"(d[89]), "=f"(d[90]), "=f"(d[91]), "=f"(d[92]), "=f"(d[93]), "=f"(d[94]), "=f"(d[95])
      : "l"(da), "l"(db));
  }
}
template <int SD> __device__ __forceinline__ void wgmma_ss_n96_t1(float (&d)[48], uint64_t da, uint64_t db) {
  if constexpr (SD == 1) {
    asm volatile("{\n.reg .pred p;\nsetp.ne.b32 p, 1, 0;\n"
      "wgmma.mma_async.sync.aligned.m64n96k16.f32.bf16.bf16 {%0, %1, %2, %3, %4, %5, %6, %7, %8, %9, %10, %11, %12, %13, %14, %15, %16, %17, %18, %19, %20, %21, %22, %23, %24, %25, %26, %27, %28, %29, %30, %31, %32, %33, %34, %35, %36, %37, %38, %39, %40, %41, %42, %43, %44, %45, %46, %47}, %48, %49, p, 1, 1, 0, 1;\n}\n"
      : "+f"(d[0]), "+f"(d[1]), "+f"(d[2]), "+f"(d[3]), "+f"(d[4]), "+f"(d[5]), "+f"(d[6]), "+f"(d[7]), "+f"(d[8]), "+f"(d[9]), "+f"(d[10]), "+f"(d[11]), "+f"(d[12]), "+f"(d[13]), "+f"(d[14]), "+f"(d[15]), "+f"(d[16]), "+f"(d[17]), "+f"(d[18]), "+f"(d[19]), "+f"(d[20]), "+f"(d[21]), "+f"(d[22]), "+f"(d[23]), "+f"(d[24]), "+f"(d[25]), "+f"(d[26]), "+f"(d[27]), "+f"(d[28]), "+f"(d[29]), "+f"(d[30]), "+f"(d[31]), "+f"(d[32]), "+f"(d[33]), "+f"(d[34]), "+f"(d[35]), "+f"(d[36]), "+f"(d[37]), "+f"(d[38]), "+f"(d[39]), "+f"(d[40]), "+f"(d[41]), "+f"(d[42]), "+f"(d[43]), "+f"(d[44]), "+f"(d[45]), "+f"(d[46]), "+f"(d[47])
      : "l"(da), "l"(db));
  } else if constexpr (SD == 2) {
    asm volatile("{\n.reg .pred p;\nsetp.ne.b32 p, 0, 0;\n"
      "wgmma.mma_async.sync.aligned.m64n96k16.f32.bf16.bf16 {%0, %1, %2, %3, %4, %5, %6, %7, %8, %9, %10, %11, %12, %13, %14, %15, %16, %17, %18, %19, %20, %21, %22, %23, %24, %25, %26, %27, %28, %29, %30, %31, %32, %33, %34, %35, %36, %37, %38, %39, %40, %41, %42, %43, %44, %45, %46, %47}, %48, %49, p, 1, 1, 0, 1;\n}\n"
      : "+f"(d[0]), "+f"(d[1]), "+f"(d[2]), "+f"(d[3]), "+f"(d[4]), "+f"(d[5]), "+f"(d[6]), "+f"(d[7]), "+f"(d[8]), "+f"(d[9]), "+f"(d[10]), "+f"(d[11]), "+f"(d[12]), "+f"(d[13]), "+f"(d[14]), "+f"(d[15]), "+f"(d[16]), "+f"(d[17]), "+f"(d[18]), "+f"(d[19]), "+f"(d[20]), "+f"(d[21]), "+f"(d[22]), "+f"(d[23]), "+f"(d[24]), "+f"(d[25]), "+f"(d[26]), "+f"(d[27]), "+f"(d[28]), "+f"(d[29]), "+f"(d[30]), "+f"(d[31]), "+f"(d[32]), "+f"(d[33]), "+f"(d[34]), "+f"(d[35]), "+f"(d[36]), "+f"(d[37]), "+f"(d[38]), "+f"(d[39]), "+f"(d[40]), "+f"(d[41]), "+f"(d[42]), "+f"(d[43]), "+f"(d[44]), "+f"(d[45]), "+f"(d[46]), "+f"(d[47])
      : "l"(da), "l"(db));
  } else {
    asm volatile("{\n.reg .pred p;\nsetp.ne.b32 p, 0, 0;\n"
      "wgmma.mma_async.sync.aligned.m64n96k16.f32.bf16.bf16 {%0, %1, %2, %3, %4, %5, %6, %7, %8, %9, %10, %11, %12, %13, %14, %15, %16, %17, %18, %19, %20, %21, %22, %23, %24, %25, %26, %27, %28, %29, %30, %31, %32, %33, %34, %35, %36, %37, %38, %39, %40, %41, %42, %43, %44, %45, %46, %47}, %48, %49, p, 1, 1, 0, 1;\n}\n"
      : "=f"(d[0]), "=f"(d[1]), "=f"(d[2]), "=f"(d[3]), "=f"(d[4]), "=f"(d[5]), "=f"(d[6]), "=f"(d[7]), "=f"(d[8]), "=f"(d[9]), "=f"(d[10]), "=f"(d[11]), "=f"(d[12]), "=f"(d[13]), "=f"(d[14]), "=f"(d[15]), "=f"(d[16]), "=f"(d[17]), "=f"(d[18]), "=f"(d[19]), "=f"(d[20]), "=f"(d[21]), "=f"(d[22]), "=f"(d[23]), "=f"(d[24]), "=f"(d[25]), "=f"(d[26]), "=f"(d[27]), "=f"(d[28]), "=f"(d[29]), "=f"(d[30]), "=f"(d[31]), "=f"(d[32]), "=f"(d[33]), "=f"(d[34]), "=f"(d[35]), "=f"(d[36]), "=f"(d[37]), "=f"(d[38]), "=f"(d[39]), "=f"(d[40]), "=f"(d[41]), "=f"(d[42]), "=f"(d[43]), "=f"(d[44]), "=f"(d[45]), "=f"(d[46]), "=f"(d[47])
      : "l"(da), "l"(db));
  }
}
template <int SD> __device__ __forceinline__ void wgmma_rs_n96_t1(float (&d)[48], uint32_t a0, uint32_t a1, uint32_t a2, uint32_t a3, uint64_t db) {
  if constexpr (SD == 1) {
    asm volatile("{\n.reg .pred p;\nsetp.ne.b32 p, 1, 0;\n"
      "wgmma.mma_async.sync.aligned.m64n96k16.f32.bf16.bf16 {%0, %1, %2, %3, %4, %5, %6, %7, %8, %9, %10, %11, %12, %13, %14, %15, %16, %17, %18, %19, %20, %21, %22, %23, %24, %25, %26, %27, %28, %29, %30, %31, %32, %33, %34, %35, %36, %37, %38, %39, %40, %41, %42, %43, %44, %45, %46, %47}, {%48, %49, %50, %51}, %52, p, 1, 1, 1;\n}\n"
      : "+f"(d[0]), "+f"(d[1]), "+f"(d[2]), "+f"(d[3]), "+f"(d[4]), "+f"(d[5]), "+f"(d[6]), "+f"(d[7]), "+f"(d[8]), "+f"(d[9]), "+f"(d[10]), "+f"(d[11]), "+f"(d[12]), "+f"(d[13]), "+f"(d[14]), "+f"(d[15]), "+f"(d[16]), "+f"(d[17]), "+f"(d[18]), "+f"(d[19]), "+f"(d[20]), "+f"(d[21]), "+f"(d[22]), "+f"(d[23]), "+f"(d[24]), "+f"(d[25]), "+f"(d[26]), "+f"(d[27]), "+f"(d[28]), "+f"(d[29]), "+f"(d[30]), "+f"(d[31]), "+f"(d[32]), "+f"(d[33]), "+f"(d[34]), "+f"(d[35]), "+f"(d[36]), "+f"(d[37]), "+f"(d[38]), "+f"(d[39]), "+f"(d[40]), "+f"(d[41]), "+f"(d[42]), "+f"(d[43]), "+f"(d[44]), "+f"(d[45]), "+f"(d[46]), "+f"(d[47])
      : "r"(a0), "r"(a1), "r"(a2), "r"(a3), "l"(db));
  } else if constexpr (SD == 2) {
    asm volatile("{\n.reg .pred p;\nsetp.ne.b32 p, 0, 0;\n"
      "wgmma.mma_async.sync.aligned.m64n96k16.f32.bf16.bf16 {%0, %1, %2, %3, %4, %5, %6, %7, %8, %9, %10, %11, %12, %13, %14, %15, %16, %17, %18, %19, %20, %21, %22, %23, %24, %25, %26, %27, %28, %29, %30, %31, %32, %33, %34, %35, %36, %37, %38, %39, %40, %41, %42, %43, %44, %45, %46, %47}, {%48, %49, %50, %51}, %52, p, 1, 1, 1;\n}\n"
      : "+f"(d[0]), "+f"(d[1]), "+f"(d[2]), "+f"(d[3]), "+f"(d[4]), "+f"(d[5]), "+f"(d[6]), "+f"(d[7]), "+f"(d[8]), "+f"(d[9]), "+f"(d[10]), "+f"(d[11]), "+f"(d[12]), "+f"(d[13]), "+f"(d[14]), "+f"(d[15]), "+f"(d[16]), "+f"(d[17]), "+f"(d[18]), "+f"(d[19]), "+f"(d[20]), "+f"(d[21]), "+f"(d[22]), "+f"(d[23]), "+f"(d[24]), "+f"(d[25]), "+f"(d[26]), "+f"(d[27]), "+f"(d[28]), "+f"(d[29]), "+f"(d[30]), "+f"(d[31]), "+f"(d[32]), "+f"(d[33]), "+f"(d[34]), "+f"(d[35]), "+f"(d[36]), "+f"(d[37]), "+f"(d[38]), "+f"(d[39]), "+f"(d[40]), "+f"(d[41]), "+f"(d[42]), "+f"(d[43]), "+f"(d[44]), "+f"(d[45]), "+f"(d[46]), "+f"(d[47])
      : "r"(a0), "r"(a1), "r"(a2), "r"(a3), "l"(db));
  } else {
    asm volatile("{\n.reg .pred p;\nsetp.ne.b32 p, 0, 0;\n"
      "wgmma.mma_async.sync.aligned.m64n96k16.f32.bf16.bf16 {%0, %1, %2, %3, %4, %5, %6, %7, %8, %9, %10, %11, %12, %13, %14, %15, %16, %17, %18, %19, %20, %21, %22, %23, %24, %25, %26, %27, %28, %29, %30, %31, %32, %33, %34, %35, %36, %37, %38, %39, %40, %41, %42, %43, %44, %45, %46, %47}, {%48, %49, %50, %51}, %52, p, 1, 1, 1;\n}\n"
      : "=f"(d[0]), "=f"(d[1]), "=f"(d[2]), "=f"(d[3]), "=f"(d[4]), "=f"(d[5]), "=f"(d[6]), "=f"(d[7]), "=f"(d[8]), "=f"(d[9]), "=f"(d[10]), "=f"(d[11]), "=f"(d[12]), "=f"(d[13]), "=f"(d[14]), "=f"(d[15]), "=f"(d[16]), "=f"(d[17]), "=f"(d[18]), "=f"(d[19]), "=f"(d[20]), "=f"(d[21]), "=f"(d[22]), "=f"(d[23]), "=f"(d[24]), "=f"(d[25]), "=f"(d[26]), "=f"(d[27]), "=f"(d[28]), "=f"(d[29]), "=f"(d[30]), "=f"(d[31]), "=f"(d[32]), "=f"(d[33]), "=f"(d[34]), "=f"(d[35]), "=f"(d[36]), "=f"(d[37]), "=f"(d[38]), "=f"(d[39]), "=f"(d[40]), "=f"(d[41]), "=f"(d[42]), "=f"(d[43]), "=f"(d[44]), "=f"(d[45]), "=f"(d[46]), "=f"(d[47])
      : "r"(a0), "r"(a1), "r"(a2), "r"(a3), "l"(db));
  }
}
template <int SD> __device__ __forceinline__ void wgmma_rs_n64_t0(float (&d)[32], uint32_t a0, uint32_t a1, uint32_t a2, uint32_t a3, uint64_t db) {
  if constexpr (SD == 1) {
    asm volatile("{\n.reg .pred p;\nsetp.ne.b32 p, 1, 0;\n"
      "wgmma.mma_async.sync.aligned.m64n64k16.f32.bf16.bf16 {%0, %1, %2, %3, %4, %5, %6, %7, %8, %9, %10, %11, %12, %13, %14, %15, %16, %17, %18, %19, %20, %21, %22, %23, %24, %25, %26, %27, %28, %29, %30, %31}, {%32, %33, %34, %35}, %36, p, 1, 1, 0;\n}\n"
      : "+f"(d[0]), "+f"(d[1]), "+f"(d[2]), "+f"(d[3]), "+f"(d[4]), "+f"(d[5]), "+f"(d[6]), "+f"(d[7]), "+f"(d[8]), "+f"(d[9]), "+f"(d[10]), "+f"(d[11]), "+f"(d[12]), "+f"(d[13]), "+f"(d[14]), "+f"(d[15]), "+f"(d[16]), "+f"(d[17]), "+f"(d[18]), "+f"(d[19]), "+f"(d[20]), "+f"(d[21]), "+f"(d[22]), "+f"(d[23]), "+f"(d[24]), "+f"(d[25]), "+f"(d[26]), "+f"(d[27]), "+f"(d[28]), "+f"(d[29]), "+f"(d[30]), "+f"(d[31])
      : "r"(a0), "r"(a1), "r"(a2), "r"(a3), "l"(db));
  } else if constexpr (SD == 2) {
    asm volatile("{\n.reg .pred p;\nsetp.ne.b32 p, 0, 0;\n"
      "wgmma.mma_async.sync.aligned.m64n64k16.f32.bf16.bf16 {%0, %1, %2, %3, %4, %5, %6, %7, %8, %9, %10, %11, %12, %13, %14, %15, %16, %17, %18, %19, %20, %21, %22, %23, %24, %25, %26, %27, %28, %29, %30, %31}, {%32, %33, %34, %35}, %36, p, 1, 1, 0;\n}\n"
      : "+f"(d[0]), "+f"(d[1]), "+f"(d[2]), "+f"(d[3]), "+f"(d[4]), "+f"(d[5]), "+f"(d[6]), "+f"(d[7]), "+f"(d[8]), "+f"(d[9]), "+f"(d[10]), "+f"(d[11]), "+f"(d[12]), "+f"(d[13]), "+f"(d[14]), "+f"(d[15]), "+f"(d[16]), "+f"(d[17]), "+f"(d[18]), "+f"(d[19]), "+f"(d[20]), "+f"(d[21]), "+f"(d[22]), "+f"(d[23]), "+f"(d[24]), "+f"(d[25]), "+f"(d[26]), "+f"(d[27]), "+f"(d[28]), "+f"(d[29]), "+f"(d[30]), "+f"(d[31])
      : "r"(a0), "r"(a1), "r"(a2), "r"(a3), "l"(db));
  } else {
    asm volatile("{\n.reg .pred p;\nsetp.ne.b32 p, 0, 0;\n"
      "wgmma.mma_async.sync.aligned.m64n64k16.f32.bf16.bf16 {%0, %1, %2, %3, %4, %5, %6, %7, %8, %9, %10, %11, %12, %13, %14, %15, %16, %17, %18, %19, %20, %21, %22, %23, %24, %25, %26, %27, %28, %29, %30, %31}, {%32, %33, %34, %35}, %36, p, 1, 1, 0;\n}\n"
      : "=f"(d[0]), "=f"(d[1]), "=f"(d[2]), "=f"(d[3]), "=f"(d[4]), "=f"(d[5]), "=f"(d[6]), "=f"(d[7]), "=f"(d[8]), "=f"(d[9]), "=f"(d[10]), "=f"(d[11]), "=f"(d[12]), "=f"(d[13]), "=f"(d[14]), "=f"(d[15]), "=f"(d[16]), "=f"(d[17]), "=f"(d[18]), "=f"(d[19]), "=f"(d[20]), "=f"(d[21]), "=f"(d[22]), "=f"(d[23]), "=f"(d[24]), "=f"(d[25]), "=f"(d[26]), "=f"(d[27]), "=f"(d[28]), "=f"(d[29]), "=f"(d[30]), "=f"(d[31])
      : "r"(a0), "r"(a1), "r"(a2), "r"(a3), "l"(db));
  }
}
template <int SD> __device__ __forceinline__ void wgmma_rs_n32_t1(float (&d)[16], uint32_t a0, uint32_t a1, uint32_t a2, uint32_t a3, uint64_t db) {
  if constexpr (SD == 1) {
    asm volatile("{\n.reg .pred p;\nsetp.ne.b32 p, 1, 0;\n"
      "wgmma.mma_async.sync.aligned.m64n32k16.f32.bf16.bf16 {%0, %1, %2, %3, %4, %5, %6, %7, %8, %9, %10, %11, %12, %13, %14, %15}, {%16, %17, %18, %19}, %20, p, 1, 1, 1;\n}\n"
      : "+f"(d[0]), "+f"(d[1]), "+f"(d[2]), "+f"(d[3]), "+f"(d[4]), "+f"(d[5]), "+f"(d[6]), "+f"(d[7]), "+f"(d[8]), "+f"(d[9]), "+f"(d[10]), "+f"(d[11]), "+f"(d[12]), "+f"(d[13]), "+f"(d[14]), "+f"(d[15])
      : "r"(a0), "r"(a1), "r"(a2), "r"(a3), "l"(db));
  } else if constexpr (SD == 2) {
    asm volatile("{\n.reg .pred p;\nsetp.ne.b32 p, 0, 0;\n"
      "wgmma.mma_async.sync.aligned.m64n32k16.f32.bf16.bf16 {%0, %1, %2, %3, %4, %5, %6, %7, %8, %9, %10, %11, %12, %13, %14, %15}, {%16, %17, %18, %19}, %20, p, 1, 1, 1;\n}\n"
      : "+f"(d[0]), "+f"(d[1]), "+f"(d[2]), "+f"(d[3]), "+f"(d[4]), "+f"(d[5]), "+f"(d[6]), "+f"(d[7]), "+f"(d[8]), "+f"(d[9]), "+f"(d[10]), "+f"(d[11]), "+f"(d[12]), "+f"(d[13]), "+f"(d[14]), "+f"(d[15])
      : "r"(a0), "r"(a1), "r"(a2), "r"(a3), "l"(db));
  } else {
    asm volatile("{\n.reg .pred p;\nsetp.ne.b32 p, 0, 0;\n"
      "wgmma.mma_async.sync.aligned.m64n32k16.f32.bf16.bf16 {%0, %1, %2, %3, %4, %5, %6, %7, %8, %9, %10, %11, %12, %13, %14, %15}, {%16, %17, %18, %19}, %20, p, 1, 1, 1;\n}\n"
      : "=f"(d[0]), "=f"(d[1]), "=f"(d[2]), "=f"(d[3]), "=f"(d[4]), "=f"(d[5]), "=f"(d[6]), "=f"(d[7]), "=f"(d[8]), "=f"(d[9]), "=f"(d[10]), "=f"(d[11]), "=f"(d[12]), "=f"(d[13]), "=f"(d[14]), "=f"(d[15])
      : "r"(a0), "r"(a1), "r"(a2), "r"(a3), "l"(db));
  }
}
template <int SD> __device__ __forceinline__ void wgmma_rs_n8_t0(float (&d)[4], uint32_t a0, uint32_t a1, uint32_t a2, uint32_t a3, uint64_t db) {
  if constexpr (SD == 1) {
    asm volatile("{\n.reg .pred p;\nsetp.ne.b32 p, 1, 0;\n"
      "wgmma.mma_async.sync.aligned.m64n8k16.f32.bf16.bf16 {%0, %1, %2, %3}, {%4, %5, %6, %7}, %8, p, 1, 1, 0;\n}\n"
      : "+f"(d[0]), "+f"(d[1]), "+f"(d[2]), "+f"(d[3])
      : "r"(a0), "r"(a1), "r"(a2), "r"(a3), "l"(db));
  } else if constexpr (SD == 2) {
    asm volatile("{\n.reg .pred p;\nsetp.ne.b32 p, 0, 0;\n"
      "wgmma.mma_async.sync.aligned.m64n8k16.f32.bf16.bf16 {%0, %1, %2, %3}, {%4, %5, %6, %7}, %8, p, 1, 1, 0;\n}\n"
      : "+f"(d[0]), "+f"(d[1]), "+f"(d[2]), "+f"(d[3])
      : "r"(a0), "r"(a1), "r"(a2), "r"(a3), "l"(db));
  } else {
    asm volatile("{\n.reg .pred p;\nsetp.ne.b32 p, 0, 0;\n"
      "wgmma.mma_async.sync.aligned.m64n8k16.f32.bf16.bf16 {%0, %1, %2, %3}, {%4, %5, %6, %7}, %8, p, 1, 1, 0;\n}\n"
      : "=f"(d[0]), "=f"(d[1]), "=f"(d[2]), "=f"(d[3])
      : "r"(a0), "r"(a1), "r"(a2), "r"(a3), "l"(db));
  }
}


__device__ __forceinline__ void wg_fence()  { asm volatile("wgmma.fence.sync.aligned;" ::: "memory"); }
__device__ __forceinline__ void wg_commit() { asm volatile("wgmma.commit_group.sync.aligned;" ::: "memory"); }
template <int N> __device__ __forceinline__ void wg_wait() { asm volatile("wgmma.wait_group.sync.aligned %0;" :: "n"(N) : "memory"); }
template <int N> __device__ __forceinline__ void fence_regs(float (&d)[N]) {
#pragma unroll
  for (int i = 0; i < N; i++) asm volatile("" : "+f"(d[i]) :: "memory");
}
__device__ __forceinline__ constexpr uint64_t mk_desc(uint32_t addr, uint32_t lbo, uint32_t sbo, uint32_t swz) {
  return (uint64_t)(addr >> 4) | ((uint64_t)(lbo >> 4) << 16) | ((uint64_t)(sbo >> 4) << 32) | ((uint64_t)swz << 62);
}
__device__ __forceinline__ uint32_t pack_bf16(float lo, float hi) {
  uint32_t r; asm("cvt.rn.bf16x2.f32 %0, %1, %2;" : "=r"(r) : "f"(hi), "f"(lo)); return r;
}
__device__ __forceinline__ uint32_t hmul2(uint32_t a, uint32_t b) {
  uint32_t r; asm("mul.rn.bf16x2 %0, %1, %2;" : "=r"(r) : "r"(a), "r"(b)); return r;
}
template <int HI> __device__ __forceinline__ uint32_t hmul2_b(uint32_t a, uint32_t b) {
  uint32_t r;
  if (HI) asm("{\n.reg .b16 l, h;\n.reg .b32 t;\nmov.b32 {l, h}, %2;\nmov.b32 t, {h, h};\nmul.rn.bf16x2 %0, %1, t;\n}\n" : "=r"(r) : "r"(a), "r"(b));
  else    asm("{\n.reg .b16 l, h;\n.reg .b32 t;\nmov.b32 {l, h}, %2;\nmov.b32 t, {l, l};\nmul.rn.bf16x2 %0, %1, t;\n}\n" : "=r"(r) : "r"(a), "r"(b));
  return r;
}
__device__ __forceinline__ uint32_t hfma2(uint32_t a, uint32_t b, uint32_t c) {
  uint32_t r; asm("fma.rn.bf16x2 %0, %1, %2, %3;" : "=r"(r) : "r"(a), "r"(b), "r"(c)); return r;
}
__device__ __forceinline__ float ex2(float x) { float r; asm("ex2.approx.ftz.f32 %0, %1;" : "=f"(r) : "f"(x)); return r; }
__device__ __forceinline__ float rsq(float x) { float r; asm("rsqrt.approx.ftz.f32 %0, %1;" : "=f"(r) : "f"(x)); return r; }
__device__ __forceinline__ float rcp(float x) { float r; asm("rcp.approx.ftz.f32 %0, %1;" : "=f"(r) : "f"(x)); return r; }
__device__ __forceinline__ void stsm4(uint32_t addr, uint32_t r0, uint32_t r1, uint32_t r2, uint32_t r3) {
  asm volatile("stmatrix.sync.aligned.m8n8.x4.shared.b16 [%0], {%1,%2,%3,%4};" :: "r"(addr), "r"(r0), "r"(r1), "r"(r2), "r"(r3) : "memory");
}
__device__ __forceinline__ void fence_async() { asm volatile("fence.proxy.async.shared::cta;" ::: "memory"); }
__device__ __forceinline__ void bar_sync_n(int id, int n) { asm volatile("bar.sync %0, %1;" :: "r"(id), "r"(n) : "memory"); }
__device__ __forceinline__ void bar_arrive_n(int id, int n) { asm volatile("bar.arrive %0, %1;" :: "r"(id), "r"(n) : "memory"); }
__device__ __forceinline__ void mbar_init(uint32_t bar, uint32_t cnt) { asm volatile("mbarrier.init.shared::cta.b64 [%0], %1;" :: "r"(bar), "r"(cnt) : "memory"); }
__device__ __forceinline__ void mbar_expect(uint32_t bar, uint32_t bytes) {
  asm volatile("mbarrier.arrive.expect_tx.shared::cta.b64 _, [%0], %1;" :: "r"(bar), "r"(bytes) : "memory");
}
__device__ __forceinline__ void mbar_arrive(uint32_t bar) { asm volatile("mbarrier.arrive.shared::cta.b64 _, [%0];" :: "r"(bar) : "memory"); }
__device__ __forceinline__ void mbar_wait(uint32_t bar, uint32_t parity) {
  asm volatile("{\n.reg .pred p;\n.reg .u32 n;\nmov.u32 n, 0;\n"
               "LW_%=:\nmbarrier.try_wait.parity.shared::cta.b64 p, [%0], %1;\n@p bra.uni LD_%=;\n"
               "add.u32 n, n, 1;\nsetp.lt.u32 p, n, 4194304;\n@p bra.uni LW_%=;\ntrap;\nLD_%=:\n}\n"
               :: "r"(bar), "r"(parity) : "memory");
}
__device__ __forceinline__ void tma5(uint32_t dst, const CUtensorMap* m, uint32_t bar, int c0, int c1, int c2, int c3, int c4) {
  asm volatile("cp.async.bulk.tensor.5d.shared::cluster.global.mbarrier::complete_tx::bytes [%0], [%1, {%3, %4, %5, %6, %7}], [%2];"
               :: "r"(dst), "l"(m), "r"(bar), "r"(c0), "r"(c1), "r"(c2), "r"(c3), "r"(c4) : "memory");
}
__device__ __forceinline__ void tma3(uint32_t dst, const CUtensorMap* m, uint32_t bar, int c0, int c1, int c2) {
  asm volatile("cp.async.bulk.tensor.3d.shared::cluster.global.mbarrier::complete_tx::bytes [%0], [%1, {%3, %4, %5}], [%2];"
               :: "r"(dst), "l"(m), "r"(bar), "r"(c0), "r"(c1), "r"(c2) : "memory");
}
__device__ __forceinline__ void bulk_g2s(uint32_t dst, const void* src, uint32_t bytes, uint32_t bar) {
  asm volatile("cp.async.bulk.shared::cluster.global.mbarrier::complete_tx::bytes [%0], [%1], %2, [%3];"
               :: "r"(dst), "l"(src), "r"(bytes), "r"(bar) : "memory");
}
__device__ __forceinline__ uint32_t lds32(uint32_t addr) {
  uint32_t v; asm volatile("ld.shared.u32 %0, [%1];" : "=r"(v) : "r"(addr)); return v;
}
__device__ __forceinline__ uint64_t opaque(uint64_t v) { asm volatile("" : "+l"(v)); return v; }
__device__ __forceinline__ uint4 lds128(uint32_t addr) {
  uint4 v; asm volatile("ld.shared.v4.u32 {%0,%1,%2,%3}, [%4];" : "=r"(v.x), "=r"(v.y), "=r"(v.z), "=r"(v.w) : "r"(addr)); return v;
}
__device__ __forceinline__ uint4 ldg128_stream(const void* p) {
  uint4 v; asm volatile("ld.global.nc.L1::no_allocate.v4.u32 {%0,%1,%2,%3}, [%4];" : "=r"(v.x), "=r"(v.y), "=r"(v.z), "=r"(v.w) : "l"(p)); return v;
}
__device__ __forceinline__ void stg128(void* p, uint32_t a, uint32_t b, uint32_t c, uint32_t d) {
  asm volatile("st.global.cs.v4.u32 [%0], {%1,%2,%3,%4};" :: "l"(p), "r"(a), "r"(b), "r"(c), "r"(d) : "memory");
}
__device__ __forceinline__ void prefetch_l2(const void* p, uint32_t bytes) {
  asm volatile("cp.async.bulk.prefetch.L2.global [%0], %1;" :: "l"(p), "r"(bytes) : "memory");
}
__device__ __forceinline__ bool elect_one() {
  uint32_t r; asm volatile("{\n.reg .pred p;\nelect.sync _|p, 0xffffffff;\nselp.u32 %0, 1, 0, p;\n}\n" : "=r"(r)); return r != 0;
}
__device__ __forceinline__ float bf_lo(uint32_t u) { return __uint_as_float(u << 16); }
__device__ __forceinline__ float bf_hi(uint32_t u) { return __uint_as_float(u & 0xFFFF0000u); }
__device__ __forceinline__ float rbf(float x) { return bf_lo(pack_bf16(x, 0.f)); }
__device__ __forceinline__ int orig_tok(int r) { return ((r & 31) >> 2) * 8 + (r >> 5) * 4 + (r & 3); }

__device__ __forceinline__ int slot_window(int s, bool g132) {
  const int A0 = g132 ? 396 + 264 + 60 : 47 * 47, A1 = A0 + 72, B0 = g132 ? 3 * 396 + 264 + 60 : A1, B1 = B0 + 23;
  const int i = s - (s >= B1 ? 95 : s >= A1 ? 72 : 0);
  const int k = s >= B0 ? s - B0 + 72 : s - A0;
  const bool border = (s >= A0 && s < A1) || (s >= B0 && s < B1);
  const int iy = (i * 2789) >> 17;
  return border ? (k < 48 ? (47 << 8 | k) : ((k - 48) << 8 | 47)) : (iy << 8 | (i - iy * 47));
}

template <int OFF = 0> __device__ __forceinline__ void load_eb(uint32_t (&e)[16], uint32_t eb_addr) {
  asm volatile("ld.shared.v4.u32 {%0,%1,%2,%3}, [%4+%5];" : "=r"(e[0]), "=r"(e[1]), "=r"(e[2]), "=r"(e[3]) : "r"(eb_addr), "n"(OFF));
  asm volatile("ld.shared.v4.u32 {%0,%1,%2,%3}, [%4+%5];" : "=r"(e[4]), "=r"(e[5]), "=r"(e[6]), "=r"(e[7]) : "r"(eb_addr), "n"(OFF + 2048));
  asm volatile("ld.shared.v4.u32 {%0,%1,%2,%3}, [%4+%5];" : "=r"(e[8]), "=r"(e[9]), "=r"(e[10]), "=r"(e[11]) : "r"(eb_addr), "n"(OFF + 4096));
  asm volatile("ld.shared.v4.u32 {%0,%1,%2,%3}, [%4+%5];" : "=r"(e[12]), "=r"(e[13]), "=r"(e[14]), "=r"(e[15]) : "r"(eb_addr), "n"(OFF + 6144));
}
__device__ __forceinline__ void softmax_fast(const float (&s)[32], uint32_t (&p)[16]) {
#pragma unroll
  for (int i = 0; i < 16; i++) p[i] = hmul2(pack_bf16(ex2(s[2 * i]), ex2(s[2 * i + 1])), p[i]);
}
__device__ __forceinline__ uint32_t hmax2(uint32_t a, uint32_t b) {
  uint32_t r; asm("max.bf16x2 %0, %1, %2;" : "=r"(r) : "r"(a), "r"(b)); return r;
}
__device__ __forceinline__ float quad_max(float m) {
  m = fmaxf(m, __shfl_xor_sync(0xffffffffu, m, 1));
  return fmaxf(m, __shfl_xor_sync(0xffffffffu, m, 2));
}
__device__ __forceinline__ void softmax_true_max(const float (&s)[32], uint32_t (&p)[16]) {
  float m0 = s[0], m1 = s[2];
#pragma unroll
  for (int g = 0; g < 8; g++) {
    m0 = fmaxf(m0, fmaxf(s[4 * g + 0], s[4 * g + 1]));
    m1 = fmaxf(m1, fmaxf(s[4 * g + 2], s[4 * g + 3]));
  }
  m0 = quad_max(m0); m1 = quad_max(m1);
  uint32_t n0 = 0, n1 = 0;
#pragma unroll
  for (int g = 0; g < 8; g++) {
    p[2 * g + 0] = hmul2(pack_bf16(ex2(s[4 * g + 0] - m0), ex2(s[4 * g + 1] - m0)), p[2 * g + 0]);
    p[2 * g + 1] = hmul2(pack_bf16(ex2(s[4 * g + 2] - m1), ex2(s[4 * g + 3] - m1)), p[2 * g + 1]);
    n0 = hmax2(n0, p[2 * g]); n1 = hmax2(n1, p[2 * g + 1]);
  }
  const uint32_t r = pack_bf16(rcp(quad_max(fmaxf(bf_lo(n0), bf_hi(n0)))), rcp(quad_max(fmaxf(bf_lo(n1), bf_hi(n1)))));
#pragma unroll
  for (int g = 0; g < 8; g++) { p[2 * g] = hmul2_b<0>(p[2 * g], r); p[2 * g + 1] = hmul2_b<1>(p[2 * g + 1], r); }
}
template <int H> __device__ __forceinline__ void issue_s(float (&s)[32], const uint32_t (&q)[24], uint64_t dK) {
  constexpr int Q0 = (H == 0 ? 0 : H == 1 ? 4 : H == 2 ? 12 : 16), P0 = (H == 0 ? 0 : H == 1 ? 3 : H == 2 ? 7 : 10);
  wgmma_rs_n64_t0<(H >= 2 ? 2 : 0)>(s, q[Q0], q[Q0 + 1], q[Q0 + 2], q[Q0 + 3], dK + P0 * 64);
  wgmma_rs_n64_t0<1>(s, q[Q0 + 4], q[Q0 + 5], q[Q0 + 6], q[Q0 + 7], dK + P0 * 64 + 128);
}
template <int H> __device__ __forceinline__ void issue_pv(float (&o)[16], const uint32_t (&p)[16], uint64_t dV) {
  constexpr int P0 = (H == 0 ? 0 : H == 1 ? 3 : H == 2 ? 7 : 10);
  wgmma_rs_n32_t1<0>(o, p[0], p[1], p[2], p[3], dV + P0 * 64);
  wgmma_rs_n32_t1<1>(o, p[4], p[5], p[6], p[7], dV + P0 * 64 + 16);
  wgmma_rs_n32_t1<1>(o, p[8], p[9], p[10], p[11], dV + P0 * 64 + 32);
  wgmma_rs_n32_t1<1>(o, p[12], p[13], p[14], p[15], dV + P0 * 64 + 48);
}
__device__ __forceinline__ void issue_proj(float (&d)[48], uint64_t dX, uint64_t dW) {
#pragma unroll
  for (int s = 0; s < 6; s++) {
    const uint64_t a = dX + (s >> 1) * 256 + (s & 1) * 2, b = dW + s * 64;
    if (s == 0) wgmma_ss_n96_t1<0>(d, a, b); else wgmma_ss_n96_t1<1>(d, a, b);
  }
}
__device__ __forceinline__ void issue_qk(float (&d)[96], uint64_t dX, uint64_t dW) {
#pragma unroll
  for (int s = 0; s < 6; s++) {
    const uint64_t a = dX + (s >> 1) * 256 + (s & 1) * 2, b = dW + s * 128;
    if (s == 0) wgmma_ss_n192_t1<0>(d, a, b); else wgmma_ss_n192_t1<1>(d, a, b);
  }
}
__device__ __forceinline__ void pack_sumsq(const float* a, uint32_t (&f)[24], uint32_t (&sq)[8], uint32_t init) {
#pragma unroll
  for (int i = 0; i < 24; i++) f[i] = pack_bf16(a[2 * i], a[2 * i + 1]);
#pragma unroll
  for (int h = 0; h < 4; h++)
#pragma unroll
    for (int r = 0; r < 2; r++) {
      uint32_t u = f[6 * h + r], v = f[6 * h + 2 + r], w = f[6 * h + 4 + r];
      sq[2 * h + r] = hfma2(w, w, hfma2(v, v, hfma2(u, u, init)));
    }
}
__device__ __forceinline__ void scale_heads(uint32_t (&f)[24], const float (&r)[8]) {
#pragma unroll
  for (int h = 0; h < 4; h++) {
    const uint32_t p = pack_bf16(r[2 * h], r[2 * h + 1]);
#pragma unroll
    for (int c = 0; c < 3; c++) {
      f[6 * h + 2 * c] = hmul2_b<0>(f[6 * h + 2 * c], p);
      f[6 * h + 2 * c + 1] = hmul2_b<1>(f[6 * h + 2 * c + 1], p);
    }
  }
}
template <int ODD> __device__ __forceinline__ uint32_t norm_o(const float (&o)[16], uint32_t* of) {
  constexpr int SO = ODD ? 0 : 12, VO = ODD ? 4 : 0;
  const uint32_t p = pack_bf16(rcp(o[SO]), rcp(o[SO + 2]));
#pragma unroll
  for (int g = 0; g < 3; g++) {
    of[2 * g + 0] = hmul2_b<0>(pack_bf16(o[VO + 4 * g + 0], o[VO + 4 * g + 1]), p);
    of[2 * g + 1] = hmul2_b<1>(pack_bf16(o[VO + 4 * g + 2], o[VO + 4 * g + 3]), p);
  }
  return p - 0x1F801F80u;
}


constexpr int BAR_KV = 1;
constexpr int BAR_AUX = 4;
constexpr int BAR_TAB = 7, BAR_SETUP = 8, BAR_PAR = 9;
constexpr int MB_WQK = 0, MB_X = 8, MB_KV = 32, MB_WV = 56, MB_WO = 64, MB_TURN = 72, MB_RDY = 128;
constexpr uint32_t sb = 1024, mbar = sb + SM_BAR;
constexpr uint32_t EPS8 = 0x2A0D2A0Du;

__device__ __forceinline__ void load_x_interior(const CUtensorMap* tm_x, int w, int g) {
  mbar_expect(mbar + MB_X + 8 * g, 12288);
  tma5(sb + SM_WG + g * WG_SZ + WG_X, tm_x, mbar + MB_X + 8 * g, 0, 0, ((w >> 8) & 255) * 8 + 4, (w & 255) * 2 + 1, 0);
}
__device__ __forceinline__ void load_x(const CUtensorMap* tm_x, const CUtensorMap* tm_xq, int w, int g) {
  const uint32_t dst = sb + SM_WG + g * WG_SZ + WG_X, bar = mbar + MB_X + 8 * g;
  const int wy = (w >> 8) & 255, wx = w & 255;
  mbar_expect(bar, 12288);
  if (wy != NWX - 1 && wx != NWX - 1) {
    tma5(dst, tm_x, bar, 0, 0, wy * 8 + 4, wx * 2 + 1, 0);
  } else {
#pragma unroll 1
    for (int i = 0; i < 12; i++) {
      const int q = i & 3, c = i >> 2;
      int y = wy * 8 + 4 + (q & 1) * 4; if (y >= IMG) y -= IMG;
      int xq = wx * 2 + 1 + (q >> 1);   if (xq >= IMG / 4) xq -= IMG / 4;
      tma5(dst + i * 1024, tm_xq, bar, 0, 0, y, xq, c);
    }
  }
}
__device__ __forceinline__ uint32_t mask_off(int w) { return (uint32_t)(((w >> 8) & 255) * NWX + (w & 255)) * 8192u; }
__device__ __forceinline__ int lds_uniform(uint32_t addr) { return __shfl_sync(0xffffffffu, lds32(addr), 0); }

__device__ __forceinline__ void scale_pair(uint32_t* f, const float (&n)[4], float s0, float s1) {
  const uint32_t p0 = pack_bf16(rsq(n[0]) * s0, rsq(n[2]) * s0), p1 = pack_bf16(rsq(n[1]) * s1, rsq(n[3]) * s1);
#pragma unroll
  for (int c = 0; c < 3; c++) {
    f[2 * c] = hmul2_b<0>(f[2 * c], p0); f[2 * c + 1] = hmul2_b<1>(f[2 * c + 1], p0);
    f[6 + 2 * c] = hmul2_b<0>(f[6 + 2 * c], p1); f[6 + 2 * c + 1] = hmul2_b<1>(f[6 + 2 * c + 1], p1);
  }
}
__device__ __forceinline__ void qkv_epilogue(float (&qk)[96], uint32_t (&qa)[24], float (&q23)[4], float2& s23, uint64_t dX, uint64_t dWv, uint32_t k_dst) {
  uint32_t ka[24], sk[8], sq[8];
  float k01[4], k23[4], q01[4], vv[48];
  constexpr uint64_t dSel = mk_desc(sb + SM_SEL, 128, 256, 0);
  wg_wait<0>(); fence_regs(qk);
  pack_sumsq(qk + 48, ka, sk, EPS8);
  pack_sumsq(qk, qa, sq, EPS8);
  wg_fence();
  wgmma_rs_n8_t0<0>(k01, sk[0], sk[1], sk[2], sk[3], dSel);
  wgmma_rs_n8_t0<0>(k23, sk[4], sk[5], sk[6], sk[7], dSel);
  wgmma_rs_n8_t0<0>(q01, sq[0], sq[1], sq[2], sq[3], dSel);
  wgmma_rs_n8_t0<0>(q23, sq[4], sq[5], sq[6], sq[7], dSel);
  wg_commit();
  issue_proj(vv, dX, dWv); wg_commit();
  const uint4 qs = lds128(sb + SM_MISC);
  wg_wait<1>(); fence_regs(k01); fence_regs(k23); fence_regs(q01); fence_regs(q23);
  const float rk[8] = {rsq(k01[0]), rsq(k01[2]), rsq(k01[1]), rsq(k01[3]), rsq(k23[0]), rsq(k23[2]), rsq(k23[1]), rsq(k23[3])};
  scale_heads(ka, rk);
#pragma unroll
  for (int i = 0; i < 6; i++) stsm4(k_dst + (i + (i >= 3)) * 1024, ka[2 * i], ka[2 * i + 1], ka[12 + 2 * i], ka[12 + 2 * i + 1]);
  wg_wait<0>(); fence_regs(vv);
#pragma unroll
  for (int i = 0; i < 6; i++)
    stsm4(k_dst + (WG_V - WG_K) + (i + (i >= 3)) * 1024, pack_bf16(vv[4 * i], vv[4 * i + 1]), pack_bf16(vv[4 * i + 2], vv[4 * i + 3]),
          pack_bf16(vv[24 + 4 * i], vv[24 + 4 * i + 1]), pack_bf16(vv[24 + 4 * i + 2], vv[24 + 4 * i + 3]));
  scale_pair(qa, q01, __uint_as_float(qs.x), __uint_as_float(qs.y));
  s23 = make_float2(__uint_as_float(qs.z), __uint_as_float(qs.w));
  fence_async();
}
__device__ __forceinline__ void issue_out(float (&y)[48], const uint32_t (&of)[24], uint64_t dWo) {
  wg_fence();
#pragma unroll
  for (int s = 0; s < 6; s++) {
    if (s == 0) wgmma_rs_n96_t1<0>(y, of[0], of[1], of[2], of[3], dWo);
    else wgmma_rs_n96_t1<1>(y, of[4 * s], of[4 * s + 1], of[4 * s + 2], of[4 * s + 3], dWo + s * 16);
  }
  wg_commit();
}
__device__ __forceinline__ void ln_head(float (&y)[48], uint32_t (&yb)[24], float (&var)[4], uint64_t dOnes) {
  uint32_t sy[8];
  wg_wait<0>(); fence_regs(y);
  pack_sumsq(y, yb, sy, 0u);
  wg_fence();
  wgmma_rs_n8_t0<0>(var, sy[0], sy[1], sy[2], sy[3], dOnes);
  wgmma_rs_n8_t0<1>(var, sy[4], sy[5], sy[6], sy[7], dOnes);
  wg_commit();
}
__device__ __forceinline__ char* out_ptr(__nv_bfloat16* out, int win, int warp, uint32_t t16) {
  int py = ((win >> 8) & 255) * 8 + 4 + (warp & 1) * 4;  if (py >= IMG) py -= IMG;
  int px = (win & 255) * 8 + 4 + (warp >> 1) * 4;        if (px >= IMG) px -= IMG;
  return reinterpret_cast<char*>(out) + ((uint32_t)(py * IMG + px) * PIXB - warp * 512 + t16 + ((t16 & 0xC0) << 1) + (t16 & 0x100) * 287);
}
__device__ __forceinline__ uint32_t ln_tail(const uint32_t (&yb)[24], float (&var)[4], char* optr) {
  fence_regs(var);
  uint32_t last;
  const uint32_t nn = pack_bf16(rsq(fmaf(var[0], 1.f / 96.f, 1e-5f)), rsq(fmaf(var[2], 1.f / 96.f, 1e-5f)));
#pragma unroll
  for (int j = 0; j < 3; j++) {
    stg128(optr + j * 64, hmul2_b<0>(yb[8 * j], nn), hmul2_b<0>(yb[8 * j + 2], nn), hmul2_b<0>(yb[8 * j + 4], nn), hmul2_b<0>(yb[8 * j + 6], nn));
    last = hmul2_b<1>(yb[8 * j + 7], nn);
    stg128(optr + 2 * ROWB + j * 64, hmul2_b<1>(yb[8 * j + 1], nn), hmul2_b<1>(yb[8 * j + 3], nn), hmul2_b<1>(yb[8 * j + 5], nn), last);
  }
  return last;
}

__device__ __forceinline__ void load_mask_frag(uint32_t (&mk)[16], const char* tile, uint32_t t16) {
  asm volatile("" : "+r"(t16));
  const char* mrow = tile + (orig_tok(((t16 >> 9) << 4) + ((t16 >> 6) & 7)) * 128 + (t16 & 32) / 2);
  const bool odd = t16 & 16;
#pragma unroll
  for (int i = 0; i < 8; i++) {
    const uint4 v = ldg128_stream(mrow + (i & 1) * 2048 + (i >> 1) * 32);
    mk[i] = odd ? v.y : v.x; mk[8 + i] = odd ? v.w : v.z;
  }
}
__device__ __forceinline__ void general_windows(const CUtensorMap* tm_x, const CUtensorMap* tm_xq, const char* mb, __nv_bfloat16* out, uint32_t xph) {
  int tid;
  asm volatile("mov.u32 %0, %%tid.x;" : "=r"(tid));
  const int lane = tid & 31;
  const int warp = __shfl_sync(0xffffffffu, (tid >> 5) & 3, 0), wg = __shfl_sync(0xffffffffu, tid >> 7, 0);
  const uint32_t t16 = (tid & 127) * 16, wgb = sb + SM_WG + wg * WG_SZ, bar_x = mbar + MB_X + 8 * wg;
  const uint32_t k_dst = wgb + WG_K + (lane >> 4) * 7168 + warp * 256 + (lane & 15) * 16;
  if (lds_uniform(sb + SM_GEN + wg * NENT * 4) < 0) return;
  const uint64_t dX = mk_desc(WG_X, 16, 512, 2) + (wgb >> 4), dK = mk_desc(WG_K, 1024, 128, 0) + (wgb >> 4), dV = mk_desc(WG_V, 128, 1024, 0) + (wgb >> 4);
#pragma unroll 1
  for (uint32_t gl = sb + SM_GEN + wg * NENT * 4;; gl += 4) {
    const int win = lds_uniform(gl);
    if (win < 0) break;
    uint32_t qa[24], of[24], mk[16];
    {
      load_mask_frag(mk, mb + mask_off(win), t16);
      float qk[96];
      mbar_wait(bar_x, xph); xph ^= 1;
      wg_fence();
      issue_qk(qk, dX, mk_desc(sb + SM_W, 12288, 1024, 1)); wg_commit();
      bar_sync_n(BAR_KV + wg, 128);
      float q23[4]; float2 s23;
      qkv_epilogue(qk, qa, q23, s23, dX, mk_desc(sb + SM_WV, 6144, 512, 2), k_dst);
      scale_pair(qa + 12, q23, s23.x, s23.y);
    }
    bar_sync_n(BAR_AUX + wg, 128);
    if (warp == 0 && elect_one()) {
      const int nxt = lds32(gl + 4);
      if (nxt >= 0) { load_x(tm_x, tm_xq, nxt, wg); prefetch_l2(mb + mask_off(nxt), 8192); }
    }
    __syncwarp();
    auto head = [&](float (&sc)[32], uint32_t (&p)[16]) {
#pragma unroll
      for (int i = 0; i < 16; i++) {
        uint32_t m = mk[i];
        asm volatile("" : "+r"(m));
        sc[2 * i] = fmaf(bf_lo(m), LOG2E, sc[2 * i]); sc[2 * i + 1] = fmaf(bf_hi(m), LOG2E, sc[2 * i + 1]);
      }
      softmax_true_max(sc, p);
    };
#pragma unroll
    for (int i = 0; i < 24; i++) of[i] = 0;
#pragma unroll 1
    for (int hp = 0; hp < 2; hp++) {
      float sA[32], sB[32], oA[16], oB[16]; uint32_t p[16];
      const uint32_t po = hp * 7 * 64;
      wg_fence();
      issue_s<0>(sA, qa, dK + po);
      issue_s<1>(sB, qa, dK + po); wg_commit();
      load_eb(p, sb + SM_EB + t16 + hp * 16384);
      wg_wait<0>(); fence_regs(sA); fence_regs(sB);
#pragma unroll
      for (int i = 0; i < 12; i++) { qa[i] = qa[i + 12]; of[i] = of[i + 12]; }
      head(sA, p);
      wg_fence(); issue_pv<0>(oA, p, dV + po); wg_commit();
      uint32_t p2[16];
      load_eb(p2, sb + SM_EB + t16 + hp * 16384 + 8192);
      head(sB, p2);
      wg_fence(); issue_pv<1>(oB, p2, dV + po); wg_commit();
      wg_wait<1>(); fence_regs(oA);
      norm_o<0>(oA, of + 12);
      wg_wait<0>(); fence_regs(oB);
      norm_o<1>(oB, of + 18);
    }
    float y[48], var[4]; uint32_t yb[24];
    issue_out(y, of, mk_desc(sb + SM_WO, 128, 1536, 0));
    ln_head(y, yb, var, dV + 3 * 64);
    wg_wait<0>();
    ln_tail(yb, var, out_ptr(out, win, warp, t16));
  }
}

__global__ void __launch_bounds__(384, 1)
swin_kernel(const __nv_bfloat16* __restrict__ logit_scale, const __nv_bfloat16* __restrict__ w1, const __nv_bfloat16* __restrict__ w2,
            const __nv_bfloat16* __restrict__ coords, const int* __restrict__ rel_idx, const __nv_bfloat16* __restrict__ wo,
            const __nv_bfloat16* __restrict__ mask, __nv_bfloat16* __restrict__ out,
            const __grid_constant__ CUtensorMap tm_wqk, const __grid_constant__ CUtensorMap tm_x,
            const __grid_constant__ CUtensorMap tm_wv, const __grid_constant__ CUtensorMap tm_xq) {
  extern __shared__ __align__(1024) uint8_t smem[];
  const int tid = threadIdx.x, lane = tid & 31;
  const int warp = __shfl_sync(0xffffffffu, (tid >> 5) & 3, 0), wg = __shfl_sync(0xffffffffu, tid >> 7, 0);
  const int G = gridDim.x;
  const int rot = (G == 132 && blockIdx.x >= 60) ? 2 : 0;
  auto column = [&](int g) { return g + rot >= 3 ? g + rot - 3 : g + rot; };
  auto first_window = [&](int g) { const int i = blockIdx.x + column(g) * G, iy = (i * 2789) >> 17; return iy << 8 | (i - iy * 47); };
  if (tid < 32) {
    if (elect_one()) {
      mbar_init(mbar + MB_WQK, 1); mbar_init(mbar + MB_X, 1);
      fence_async();
      mbar_expect(mbar + MB_WQK, 3 * 12288);
      tma3(sb + SM_W, &tm_wqk, mbar + MB_WQK, 0, 0, 0);
      load_x_interior(&tm_x, first_window(0), 0);
#pragma unroll
      for (int i = 2; i < 13; i++) mbar_init(mbar + 8 * i, ((i >= 4 && i < 7) || i >= 9) ? 4 : 1);
      mbar_init(mbar + MB_RDY, 8);
      fence_async();
      mbar_expect(mbar + MB_WV, 3 * 6144);
      tma3(sb + SM_WV, &tm_wv, mbar + MB_WV, 0, 0, 0);
      mbar_expect(mbar + MB_WO, 18432);
      bulk_g2s(sb + SM_WOR, wo, 18432, mbar + MB_WO);
      load_x_interior(&tm_x, first_window(1), 1);
      load_x_interior(&tm_x, first_window(2), 2);
    }
    __syncwarp();
  }
  const char* mb = reinterpret_cast<const char*>(mask);

  const bool g132 = G == 132;
  uint32_t cw = 0;
  uint4 rid[4];
  if (tid >= 128) {
    const int i = tid - 128;
    if (i < 225) cw = __ldg(reinterpret_cast<const uint32_t*>(coords) + i);
  } else if (tid >= 64 && tid < 96) {
    if (lane < 12) *reinterpret_cast<uint4*>(smem + SM_PAR + 16 * lane) =
        ldg128_stream(lane < 4 ? reinterpret_cast<const uint4*>(w1) + lane : reinterpret_cast<const uint4*>(w2) + (lane - 4));
    __syncwarp();
    bar_arrive_n(BAR_PAR, 288);
  }
  const uint2 lsw = __ldg(reinterpret_cast<const uint2*>(logit_scale));
  if (tid >= 128) {
#pragma unroll
    for (int c = 0; c < 4; c++) rid[c] = ldg128_stream(reinterpret_cast<const int4*>(rel_idx) + c * 256 + (tid - 128));
  }
  if ((uint32_t)__cvta_generic_to_shared(smem) != sb) __trap();
  auto const_tiles = [&]() {
    const int i = tid & 127;
    uint8_t* vt = smem + SM_WG + wg * WG_SZ + WG_V + (i < 64 ? 3 : 10) * 1024 + (i & 63) * 16;
    *reinterpret_cast<uint4*>(vt) = make_uint4(0x3F803F80u, 0x3F803F80u, 0x3F803F80u, 0x3F803F80u);
    *reinterpret_cast<uint4*>(vt - (WG_V - WG_K)) = make_uint4(0u, 0u, 0u, 0u);
  };
  if (wg != 2) const_tiles();
  float tau[4];
  auto head_scales = [&]() {
    const float ls[4] = {bf_lo(lsw.x), bf_hi(lsw.x), bf_lo(lsw.y), bf_hi(lsw.y)};
#pragma unroll
    for (int h = 0; h < 4; h++) {
      float c;
      asm("max.NaN.f32 %0, %1, 0fC2C80000;" : "=f"(c) : "f"(ls[h]));
      asm("min.NaN.f32 %0, %0, 0f40930000;" : "+f"(c));
      tau[h] = rbf(ex2(c * LOG2E)) * LOG2E;
    }
  };
  if (wg == 0) head_scales();
  if (wg == 0 && warp == 1) {
    const int eg = lane / NENT, ei = lane - eg * NENT, sl = blockIdx.x + column(eg) * G + ei * 3 * G;
    const int w = (sl < NWIN && eg < 3) ? slot_window(sl, g132) : -1;
    const bool fast = w >= 0 && (w >> 8) != NWX - 1 && (w & 255) != NWX - 1;
    const uint32_t fm = __ballot_sync(0xffffffffu, fast);
    const int pos = __popc(((fast ? fm : ~fm) >> (eg * NENT)) & ((1u << ei) - 1));
    int ticket = 0;
#pragma unroll
    for (int g = 0; g < 3; g++) ticket += min(__popc((fm >> (g * NENT)) & ((1u << NENT) - 1)), pos + (g < eg));
    if (eg < 3) {
      *reinterpret_cast<int*>(smem + SM_WIN + lane * 4) = -1;
      *reinterpret_cast<int*>(smem + SM_GEN + lane * 4) = -1;
    }
    __syncwarp();
    if (w >= 0) *reinterpret_cast<int*>(smem + (fast ? SM_WIN : SM_GEN) + (eg * NENT + pos) * 4) = w | ticket << 16;
  }
  if (wg == 0 && warp == 3 && lane < 16) {
    const uint32_t v = (((lane >> 3) ^ lane) & 1) ? 0u : 0x3F803F80u;
    *reinterpret_cast<uint4*>(smem + SM_SEL + lane * 16) = make_uint4(v, v, v, v);
  }
  if (wg == 0) {
    if (tid == 0) *reinterpret_cast<float4*>(smem + SM_MISC) = make_float4(tau[0], tau[1], tau[2], tau[3]);
    fence_async();
    bar_arrive_n(BAR_SETUP, 384);
    bar_sync_n(BAR_AUX, 128);
  } else {
    const int i = tid - 128;
    bar_sync_n(BAR_PAR, 288);
    head_scales();

    if (i < 225) {
      const float c0 = bf_lo(cw), c1 = bf_hi(cw);
      float z[4] = {0.f, 0.f, 0.f, 0.f};
#pragma unroll
      for (int jj = 0; jj < 2; jj++) {
        const uint4 ua4 = lds128(sb + SM_PAR + 16 * jj), ub4 = lds128(sb + SM_PAR + 32 + 16 * jj);
        const uint32_t ua[4] = {ua4.x, ua4.y, ua4.z, ua4.w}, ub[4] = {ub4.x, ub4.y, ub4.z, ub4.w};
#pragma unroll
        for (int j = 0; j < 4; j++) {
          const uint4 wb = lds128(sb + SM_PAR + 64 + 64 * jj + 16 * j);
          const uint32_t hp = pack_bf16(fmaf(c1, bf_lo(ub[j]), c0 * bf_lo(ua[j])), fmaf(c1, bf_hi(ub[j]), c0 * bf_hi(ua[j])));
          float h0 = bf_lo(hp), h1 = bf_hi(hp);
          h0 = h0 > 0.f ? h0 : h0 * 0.f; h1 = h1 > 0.f ? h1 : h1 * 0.f;
          z[0] = fmaf(h0, bf_lo(wb.x), z[0]); z[1] = fmaf(h0, bf_hi(wb.x), z[1]); z[2] = fmaf(h0, bf_lo(wb.y), z[2]); z[3] = fmaf(h0, bf_hi(wb.y), z[3]);
          z[0] = fmaf(h1, bf_lo(wb.z), z[0]); z[1] = fmaf(h1, bf_hi(wb.z), z[1]); z[2] = fmaf(h1, bf_lo(wb.w), z[2]); z[3] = fmaf(h1, bf_hi(wb.w), z[3]);
        }
      }
      float e[4];
#pragma unroll
      for (int q = 0; q < 4; q++) {
        const float sh = -10.f - 0.55f * tau[q];
        e[q] = ex2(fmaf(16.f * LOG2E, rbf(rcp(1.f + ex2(-LOG2E * rbf(z[q])))), sh));
      }
      *reinterpret_cast<uint2*>(smem + SM_TAB + 8 * i) = make_uint2(pack_bf16(e[0], e[1]), pack_bf16(e[2], e[3]));
    }
    bar_sync_n(BAR_SETUP, 384);
#pragma unroll
    for (int c = 0; c < 4; c++) asm volatile("" : "+r"(rid[c].x), "+r"(rid[c].y), "+r"(rid[c].z), "+r"(rid[c].w));
    {
      const int y = (i & 15) >> 1, xh = i & 1, j = 2 * xh + (y >> 2);
      const int X = (i >> 4) & 7, Yl = (i >> 7) & 1;
      uint8_t* dst = smem + SM_EB + j * 2048 + ((X >> 2) * 64 + (Yl * 4 + (X & 3)) * 4 + 2 * (y & 1)) * 16 + ((y >> 1) & 1) * 8;
      uint2 e[16];
#pragma unroll
      for (int c = 0; c < 4; c++) {
        const uint32_t id[4] = {xh ? rid[c].z : rid[c].x, xh ? rid[c].w : rid[c].y, xh ? rid[c].x : rid[c].z, xh ? rid[c].y : rid[c].w};
#pragma unroll
        for (int q = 0; q < 4; q++) e[4 * c + q] = *reinterpret_cast<const uint2*>(smem + SM_TAB + 8 * id[q]);
      }
#pragma unroll
      for (int c = 0; c < 4; c++) {
        const uint2 a0 = e[4 * c], a1 = e[4 * c + 1], b0 = e[4 * c + 2], b1 = e[4 * c + 3];
        uint8_t* d0 = dst + (c >> 1) * 512 + (c & 1) * 4 + xh * 16;
        uint8_t* d1 = dst + (c >> 1) * 512 + (c & 1) * 4 + (xh ^ 1) * 16;
        *reinterpret_cast<uint32_t*>(d0)         = __byte_perm(a0.x, a1.x, 0x5410); *reinterpret_cast<uint32_t*>(d1)         = __byte_perm(b0.x, b1.x, 0x5410);
        *reinterpret_cast<uint32_t*>(d0 + 8192)  = __byte_perm(a0.x, a1.x, 0x7632); *reinterpret_cast<uint32_t*>(d1 + 8192)  = __byte_perm(b0.x, b1.x, 0x7632);
        *reinterpret_cast<uint32_t*>(d0 + 16384) = __byte_perm(a0.y, a1.y, 0x5410); *reinterpret_cast<uint32_t*>(d1 + 16384) = __byte_perm(b0.y, b1.y, 0x5410);
        *reinterpret_cast<uint32_t*>(d0 + 24576) = __byte_perm(a0.y, a1.y, 0x7632); *reinterpret_cast<uint32_t*>(d1 + 24576) = __byte_perm(b0.y, b1.y, 0x7632);
      }
    }
    __syncwarp();
    fence_async();
    if (elect_one()) mbar_arrive(mbar + MB_RDY);
    __syncwarp();
    bar_sync_n(BAR_TAB, 256);
    if (wg == 2) {
      mbar_wait(mbar + MB_WO, 0);
      uint4 v[9];
#pragma unroll
      for (int c = 0; c < 9; c++) v[c] = lds128(sb + SM_WOR + ((c / 3) * 32 + ((tid & 127) >> 2)) * 192 + (c % 3) * 64 + (lane & 3) * 16);
      bar_sync_n(BAR_AUX + 2, 128);
      const_tiles();
#pragma unroll
      for (int r = 0; r < 3; r++) {
        float sum = 0.f;
#pragma unroll
        for (int c = 3 * r; c < 3 * r + 3; c++)
          sum += (bf_lo(v[c].x) + bf_hi(v[c].x)) + (bf_lo(v[c].y) + bf_hi(v[c].y)) + (bf_lo(v[c].z) + bf_hi(v[c].z)) + (bf_lo(v[c].w) + bf_hi(v[c].w));
        sum += __shfl_xor_sync(0xffffffffu, sum, 1);
        sum += __shfl_xor_sync(0xffffffffu, sum, 2);
        const float mu = sum * (1.f / 96.f);
        auto cen = [&](uint32_t u) { return pack_bf16(bf_lo(u) - mu, bf_hi(u) - mu); };
        uint8_t* dst = smem + SM_WO + (r * 4 + warp) * 128 + lane * 4;
#pragma unroll
        for (int j = 0; j < 3; j++) {
          *reinterpret_cast<uint32_t*>(dst + (4 * j + 0) * 1536) = cen(v[3 * r + j].x);
          *reinterpret_cast<uint32_t*>(dst + (4 * j + 1) * 1536) = cen(v[3 * r + j].y);
          *reinterpret_cast<uint32_t*>(dst + (4 * j + 2) * 1536) = cen(v[3 * r + j].z);
          *reinterpret_cast<uint32_t*>(dst + (4 * j + 3) * 1536) = cen(v[3 * r + j].w);
        }
      }
      fence_async();
      __syncwarp();
      if (elect_one()) mbar_arrive(mbar + MB_TURN);
      __syncwarp();
    }
  }
  mbar_wait(mbar + MB_WQK, 0);
  uint32_t xpar = 0;

  uint32_t wl = sb + SM_WIN + wg * NENT * 4;
  int win = lds_uniform(wl), nxt = lds_uniform(wl + 4);
  if (win >= 0) {
    const uint32_t wgb = sb + SM_WG + wg * WG_SZ, bar_x = mbar + MB_X + 8 * wg;
    const uint32_t t16 = (tid & 127) * 16;
    const uint32_t k_dst = wgb + WG_K + (tid & 16) * 448 + warp * 256 + (tid & 15) * 16;
    const uint32_t eb_base = sb + SM_EB + t16;
    float qk[96];
    mbar_wait(bar_x, 0);
    wg_fence();
    issue_qk(qk, mk_desc(WG_X, 16, 512, 2) + (wgb >> 4), mk_desc(sb + SM_W, 12288, 1024, 1)); wg_commit();
    bool first = true;
    if (t16 == 0) prefetch_l2(mb + mask_off(win), 8192);
    __syncwarp();
    mbar_wait(mbar + MB_WV, 0);
    while (true) {
      const int nxt2 = lds_uniform(wl + 8);
      const int tk = win >> 16;
      const bool more = nxt >= 0;
      const uint32_t z0 = wl >> 20, zw = z0 + (wgb >> 4);
      const uint64_t dX = opaque(mk_desc(WG_X, 16, 512, 2) + zw);
      uint32_t qa[24];
      float q23[4]; float2 s23;
      qkv_epilogue(qk, qa, q23, s23, dX, opaque(mk_desc(sb + SM_WV, 6144, 512, 2) + z0), k_dst);
      if (__builtin_expect(first, 0)) {
        mbar_wait(mbar + MB_RDY, 0);
        first = false;
      }
      uint32_t pA[16], pB[16];
      bar_sync_n(BAR_KV + wg, 128);
      const uint64_t dK = opaque(mk_desc(WG_K, 1024, 128, 0) + zw), dV = opaque(mk_desc(WG_V, 128, 1024, 0) + zw);
      auto prefetch_next = [&]() {
        if (warp == 0) {
          if (elect_one()) {
            if (more) {
              load_x_interior(&tm_x, nxt, wg);
              prefetch_l2(mb + mask_off(nxt), 8192);
            } else {
              const int w = lds32(sb + SM_GEN + wg * NENT * 4);
              if (w >= 0) { load_x(&tm_x, &tm_xq, w, wg); prefetch_l2(mb + mask_off(w), 8192); }
              asm volatile("st.shared.u32 [%0], %1;" :: "r"(sb + SM_REQ + 4 * wg), "r"(w) : "memory");
            }
          }
          __syncwarp();
        }
      };
      auto redo = [&](int w) {
        if (elect_one()) {
          uint32_t gl = sb + SM_GEN + wg * NENT * 4, old;
          do {
            asm volatile("atom.shared.cas.b32 %0, [%1], %2, %3;" : "=r"(old) : "r"(gl), "r"(-1), "r"(w) : "memory");
            gl += 4;
          } while (old != 0xFFFFFFFFu && old != (uint32_t)w);
        }
        __syncwarp();
      };
      auto wait_turn = [&]() { mbar_wait(mbar + MB_TURN + (tk & 3) * 8, (tk >> 2) & 1); };
      auto pass_turn = [&](uint32_t after) {
        asm volatile("{\n.reg .pred p, q;\nelect.sync _|p, 0xffffffff;\nsetp.ne.and.s32 q, %1, -1, p;\n"
                     "@q mbarrier.arrive.shared::cta.b64 _, [%0];\n}\n"
                     :: "r"(mbar + MB_TURN + ((tk + 1) & 3) * 8), "r"(after) : "memory");
      };
      auto next_qk = [&]() { issue_qk(qk, dX, opaque(mk_desc(sb + SM_W, 12288, 1024, 1) + z0)); wg_commit(); };
      auto tiles_ready = [&]() {
        if (elect_one()) mbar_arrive(bar_x + (MB_KV - MB_X));
        __syncwarp();
        const uint32_t par = (wl >> 2) & 1;
        mbar_wait(bar_x, par ^ 1);
        mbar_wait(bar_x + (MB_KV - MB_X), par);
      };
      uint32_t of[24], bad;
      uint4 mw[4];
      {
        float sA[32], sB[32], oA[16], oB[16], oC[16], oD[16];
        uint32_t pC[16], pD[16];
        wg_fence();
        issue_s<0>(sA, qa, dK);
        issue_s<1>(sB, qa, dK); wg_commit();
        prefetch_next();
        load_eb(pA, eb_base);
        wait_turn();
        wg_wait<0>(); fence_regs(sA); fence_regs(sB);
        load_eb<8192>(pB, eb_base);
        fence_regs(q23);
        scale_pair(qa + 12, q23, s23.x, s23.y);
        softmax_fast(sA, pA);
        wg_fence();
        issue_s<2>(sA, qa, dK); wg_commit();
        issue_pv<0>(oA, pA, dV); wg_commit();
        softmax_fast(sB, pB);
        load_eb<16384>(pC, eb_base);
        wg_wait<1>(); fence_regs(sA);
        wg_fence();
        issue_s<3>(sB, qa, dK); wg_commit();
        issue_pv<1>(oB, pB, dV); wg_commit();
        softmax_fast(sA, pC);
        load_eb<24576>(pD, eb_base);
        wg_wait<1>(); fence_regs(sB); fence_regs(oA);
        wg_fence();
        issue_pv<2>(oC, pC, dV); wg_commit();
        bad = norm_o<0>(oA, of);
        wg_wait<1>(); fence_regs(oB);
        bad |= norm_o<1>(oB, of + 6);
        softmax_fast(sB, pD);
        pass_turn(pD[3]);
        wg_fence();
        issue_pv<3>(oD, pD, dV); wg_commit();
        {
          const char* src = mb + (mask_off(win) + (warp & 1) * 3584 - (warp >> 1) * 512 + (t16 ^ (pD[15] >> 31 << 4)));
#pragma unroll
          for (int i = 0; i < 4; i++) mw[i] = ldg128_stream(src + i * 1024);
        }
        wg_wait<1>(); fence_regs(oC);
        bad |= norm_o<0>(oC, of + 12);
        wg_wait<0>(); fence_regs(oD);
        bad |= norm_o<1>(oD, of + 18);
      }
      float y[48], var[4]; uint32_t yb[24];
      issue_out(y, of, opaque(mk_desc(sb + SM_WO, 128, 1536, 0) + z0));
      char* const optr = out_ptr(out, win, warp, t16);
      auto verify = [&](uint32_t seed) {
        uint32_t r = seed & 0x80008000u;
#pragma unroll
        for (int i = 0; i < 4; i++) {
          asm("lop3.b32 %0, %0, %1, %2, 0xFE;" : "+r"(r) : "r"(mw[i].x), "r"(mw[i].y));
          asm("lop3.b32 %0, %0, %1, %2, 0xFE;" : "+r"(r) : "r"(mw[i].z), "r"(mw[i].w));
        }
        if (__builtin_expect(__any_sync(0xffffffffu, ((r & 0x7FFF7FFFu) | (bad & 0x40004000u)) != 0u), 0)) redo(win);
      };
      if (!more) { ln_head(y, yb, var, dV + 3 * 64); wg_wait<0>(); verify(ln_tail(yb, var, optr)); break; }
      tiles_ready();
      ln_head(y, yb, var, dV + 3 * 64);
      next_qk();
      wg_wait<1>();
      const uint32_t last = ln_tail(yb, var, optr);
      wg_wait<0>();
      verify(last);
      wl += 4;
      win = nxt; nxt = nxt2;
    }
    xpar = ((wl >> 2) & 1) ^ 1;
    bar_sync_n(BAR_AUX + wg, 128);
    if (warp == 0 && elect_one()) {
      const int w = lds32(sb + SM_GEN + wg * NENT * 4);
      if (w >= 0 && (int)lds32(sb + SM_REQ + 4 * wg) < 0) load_x(&tm_x, &tm_xq, w, wg);
    }
    __syncwarp();
  }
  general_windows(&tm_x, &tm_xq, mb, out, xpar);
}

typedef CUresult (*EncodeFn)(CUtensorMap*, CUtensorMapDataType, cuuint32_t, void*, const cuuint64_t*, const cuuint64_t*,
                             const cuuint32_t*, const cuuint32_t*, CUtensorMapInterleave, CUtensorMapSwizzle,
                             CUtensorMapL2promotion, CUtensorMapFloatOOBfill);

}

extern "C" void kernel_launch(void* const* d_in, const int* in_sizes, int n_in, void* d_out, int out_size) {
  static int sms = 0;
  static EncodeFn encode = nullptr;
  if (sms == 0) {
    int dev = 0;
    cudaGetDevice(&dev);
    cudaDeviceGetAttribute(&sms, cudaDevAttrMultiProcessorCount, dev);
    if (sms < 96) sms = 96;
    if (sms > 512) sms = 512;
    cudaFuncSetAttribute(swin_kernel, cudaFuncAttributeMaxDynamicSharedMemorySize, SM_TOTAL);
    cudaDriverEntryPointQueryResult qr;
    void* fn = nullptr;
    cudaGetDriverEntryPoint("cuTensorMapEncodeTiled", &fn, cudaEnableDefault, &qr);
    encode = (EncodeFn)fn;
  }
  CUtensorMap tm_x, tm_xq, tm_wqk, tm_wv;
  {
    cuuint64_t dims[5] = {32, 4, IMG, IMG / 4, 3};
    cuuint64_t strides[4] = {PIXB, ROWB, 4 * PIXB, 64};
    cuuint32_t es[5] = {1, 1, 1, 1, 1};
    cuuint32_t box[5] = {32, 4, 8, 2, 3}, boxq[5] = {32, 4, 4, 1, 1};
    encode(&tm_x, CU_TENSOR_MAP_DATA_TYPE_BFLOAT16, 5, d_in[0], dims, strides, box, es, CU_TENSOR_MAP_INTERLEAVE_NONE,
           CU_TENSOR_MAP_SWIZZLE_64B, CU_TENSOR_MAP_L2_PROMOTION_L2_128B, CU_TENSOR_MAP_FLOAT_OOB_FILL_NONE);
    encode(&tm_xq, CU_TENSOR_MAP_DATA_TYPE_BFLOAT16, 5, d_in[0], dims, strides, boxq, es, CU_TENSOR_MAP_INTERLEAVE_NONE,
           CU_TENSOR_MAP_SWIZZLE_64B, CU_TENSOR_MAP_L2_PROMOTION_L2_128B, CU_TENSOR_MAP_FLOAT_OOB_FILL_NONE);
    cuuint64_t qd[3] = {64, 96, 3}, qs[2] = {576, 128}, vd[3] = {32, 96, 3}, vs[2] = {576, 64};
    cuuint32_t qb[3] = {64, 96, 3}, vb[3] = {32, 96, 3};
    encode(&tm_wqk, CU_TENSOR_MAP_DATA_TYPE_BFLOAT16, 3, d_in[1], qd, qs, qb, es, CU_TENSOR_MAP_INTERLEAVE_NONE,
           CU_TENSOR_MAP_SWIZZLE_128B, CU_TENSOR_MAP_L2_PROMOTION_L2_256B, CU_TENSOR_MAP_FLOAT_OOB_FILL_NONE);
    encode(&tm_wv, CU_TENSOR_MAP_DATA_TYPE_BFLOAT16, 3, (char*)d_in[1] + 384, vd, vs, vb, es, CU_TENSOR_MAP_INTERLEAVE_NONE,
           CU_TENSOR_MAP_SWIZZLE_64B, CU_TENSOR_MAP_L2_PROMOTION_L2_256B, CU_TENSOR_MAP_FLOAT_OOB_FILL_NONE);
  }
  swin_kernel<<<sms, 384, SM_TOTAL>>>(
      (const __nv_bfloat16*)d_in[3], (const __nv_bfloat16*)d_in[4], (const __nv_bfloat16*)d_in[5], (const __nv_bfloat16*)d_in[6],
      (const int*)d_in[7], (const __nv_bfloat16*)d_in[2], (const __nv_bfloat16*)d_in[8], (__nv_bfloat16*)d_out,
      tm_wqk, tm_x, tm_wv, tm_xq);
}
```
